```python
import torch

def _softmax(x, axis=-1):
    return torch.softmax(x, dim=axis)
def _gelu(x):
    return torch.nn.functional.gelu(x, approximate="tanh")
def _silu(x):
    return torch.nn.functional.silu(x)
def _sigmoid(x):
    return torch.sigmoid(x)
def _layernorm(x, axis=-1, eps=1e-5):
    m = x.mean(dim=axis, keepdim=True)
    v = x.var(dim=axis, keepdim=True, unbiased=False)
    return (x - m) / torch.sqrt(v + eps)
def _scatter_add(tgt, idx, src, axis=0):
    return tgt.clone().index_add_(axis, idx, src)
def _segment_sum(src, seg, n):
    out = torch.zeros((n,) + src.shape[1:], dtype=src.dtype)
    return out.index_add_(0, seg, src)
def _pad(x, pw):
    flat = tuple(v for pair in reversed(pw) for v in pair)
    return torch.nn.functional.pad(x, flat)

kernel_name = 'interleave_layers__sliding_local_dilated__glu_gated_swiglu__prompt'

def setup_inputs():

    _w = (lambda a: (lambda t: t.to(torch.bfloat16) if t.is_floating_point() else t)(torch.as_tensor(a)))
    def _A_setup():
        B, S, D = 1, 2048, 1024
        return {
            "x": _w((lambda *s: torch.randn(*s, dtype=torch.bfloat16) * 0.05)(B, S, D)),
            "wqkv": _w((lambda *s: torch.randn(*s, dtype=torch.bfloat16) * 0.05)(D, 3 * D)),
            "wo": _w((lambda *s: torch.randn(*s, dtype=torch.bfloat16) * 0.05)(D, D)),
        }
    _A_in = _A_setup()

    def _B_setup():
        B, S, D, F = 1, 2048, 1024, 3584
        return {
            "x": _w((lambda *s: torch.randn(*s, dtype=torch.bfloat16) * 0.05)(B, S, D)),
            "w1": _w((lambda *s: torch.randn(*s, dtype=torch.bfloat16) * 0.8)(D, F) * (2.0 / D) ** 0.5),
            "w3": _w((lambda *s: torch.randn(*s, dtype=torch.bfloat16) * 0.8)(D, F) * (2.0 / D) ** 0.5),
            "w2": _w((lambda *s: torch.randn(*s, dtype=torch.bfloat16) * 0.8)(F, D) * (2.0 / F) ** 0.5),
        }
    _B_in = _B_setup()

    return {
        "A_x": _A_in["x"],
        "A_wqkv": _A_in["wqkv"],
        "A_wo": _A_in["wo"],
        "B_x": _B_in["x"],
        "B_w1": _B_in["w1"],
        "B_w3": _B_in["w3"],
        "B_w2": _B_in["w2"],
    }

def reference(A_x, A_wqkv, A_wo, B_x, B_w1, B_w3, B_w2):
    def _A_ref(x, wqkv, wo):
        B, S, D = x.shape
        H = 32; Dh = D // H
        W, dil = 8, 2
        qkv = (lambda x, *d: x.permute(*d))((x @ wqkv).reshape(B, S, 3, H, Dh), 2, 0, 3, 1, 4)
        q, k, v = qkv[0], qkv[1], qkv[2]
        scale = Dh ** -0.5
        pos = torch.arange(S)
        off = torch.arange(W) * dil
        idx = pos[:, None] - off[None, :]
        mask = idx >= 0
        idx_c = torch.where(mask, idx, 0).reshape(-1)
        kg = k[:, :, idx_c, :].reshape(B, H, S, W, Dh)
        vg = v[:, :, idx_c, :].reshape(B, H, S, W, Dh)
        logits = torch.einsum("bhsd,bhswd->bhsw", q, kg) * scale
        logits = torch.where(mask[None, None, :, :], logits, -1e9)
        attn = _softmax(logits, axis=-1)
        o = torch.einsum("bhsw,bhswd->bhsd", attn, vg)
        return (lambda x, *d: x.permute(*d))(o, 0, 2, 1, 3).reshape(B, S, D) @ wo

    def _B_ref(x, w1, w3, w2):
        gate = torch.einsum("bsd,df->bsf", x, w1)
        up = torch.einsum("bsd,df->bsf", x, w3)
        h = _silu(gate) * up
        out = torch.einsum("bsf,fd->bsd", h, w2)
        return out

    x = A_x
    x = x + _A_ref(_layernorm(x, axis=-1), A_wqkv, A_wo)
    x = x + _B_ref(_layernorm(x, axis=-1), B_w1, B_w3, B_w2)
    x = x + _A_ref(_layernorm(x, axis=-1), A_wqkv, A_wo)
    x = x + _B_ref(_layernorm(x, axis=-1), B_w1, B_w3, B_w2)
    return x
```

```cpp
#include <cuda_runtime.h>
#include <cuda_bf16.h>
#include <cuda.h>
#include <stdint.h>

namespace {

constexpr int SEQ = 2048, DM = 1024, FF = 3584;
constexpr int NCS = 3 * DM + 2 * FF;
constexpr float LN_EPS = 1e-5f;
constexpr float LOG2E = 1.4426950408889634f;

__device__ __align__(1024) __nv_bfloat16 g_act[3 * SEQ * DM];
__device__ __align__(1024) __nv_bfloat16 g_h[SEQ * FF];
__device__ __align__(128) uint4 g_stats[4 * 16 * 128 * 8];
__device__ __align__(128) uint2 g_cs[NCS];
__device__ __align__(128) uint4 g_halo[4 * 16 * 8 * 8 * 32];
__device__ __align__(128) uint32_t g_flags[16 * 16 * 16];
__device__ uint32_t g_epoch[256];

enum { M_XIN, M_ACT_LD, M_ACT_ST, M_H_LD, M_H_ST, M_OUT_ST, M_WQKV, M_WO, M_W13, M_W13H, M_W2, M_COUNT };
struct alignas(64) Params {
  CUtensorMap map[M_COUNT];
  const __nv_bfloat16* xin;
  int use_smid;
  int w13_swapped;
  uint8_t role[136];
};

constexpr uint32_t PAGE = 16384, NPAGE = 12;
constexpr uint32_t SM_STAGE = NPAGE * PAGE;
constexpr uint32_t SM_BAR = SM_STAGE + 2 * PAGE;
constexpr uint32_t SM_CS = SM_BAR + 256;
constexpr uint32_t SM_TOTAL = SM_CS + 2048;
constexpr uint32_t BAR_FULL = SM_BAR, BAR_EMPTY = SM_BAR + 64, BAR_SFULL = SM_BAR + 128, BAR_SEMPTY = SM_BAR + 144;

__device__ __forceinline__ uint32_t smem_u32(const void* p) { return (uint32_t)__cvta_generic_to_shared(p); }
__device__ __forceinline__ void mbar_init(uint32_t bar, uint32_t cnt) { asm volatile("mbarrier.init.shared::cta.b64 [%0], %1;" :: "r"(bar), "r"(cnt)); }
__device__ __forceinline__ void mbar_expect_tx(uint32_t bar, uint32_t bytes) { asm volatile("mbarrier.arrive.expect_tx.shared::cta.b64 _, [%0], %1;" :: "r"(bar), "r"(bytes) : "memory"); }
__device__ __forceinline__ void mbar_arrive(uint32_t bar) { asm volatile("mbarrier.arrive.shared::cta.b64 _, [%0];" :: "r"(bar) : "memory"); }
__device__ __forceinline__ void mbar_wait(uint32_t bar, uint32_t parity) {
  asm volatile("{\n.reg .pred p;\n.reg .u32 n;\nmov.u32 n, 0;\nLAB_WAIT:\n"
               "mbarrier.try_wait.parity.shared::cta.b64 p, [%0], %1;\n@p bra LAB_DONE;\n"
               "add.u32 n, n, 1;\nsetp.lt.u32 p, n, 4194304;\n@p bra LAB_WAIT;\ntrap;\nLAB_DONE:\n}" :: "r"(bar), "r"(parity) : "memory");
}
__device__ __forceinline__ void spin_check(uint32_t n) { asm volatile("{\n.reg .pred p;\nsetp.ge.u32 p, %0, 4194304;\n@p st.volatile.global.u32 [%1], %0;\n}" :: "r"(n), "l"(0ull)); }
__device__ __forceinline__ void tma_ld2(uint32_t dst, const CUtensorMap* m, uint32_t bar, int c0, int c1) {
  asm volatile("cp.async.bulk.tensor.2d.shared::cluster.global.mbarrier::complete_tx::bytes [%0], [%1, {%3, %4}], [%2];" :: "r"(dst), "l"(m), "r"(bar), "r"(c0), "r"(c1) : "memory");
}
__device__ __forceinline__ void tma_ld3(uint32_t dst, const CUtensorMap* m, uint32_t bar, int c0, int c1, int c2) {
  asm volatile("cp.async.bulk.tensor.3d.shared::cluster.global.mbarrier::complete_tx::bytes [%0], [%1, {%3, %4, %5}], [%2];" :: "r"(dst), "l"(m), "r"(bar), "r"(c0), "r"(c1), "r"(c2) : "memory");
}
__device__ __forceinline__ void tma_ld4(uint32_t dst, const CUtensorMap* m, uint32_t bar, int c0, int c1, int c2, int c3) {
  asm volatile("cp.async.bulk.tensor.4d.shared::cluster.global.mbarrier::complete_tx::bytes [%0], [%1, {%3, %4, %5, %6}], [%2];" :: "r"(dst), "l"(m), "r"(bar), "r"(c0), "r"(c1), "r"(c2), "r"(c3) : "memory");
}
__device__ __forceinline__ void tma_st2(const CUtensorMap* m, uint32_t src, int c0, int c1) {
  asm volatile("cp.async.bulk.tensor.2d.global.shared::cta.bulk_group [%0, {%2, %3}], [%1];" :: "l"(m), "r"(src), "r"(c0), "r"(c1) : "memory");
}
__device__ __forceinline__ void tma_st3(const CUtensorMap* m, uint32_t src, int c0, int c1, int c2) {
  asm volatile("cp.async.bulk.tensor.3d.global.shared::cta.bulk_group [%0, {%2, %3, %4}], [%1];" :: "l"(m), "r"(src), "r"(c0), "r"(c1), "r"(c2) : "memory");
}
__device__ __forceinline__ void bulk_commit() { asm volatile("cp.async.bulk.commit_group;" ::: "memory"); }
__device__ __forceinline__ void bulk_wait_read() { asm volatile("cp.async.bulk.wait_group.read 0;" ::: "memory"); }
__device__ __forceinline__ void bulk_wait_all() { asm volatile("cp.async.bulk.wait_group 0;" ::: "memory"); }
__device__ __forceinline__ void fence_async_smem() { asm volatile("fence.proxy.async.shared::cta;" ::: "memory"); }
__device__ __forceinline__ void fence_async_all() { asm volatile("fence.proxy.async;" ::: "memory"); }
__device__ __forceinline__ void wgmma_fence() { asm volatile("wgmma.fence.sync.aligned;" ::: "memory"); }
__device__ __forceinline__ void wgmma_commit() { asm volatile("wgmma.commit_group.sync.aligned;" ::: "memory"); }
template <int N> __device__ __forceinline__ void wgmma_wait() { asm volatile("wgmma.wait_group.sync.aligned %0;" :: "n"(N) : "memory"); }
__device__ __forceinline__ uint64_t make_desc(uint32_t addr, uint32_t lbo, uint32_t sbo) {
  return (uint64_t)((addr & 0x3FFFF) >> 4) | ((uint64_t)(lbo >> 4) << 16) | ((uint64_t)(sbo >> 4) << 32) | (1ull << 62);
}
__device__ __forceinline__ void bar_sync(int id, int n) { asm volatile("bar.sync %0, %1;" :: "r"(id), "r"(n) : "memory"); }
__device__ __forceinline__ void bar_arrive(int id, int n) { asm volatile("bar.arrive %0, %1;" :: "r"(id), "r"(n) : "memory"); }
__device__ __forceinline__ uint32_t pack_bf16(float lo, float hi) { uint32_t r; asm("cvt.rn.bf16x2.f32 %0, %1, %2;" : "=r"(r) : "f"(hi), "f"(lo)); return r; }
__device__ __forceinline__ float bf_lo(uint32_t v) { return __uint_as_float(v << 16); }
__device__ __forceinline__ float bf_hi(uint32_t v) { return __uint_as_float(v & 0xffff0000u); }
__device__ __forceinline__ float ex2(float x) { float r; asm("ex2.approx.ftz.f32 %0, %1;" : "=f"(r) : "f"(x)); return r; }
__device__ __forceinline__ float rcp(float x) { float r; asm("rcp.approx.ftz.f32 %0, %1;" : "=f"(r) : "f"(x)); return r; }
__device__ __forceinline__ void stsm4(uint32_t a, uint32_t r0, uint32_t r1, uint32_t r2, uint32_t r3) {
  asm volatile("stmatrix.sync.aligned.m8n8.x4.shared.b16 [%0], {%1, %2, %3, %4};" :: "r"(a), "r"(r0), "r"(r1), "r"(r2), "r"(r3) : "memory");
}
__device__ __forceinline__ void ldsm4(uint32_t a, uint32_t& r0, uint32_t& r1, uint32_t& r2, uint32_t& r3) {
  asm volatile("ldmatrix.sync.aligned.m8n8.x4.shared.b16 {%0, %1, %2, %3}, [%4];" : "=r"(r0), "=r"(r1), "=r"(r2), "=r"(r3) : "r"(a) : "memory");
}
__device__ __forceinline__ void ldsm4t(uint32_t a, uint32_t& r0, uint32_t& r1, uint32_t& r2, uint32_t& r3) {
  asm volatile("ldmatrix.sync.aligned.m8n8.x4.trans.shared.b16 {%0, %1, %2, %3}, [%4];" : "=r"(r0), "=r"(r1), "=r"(r2), "=r"(r3) : "r"(a) : "memory");
}
__device__ __forceinline__ uint32_t movm(uint32_t v) { uint32_t r; asm volatile("movmatrix.sync.aligned.m8n8.trans.b16 %0, %1;" : "=r"(r) : "r"(v)); return r; }
__device__ __forceinline__ void sts128(uint32_t a, uint32_t r0, uint32_t r1, uint32_t r2, uint32_t r3) {
  asm volatile("st.shared.v4.b32 [%0], {%1, %2, %3, %4};" :: "r"(a), "r"(r0), "r"(r1), "r"(r2), "r"(r3) : "memory");
}
__device__ __forceinline__ void lds128(uint32_t a, uint32_t& r0, uint32_t& r1, uint32_t& r2, uint32_t& r3) {
  asm volatile("ld.shared.v4.b32 {%0, %1, %2, %3}, [%4];" : "=r"(r0), "=r"(r1), "=r"(r2), "=r"(r3) : "r"(a) : "memory");
}
__device__ __forceinline__ float2 lds64f(uint32_t a) { float2 r; asm volatile("ld.shared.v2.f32 {%0, %1}, [%2];" : "=f"(r.x), "=f"(r.y) : "r"(a) : "memory"); return r; }
__device__ __forceinline__ void sts32f(uint32_t a, float v) { asm volatile("st.shared.f32 [%0], %1;" :: "r"(a), "f"(v) : "memory"); }
__device__ __forceinline__ void mma16816(float (&c)[4], uint32_t a0, uint32_t a1, uint32_t a2, uint32_t a3, uint32_t b0, uint32_t b1) {
  asm volatile("mma.sync.aligned.m16n8k16.row.col.f32.bf16.bf16.f32 {%0, %1, %2, %3}, {%4, %5, %6, %7}, {%8, %9}, {%0, %1, %2, %3};"
               : "+f"(c[0]), "+f"(c[1]), "+f"(c[2]), "+f"(c[3]) : "r"(a0), "r"(a1), "r"(a2), "r"(a3), "r"(b0), "r"(b1));
}
__device__ __forceinline__ void mma1688(float (&c)[4], uint32_t a0, uint32_t a1, uint32_t b0) {
  asm volatile("mma.sync.aligned.m16n8k8.row.col.f32.bf16.bf16.f32 {%0, %1, %2, %3}, {%4, %5}, {%6}, {%0, %1, %2, %3};"
               : "+f"(c[0]), "+f"(c[1]), "+f"(c[2]), "+f"(c[3]) : "r"(a0), "r"(a1), "r"(b0));
}
__device__ __forceinline__ void ll_store(uint4* p, uint32_t a, uint32_t b, uint32_t tag) {
  asm volatile("st.relaxed.gpu.global.v2.b64 [%0], {%1, %2};" :: "l"(p), "l"((uint64_t)a | ((uint64_t)tag << 32)), "l"((uint64_t)b | ((uint64_t)tag << 32)) : "memory");
}
__device__ __forceinline__ uint4 ll_load(const uint4* p) {
  uint64_t a, b;
  asm volatile("ld.relaxed.gpu.global.v2.b64 {%0, %1}, [%2];" : "=l"(a), "=l"(b) : "l"(p) : "memory");
  return make_uint4((uint32_t)a, (uint32_t)(a >> 32), (uint32_t)b, (uint32_t)(b >> 32));
}
__device__ __forceinline__ uint2 ll_load2(const uint2* p) {
  uint64_t a;
  asm volatile("ld.relaxed.gpu.global.b64 %0, [%1];" : "=l"(a) : "l"(p) : "memory");
  return make_uint2((uint32_t)a, (uint32_t)(a >> 32));
}
template <typename T> __device__ __forceinline__ T* ptr_add(T* p, uint32_t bytes) {
  uint64_t r;
  asm("{\n.reg .u32 lo, hi;\nmov.b64 {lo, hi}, %1;\nadd.cc.u32 lo, lo, %2;\naddc.u32 hi, hi, 0;\nmov.b64 %0, {lo, hi};\n}" : "=l"(r) : "l"(p), "r"(bytes));
  return (T*)r;
}
#define TL(who, slot) do {} while (0)

__device__ __forceinline__ void wgmma_n128(float (&d)[64], uint64_t da, uint64_t db, int scale_d) {
  asm volatile("{\n.reg .pred p;\nsetp.ne.b32 p, %66, 0;\n"
    "wgmma.mma_async.sync.aligned.m64n128k16.f32.bf16.bf16 "
    "{%0, %1, %2, %3, %4, %5, %6, %7, %8, %9, %10, %11, %12, %13, %14, %15, "
    "%16, %17, %18, %19, %20, %21, %22, %23, %24, %25, %26, %27, %28, %29, %30, %31, "
    "%32, %33, %34, %35, %36, %37, %38, %39, %40, %41, %42, %43, %44, %45, %46, %47, "
    "%48, %49, %50, %51, %52, %53, %54, %55, %56, %57, %58, %59, %60, %61, %62, %63}, "
    "%64, %65, p, 1, 1, 0, 1;\n}\n"
    : "+f"(d[0]), "+f"(d[1]), "+f"(d[2]), "+f"(d[3]), "+f"(d[4]), "+f"(d[5]), "+f"(d[6]), "+f"(d[7]),
      "+f"(d[8]), "+f"(d[9]), "+f"(d[10]), "+f"(d[11]), "+f"(d[12]), "+f"(d[13]), "+f"(d[14]), "+f"(d[15]),
      "+f"(d[16]), "+f"(d[17]), "+f"(d[18]), "+f"(d[19]), "+f"(d[20]), "+f"(d[21]), "+f"(d[22]), "+f"(d[23]),
      "+f"(d[24]), "+f"(d[25]), "+f"(d[26]), "+f"(d[27]), "+f"(d[28]), "+f"(d[29]), "+f"(d[30]), "+f"(d[31]),
      "+f"(d[32]), "+f"(d[33]), "+f"(d[34]), "+f"(d[35]), "+f"(d[36]), "+f"(d[37]), "+f"(d[38]), "+f"(d[39]),
      "+f"(d[40]), "+f"(d[41]), "+f"(d[42]), "+f"(d[43]), "+f"(d[44]), "+f"(d[45]), "+f"(d[46]), "+f"(d[47]),
      "+f"(d[48]), "+f"(d[49]), "+f"(d[50]), "+f"(d[51]), "+f"(d[52]), "+f"(d[53]), "+f"(d[54]), "+f"(d[55]),
      "+f"(d[56]), "+f"(d[57]), "+f"(d[58]), "+f"(d[59]), "+f"(d[60]), "+f"(d[61]), "+f"(d[62]), "+f"(d[63])
    : "l"(da), "l"(db), "r"(scale_d));
}
__device__ __forceinline__ void wgmma_n192(float (&d)[96], uint64_t da, uint64_t db, int scale_d) {
  asm volatile("{\n.reg .pred p;\nsetp.ne.b32 p, %98, 0;\n"
    "wgmma.mma_async.sync.aligned.m64n192k16.f32.bf16.bf16 "
    "{%0, %1, %2, %3, %4, %5, %6, %7, %8, %9, %10, %11, %12, %13, %14, %15, "
    "%16, %17, %18, %19, %20, %21, %22, %23, %24, %25, %26, %27, %28, %29, %30, %31, "
    "%32, %33, %34, %35, %36, %37, %38, %39, %40, %41, %42, %43, %44, %45, %46, %47, "
    "%48, %49, %50, %51, %52, %53, %54, %55, %56, %57, %58, %59, %60, %61, %62, %63, "
    "%64, %65, %66, %67, %68, %69, %70, %71, %72, %73, %74, %75, %76, %77, %78, %79, "
    "%80, %81, %82, %83, %84, %85, %86, %87, %88, %89, %90, %91, %92, %93, %94, %95}, "
    "%96, %97, p, 1, 1, 0, 1;\n}\n"
    : "+f"(d[0]), "+f"(d[1]), "+f"(d[2]), "+f"(d[3]), "+f"(d[4]), "+f"(d[5]), "+f"(d[6]), "+f"(d[7]),
      "+f"(d[8]), "+f"(d[9]), "+f"(d[10]), "+f"(d[11]), "+f"(d[12]), "+f"(d[13]), "+f"(d[14]), "+f"(d[15]),
      "+f"(d[16]), "+f"(d[17]), "+f"(d[18]), "+f"(d[19]), "+f"(d[20]), "+f"(d[21]), "+f"(d[22]), "+f"(d[23]),
      "+f"(d[24]), "+f"(d[25]), "+f"(d[26]), "+f"(d[27]), "+f"(d[28]), "+f"(d[29]), "+f"(d[30]), "+f"(d[31]),
      "+f"(d[32]), "+f"(d[33]), "+f"(d[34]), "+f"(d[35]), "+f"(d[36]), "+f"(d[37]), "+f"(d[38]), "+f"(d[39]),
      "+f"(d[40]), "+f"(d[41]), "+f"(d[42]), "+f"(d[43]), "+f"(d[44]), "+f"(d[45]), "+f"(d[46]), "+f"(d[47]),
      "+f"(d[48]), "+f"(d[49]), "+f"(d[50]), "+f"(d[51]), "+f"(d[52]), "+f"(d[53]), "+f"(d[54]), "+f"(d[55]),
      "+f"(d[56]), "+f"(d[57]), "+f"(d[58]), "+f"(d[59]), "+f"(d[60]), "+f"(d[61]), "+f"(d[62]), "+f"(d[63]),
      "+f"(d[64]), "+f"(d[65]), "+f"(d[66]), "+f"(d[67]), "+f"(d[68]), "+f"(d[69]), "+f"(d[70]), "+f"(d[71]),
      "+f"(d[72]), "+f"(d[73]), "+f"(d[74]), "+f"(d[75]), "+f"(d[76]), "+f"(d[77]), "+f"(d[78]), "+f"(d[79]),
      "+f"(d[80]), "+f"(d[81]), "+f"(d[82]), "+f"(d[83]), "+f"(d[84]), "+f"(d[85]), "+f"(d[86]), "+f"(d[87]),
      "+f"(d[88]), "+f"(d[89]), "+f"(d[90]), "+f"(d[91]), "+f"(d[92]), "+f"(d[93]), "+f"(d[94]), "+f"(d[95])
    : "l"(da), "l"(db), "r"(scale_d));
}
__device__ __forceinline__ void wgmma_n256(float (&d)[128], uint64_t da, uint64_t db, int scale_d) {
  asm volatile("{\n.reg .pred p;\nsetp.ne.b32 p, %130, 0;\n"
    "wgmma.mma_async.sync.aligned.m64n256k16.f32.bf16.bf16 "
    "{%0, %1, %2, %3, %4, %5, %6, %7, %8, %9, %10, %11, %12, %13, %14, %15, "
    "%16, %17, %18, %19, %20, %21, %22, %23, %24, %25, %26, %27, %28, %29, %30, %31, "
    "%32, %33, %34, %35, %36, %37, %38, %39, %40, %41, %42, %43, %44, %45, %46, %47, "
    "%48, %49, %50, %51, %52, %53, %54, %55, %56, %57, %58, %59, %60, %61, %62, %63, "
    "%64, %65, %66, %67, %68, %69, %70, %71, %72, %73, %74, %75, %76, %77, %78, %79, "
    "%80, %81, %82, %83, %84, %85, %86, %87, %88, %89, %90, %91, %92, %93, %94, %95, "
    "%96, %97, %98, %99, %100, %101, %102, %103, %104, %105, %106, %107, %108, %109, %110, %111, "
    "%112, %113, %114, %115, %116, %117, %118, %119, %120, %121, %122, %123, %124, %125, %126, %127}, "
    "%128, %129, p, 1, 1, 0, 1;\n}\n"
    : "+f"(d[0]), "+f"(d[1]), "+f"(d[2]), "+f"(d[3]), "+f"(d[4]), "+f"(d[5]), "+f"(d[6]), "+f"(d[7]),
      "+f"(d[8]), "+f"(d[9]), "+f"(d[10]), "+f"(d[11]), "+f"(d[12]), "+f"(d[13]), "+f"(d[14]), "+f"(d[15]),
      "+f"(d[16]), "+f"(d[17]), "+f"(d[18]), "+f"(d[19]), "+f"(d[20]), "+f"(d[21]), "+f"(d[22]), "+f"(d[23]),
      "+f"(d[24]), "+f"(d[25]), "+f"(d[26]), "+f"(d[27]), "+f"(d[28]), "+f"(d[29]), "+f"(d[30]), "+f"(d[31]),
      "+f"(d[32]), "+f"(d[33]), "+f"(d[34]), "+f"(d[35]), "+f"(d[36]), "+f"(d[37]), "+f"(d[38]), "+f"(d[39]),
      "+f"(d[40]), "+f"(d[41]), "+f"(d[42]), "+f"(d[43]), "+f"(d[44]), "+f"(d[45]), "+f"(d[46]), "+f"(d[47]),
      "+f"(d[48]), "+f"(d[49]), "+f"(d[50]), "+f"(d[51]), "+f"(d[52]), "+f"(d[53]), "+f"(d[54]), "+f"(d[55]),
      "+f"(d[56]), "+f"(d[57]), "+f"(d[58]), "+f"(d[59]), "+f"(d[60]), "+f"(d[61]), "+f"(d[62]), "+f"(d[63]),
      "+f"(d[64]), "+f"(d[65]), "+f"(d[66]), "+f"(d[67]), "+f"(d[68]), "+f"(d[69]), "+f"(d[70]), "+f"(d[71]),
      "+f"(d[72]), "+f"(d[73]), "+f"(d[74]), "+f"(d[75]), "+f"(d[76]), "+f"(d[77]), "+f"(d[78]), "+f"(d[79]),
      "+f"(d[80]), "+f"(d[81]), "+f"(d[82]), "+f"(d[83]), "+f"(d[84]), "+f"(d[85]), "+f"(d[86]), "+f"(d[87]),
      "+f"(d[88]), "+f"(d[89]), "+f"(d[90]), "+f"(d[91]), "+f"(d[92]), "+f"(d[93]), "+f"(d[94]), "+f"(d[95]),
      "+f"(d[96]), "+f"(d[97]), "+f"(d[98]), "+f"(d[99]), "+f"(d[100]), "+f"(d[101]), "+f"(d[102]), "+f"(d[103]),
      "+f"(d[104]), "+f"(d[105]), "+f"(d[106]), "+f"(d[107]), "+f"(d[108]), "+f"(d[109]), "+f"(d[110]), "+f"(d[111]),
      "+f"(d[112]), "+f"(d[113]), "+f"(d[114]), "+f"(d[115]), "+f"(d[116]), "+f"(d[117]), "+f"(d[118]), "+f"(d[119]),
      "+f"(d[120]), "+f"(d[121]), "+f"(d[122]), "+f"(d[123]), "+f"(d[124]), "+f"(d[125]), "+f"(d[126]), "+f"(d[127])
    : "l"(da), "l"(db), "r"(scale_d));
}

template <int BN> __device__ __forceinline__ void wgmma(float (&d)[BN / 2], uint64_t a, uint64_t b, int s) {
  if constexpr (BN == 128) wgmma_n128(d, a, b, s);
  else if constexpr (BN == 192) wgmma_n192(d, a, b, s);
  else wgmma_n256(d, a, b, s);
}

struct Prod {
  uint32_t sb;
  uint32_t n, page, used, tail, sizes, skip;
  uint32_t ready, tag;
  int lane;
  __device__ __forceinline__ uint32_t acquire(uint32_t pages, uint32_t bytes, uint32_t& fb) {
    uint32_t sz = pages + skip; skip = 0;
    while (used + sz > NPAGE) {
      mbar_wait(sb + BAR_EMPTY + ((tail & 7) << 3), (tail >> 3) & 1);
      used -= (sizes >> ((tail & 7) << 2)) & 15; tail++;
    }
    used += sz;
    uint32_t sh = (n & 7) << 2;
    sizes = (sizes & ~(15u << sh)) | (sz << sh);
    fb = sb + BAR_FULL + ((n & 7) << 3);
    if (lane == 0) mbar_expect_tx(fb, bytes);
    uint32_t a = sb + page * PAGE;
    page += pages; if (page >= NPAGE) page -= NPAGE;
    n++;
    return a;
  }
  __device__ __forceinline__ void align2() { skip = page & 1; page += skip; if (page >= NPAGE) page -= NPAGE; }
  __device__ __forceinline__ void align3() { skip = (0x120120120ull >> (page << 2)) & 3; if (page >= 9) skip = (0x120u >> ((page - 9) << 2)) & 3; page += skip; if (page >= NPAGE) page -= NPAGE; }
  __device__ __forceinline__ void need(const uint32_t* ev, uint32_t mask) {
    if ((ready & mask) != mask) {
      uint32_t spins = 0;
      do {
        uint32_t v = 0;
        if (lane < 16) asm volatile("ld.acquire.gpu.global.u32 %0, [%1];" : "=r"(v) : "l"(ev) : "memory");
        ready = __ballot_sync(0xffffffffu, v == tag);
        spin_check(++spins);
      } while ((ready & mask) != mask);
      __syncwarp();
      fence_async_all();
    }
  }
};

struct Cons {
  uint32_t sb, n, page, prev, sphase;
  uint64_t da0, db0;
  int lane;
  __device__ __forceinline__ void align2() { page += page & 1; if (page >= NPAGE) page -= NPAGE; }
  __device__ __forceinline__ void align3() { uint32_t s = (0x120120120ull >> (page << 2)) & 3; if (page >= 9) s = (0x120u >> ((page - 9) << 2)) & 3; page += s; if (page >= NPAGE) page -= NPAGE; }
  template <int BN, int PAGES> __device__ __forceinline__ void step(float (&acc)[BN / 2], int accumulate) {
    mbar_wait(sb + BAR_FULL + ((n & 7) << 3), (n >> 3) & 1);
    uint64_t da = da0 + (page << 10), db = db0 + (page << 10);
    wgmma_fence();
#pragma unroll
    for (int k = 0; k < 4; k++) wgmma<BN>(acc, da + 2 * k, db + 128 * k, k ? 1 : accumulate);
    wgmma_commit();
    wgmma_wait<1>();
    if (prev && lane == 0) mbar_arrive(prev);
    prev = sb + BAR_EMPTY + ((n & 7) << 3);
    n++; page += PAGES; if (page >= NPAGE) page -= NPAGE;
  }
  __device__ __forceinline__ void drain() {
    wgmma_wait<0>();
    if (lane == 0) mbar_arrive(prev);
    prev = 0;
  }
};

struct RowStats { float mean[2], rstd[2]; };

__device__ __forceinline__ RowStats load_stats(const uint4* base, uint32_t tag, int lane) {
  RowStats st;
#pragma unroll
  for (int r = 0; r < 2; r++) {
    const uint4* p = base + r * 64;
    uint4 a, b; uint32_t spins = 0;
    do { a = ll_load(p); b = ll_load(p + 1); spin_check(++spins); } while (a.y != tag || a.w != tag || b.y != tag || b.w != tag);
    __syncwarp();
    float s0 = __uint_as_float(a.x), s1 = __uint_as_float(b.x);
    float s = s0 + s1;
    s += __shfl_xor_sync(0xffffffffu, s, 1); s += __shfl_xor_sync(0xffffffffu, s, 2);
    float mean = s * (1.0f / DM);
    float d0 = s0 * (1.0f / 128) - mean, d1 = s1 * (1.0f / 128) - mean;
    float m2 = __uint_as_float(a.z) + __uint_as_float(b.z) + 128.0f * (d0 * d0 + d1 * d1);
    m2 += __shfl_xor_sync(0xffffffffu, m2, 1); m2 += __shfl_xor_sync(0xffffffffu, m2, 2);
    st.mean[r] = mean; st.rstd[r] = rsqrtf(m2 * (1.0f / DM) + LN_EPS);
  }
  return st;
}
__device__ __forceinline__ void fetch_cs(uint32_t dst, uint32_t col, uint32_t tag) {
  const uint2* p = ptr_add(&g_cs[0], col * 8u);
  uint2 v; uint32_t spins = 0;
  do { v = ll_load2(p); spin_check(++spins); } while (v.y != tag);
  sts32f(dst, __uint_as_float(v.x));
}
__device__ __forceinline__ float swiglu(float g, float u) { return g * rcp(1.0f + ex2(-LOG2E * g)) * u; }

__global__ void __launch_bounds__(384, 1) fused_kernel(const __grid_constant__ Params P) {
  extern __shared__ __align__(1024) uint8_t smem_raw[];
  const uint32_t sb = __shfl_sync(0xffffffffu, smem_u32(smem_raw), 0);
  const int warp = __shfl_sync(0xffffffffu, threadIdx.x >> 5, 0);
  const int lane = threadIdx.x & 31;
  uint32_t role = blockIdx.x;
  if (P.use_smid) { uint32_t smid; asm volatile("mov.u32 %0, %%smid;" : "=r"(smid)); role = P.role[smid]; }
  const uint32_t tag = *(volatile uint32_t*)&g_epoch[blockIdx.x] + 1;
  if (role >= 128) {
    if (threadIdx.x < 128) {
      const uint4* p = &g_stats[(threadIdx.x >> 3) * 1024 + (threadIdx.x & 7)];
      uint32_t spins = 0;
      while (ll_load(p).y != tag) { __nanosleep(200); spin_check(++spins); }
    }
    __syncthreads();
    if (threadIdx.x == 0) g_epoch[blockIdx.x] = tag;
    return;
  }
  const int g = role >> 3, j = role & 7;
  if (threadIdx.x == 0) {
    spin_check((sb & 1023) << 22);
    for (int s = 0; s < 8; s++) { mbar_init(sb + BAR_FULL + 8 * s, 1); mbar_init(sb + BAR_EMPTY + 8 * s, 8); }
    for (int s = 0; s < 2; s++) { mbar_init(sb + BAR_SFULL + 8 * s, 4); mbar_init(sb + BAR_SEMPTY + 8 * s, 1); }
    asm volatile("fence.mbarrier_init.release.cluster;" ::: "memory");
    fence_async_smem();
  }
  __syncthreads();

  if (warp >= 8) {
    asm volatile("setmaxnreg.dec.sync.aligned.u32 40;");
    if (warp == 8) {
      Prod p; p.sb = sb; p.n = p.page = p.used = p.tail = p.sizes = p.skip = 0; p.ready = 0; p.tag = tag; p.lane = lane;
      const uint32_t* fl = ptr_add(&g_flags[0], (uint32_t)(g * 256 + (lane & 15)) * 4u);
      const int row0 = g * 128;
      const int par = g & 1, pair0 = (g >> 1) * 128;
      uint32_t fb;
      TL(2, 0);
#pragma unroll 1
      for (int l = 0; l < 2; l++) {
        const uint32_t* ev = ptr_add(fl, (uint32_t)l * 512u);
        p.align3(); p.ready = 0;
#pragma unroll 1
        for (int t = 0; t < 2; t++) {
#pragma unroll 1
          for (int k = 0; k < 16; k++) {
            uint32_t a = p.acquire(3, 40960, fb);
            if (lane == 0) tma_ld4(a + PAGE, &P.map[M_WQKV], fb, 0, k * 64, 0, t * 8 + j);
            if (l == 0) { if (lane == 0) tma_ld3(a, &P.map[M_XIN], fb, k * 64, par, pair0); }
            else { p.need(fl + 7 * 16, 3u << (k & 14)); if (lane == 0) tma_ld2(a, &P.map[M_ACT_LD], fb, k * 64, SEQ + row0); }
          }
        }
        TL(2, 1 + l * 8);
        p.align2();
#pragma unroll 1
        for (int k = 0; k < 16; k++) {
          if ((k & 7) == 0) p.ready = 0;
          uint32_t a = p.acquire(2, 32768, fb);
          if (lane == 0) tma_ld3(a + PAGE, &P.map[M_WO], fb, 0, k * 64, 2 * j);
          p.need(ptr_add(ev, (k >> 3) * 64), 3u << ((k & 7) * 2));
          if (lane == 0) tma_ld2(a, &P.map[M_ACT_LD], fb, k * 64, 2 * SEQ + row0);
          if (k == 1) {
            a = p.acquire(2, 32768, fb);
            if (lane == 0) {
              if (l == 0) { tma_ld3(a, &P.map[M_XIN], fb, j * 128, par, pair0); tma_ld3(a + PAGE, &P.map[M_XIN], fb, j * 128 + 64, par, pair0); }
              else { tma_ld2(a, &P.map[M_ACT_LD], fb, j * 128, SEQ + row0); tma_ld2(a + PAGE, &P.map[M_ACT_LD], fb, j * 128 + 64, SEQ + row0); }
            }
          }
        }
        TL(2, 2 + l * 8);
        p.align3(); p.ready = 0;
#pragma unroll 1
        for (int t = 0; t < 3; t++) {
#pragma unroll 1
          for (int k = 0; k < 16; k++) {
            uint32_t a = p.acquire(3, 49152, fb);
            if (lane == 0) {
              if (!P.w13_swapped) tma_ld4(a + PAGE, &P.map[M_W13], fb, 0, k * 64, t * 16 + 2 * j, 0);
              else { tma_ld4(a + PAGE, &P.map[M_W13], fb, 0, k * 64, t * 16 + 2 * j, 1); tma_ld4(a + 2 * PAGE, &P.map[M_W13], fb, 0, k * 64, t * 16 + 2 * j, 0); }
            }
            p.need(ev + 2 * 16, 3u << (k & 14));
            if (lane == 0) tma_ld2(a, &P.map[M_ACT_LD], fb, k * 64, row0);
          }
        }
        p.align2();
#pragma unroll 1
        for (int k = 0; k < 16; k++) {
          uint32_t a = p.acquire(2, 32768, fb);
          if (lane == 0) {
            if (!P.w13_swapped) tma_ld4(a + PAGE, &P.map[M_W13H], fb, 0, k * 64, 48 + j, 0);
            else { tma_ld4(a + PAGE, &P.map[M_W13H], fb, 0, k * 64, 48 + j, 1); tma_ld4(a + PAGE + 8192, &P.map[M_W13H], fb, 0, k * 64, 48 + j, 0); }
            tma_ld2(a, &P.map[M_ACT_LD], fb, k * 64, row0);
          }
        }
        TL(2, 3 + l * 8);
#pragma unroll 1
        for (int k = 0; k < 56; k++) {
          if ((k & 15) == 0) p.ready = 0;
          uint32_t a = p.acquire(2, 32768, fb);
          if (lane == 0) tma_ld3(a + PAGE, &P.map[M_W2], fb, 0, k * 64, 2 * j);
          p.need(ptr_add(ev, (3 + (k >> 4)) * 64), k < 48 ? 3u << (k & 14) : 3u << ((k & 7) * 2));
          if (lane == 0) tma_ld2(a, &P.map[M_H_LD], fb, k * 64, row0);
          if (k == 1) {
            a = p.acquire(2, 32768, fb);
            if (lane == 0) { tma_ld2(a, &P.map[M_ACT_LD], fb, j * 128, row0); tma_ld2(a + PAGE, &P.map[M_ACT_LD], fb, j * 128 + 64, row0); }
          }
        }
        TL(2, 4 + l * 8);
      }
    } else if (warp <= 10) {
      if (lane == 0) {
        const int w = warp - 9;
        const uint32_t src = sb + SM_STAGE + w * PAGE;
        const int row = g * 128 + w * 64;
        uint32_t* fl = ptr_add(&g_flags[0], (uint32_t)(g * 256 + j * 2 + w) * 4u);
#pragma unroll 1
        for (int e = 0; e < 16; e++) {
          mbar_wait(sb + BAR_SFULL + 8 * w, e & 1);
          const int q = e & 7;
          if (q < 2) tma_st2(&P.map[M_ACT_ST], src, (q * 8 + j) * 64, 2 * SEQ + row);
          else if (q == 2 || e == 7) { const int r = (q == 2 ? 0 : SEQ) + row; tma_st2(&P.map[M_ACT_ST], src, j * 128, r); tma_st2(&P.map[M_ACT_ST], src + 8192, j * 128 + 64, r); }
          else if (q < 6) { const int c = (q - 3) * 1024 + j * 128; tma_st2(&P.map[M_H_ST], src, c, row); tma_st2(&P.map[M_H_ST], src + 8192, c + 64, row); }
          else if (q == 6) tma_st2(&P.map[M_H_ST], src, 3072 + j * 64, row);
          else { const int pr = (g >> 1) * 128 + w * 64; tma_st3(&P.map[M_OUT_ST], src, j * 128, g & 1, pr); tma_st3(&P.map[M_OUT_ST], src + 8192, j * 128 + 64, g & 1, pr); }
          bulk_commit();
          bulk_wait_read();
          mbar_arrive(sb + BAR_SEMPTY + 8 * w);
          bulk_wait_all();
          asm volatile("st.release.gpu.global.u32 [%0], %1;" :: "l"(fl), "r"(tag) : "memory");
          if (w == 0) TL(3, e);
          fl += 16;
        }
        if (w == 0) g_epoch[blockIdx.x] = tag;
      }
    }
  } else {
    asm volatile("setmaxnreg.inc.sync.aligned.u32 232;");
    const int wg = warp >> 2, tid = threadIdx.x & 127;
    const int quad = lane & 3, gr = lane >> 2;
    Cons c; c.sb = sb; c.n = 0; c.page = 0; c.prev = 0; c.sphase = 1; c.lane = lane;
    c.da0 = make_desc(sb + wg * 8192, 16, 1024); c.db0 = make_desc(sb + PAGE, 8192, 1024);
    const uint32_t stage = sb + SM_STAGE + wg * PAGE;
    const uint32_t csb = sb + SM_CS + wg * 1024;
    const uint32_t mrow = (warp & 3) * 16 + (lane & 15);
    const uint32_t moff = mrow * 128, msw = (lane >> 4) ^ (lane & 7);
    const uint32_t strow = (uint32_t)(g * 128 + wg * 64 + (warp & 3) * 16 + gr);
    TL(wg, 0);
    {
      const int r = threadIdx.x >> 1, hf = threadIdx.x & 1;
      const uint32_t tok = 2 * ((g >> 1) * 128 + r) + (g & 1);
      const uint4* xp = ptr_add((const uint4*)P.xin, tok * 2048u + j * 256u + hf * 128u);
      uint4 v[8];
#pragma unroll
      for (int i = 0; i < 8; i++) v[i] = __ldg(xp + i);
      float s = 0;
#pragma unroll
      for (int i = 0; i < 8; i++) s += bf_lo(v[i].x) + bf_hi(v[i].x) + bf_lo(v[i].y) + bf_hi(v[i].y) + bf_lo(v[i].z) + bf_hi(v[i].z) + bf_lo(v[i].w) + bf_hi(v[i].w);
      s += __shfl_xor_sync(0xffffffffu, s, 1);
      const float m = s * (1.0f / 128);
      float q2 = 0;
#pragma unroll
      for (int i = 0; i < 8; i++) {
        const uint32_t w4[4] = {v[i].x, v[i].y, v[i].z, v[i].w};
#pragma unroll
        for (int e = 0; e < 4; e++) { float a = bf_lo(w4[e]) - m, b = bf_hi(w4[e]) - m; q2 += a * a; q2 += b * b; }
      }
      q2 += __shfl_xor_sync(0xffffffffu, q2, 1);
      if (hf == 0) ll_store(ptr_add(&g_stats[0], (uint32_t)((g * 128 + r) * 8 + j) * 16u), __float_as_uint(s), __float_as_uint(q2), tag);
    }
    auto x_epilogue = [&](float (&acc)[64], uint32_t (&res)[32], int stat_event) {
      uint32_t pk[32];
#pragma unroll
      for (int i = 0; i < 32; i++) pk[i] = pack_bf16(acc[2 * i] + bf_lo(res[i]), acc[2 * i + 1] + bf_hi(res[i]));
      mbar_wait(sb + BAR_SEMPTY + 8 * wg, c.sphase); c.sphase ^= 1;
#pragma unroll
      for (int i = 0; i < 8; i++) stsm4(stage + (i >> 2) * 8192 + moff + ((((i & 3) * 2) ^ msw) << 4), pk[4 * i], pk[4 * i + 1], pk[4 * i + 2], pk[4 * i + 3]);
      fence_async_smem();
      __syncwarp();
      if (lane == 0) mbar_arrive(sb + BAR_SFULL + 8 * wg);
      if (stat_event >= 0) {
#pragma unroll
        for (int r = 0; r < 2; r++) {
          float s = 0;
#pragma unroll
          for (int i = 0; i < 16; i++) s += bf_lo(pk[2 * i + r]) + bf_hi(pk[2 * i + r]);
          s += __shfl_xor_sync(0xffffffffu, s, 1); s += __shfl_xor_sync(0xffffffffu, s, 2);
          const float m = s * (1.0f / 128);
          float q2 = 0;
#pragma unroll
          for (int i = 0; i < 16; i++) { float a = bf_lo(pk[2 * i + r]) - m, b = bf_hi(pk[2 * i + r]) - m; q2 += a * a; q2 += b * b; }
          q2 += __shfl_xor_sync(0xffffffffu, q2, 1); q2 += __shfl_xor_sync(0xffffffffu, q2, 2);
          if (quad == 0) ll_store(ptr_add(&g_stats[0], (((uint32_t)stat_event * 2048u + strow + r * 8) * 8u + j) * 16u), __float_as_uint(s), __float_as_uint(q2), tag);
        }
      }
    };
    auto residual_step = [&](uint32_t (&res)[32]) {
      mbar_wait(sb + BAR_FULL + ((c.n & 7) << 3), (c.n >> 3) & 1);
      const uint32_t a = sb + c.page * PAGE + wg * 8192 + moff;
#pragma unroll
      for (int i = 0; i < 8; i++) ldsm4(a + (i >> 2) * PAGE + ((((i & 3) * 2) ^ msw) << 4), res[4 * i], res[4 * i + 1], res[4 * i + 2], res[4 * i + 3]);
      __syncwarp();
      if (lane == 0) mbar_arrive(sb + BAR_EMPTY + ((c.n & 7) << 3));
      c.n++; c.page += 2; if (c.page >= NPAGE) c.page -= NPAGE;
    };

#pragma unroll 1
    for (int l = 0; l < 2; l++) {
      c.align3();
      RowStats st;
#pragma unroll 1
      for (int t = 0; t < 2; t++) {
        float acc[96];
        c.step<192, 3>(acc, 0);
        {
          const uint32_t c0 = (t * 8 + j) * 64;
          fetch_cs(csb + tid * 4, (tid >> 6) * 1024 + c0 + (tid & 63), tag);
          if (tid < 64) fetch_cs(csb + 512 + tid * 4, 2048 + c0 + tid, tag);
          __syncwarp();
        }
#pragma unroll 1
        for (int k = 1; k < 8; k++) c.step<192, 3>(acc, 1);
        if (t == 0) st = load_stats(ptr_add(&g_stats[0], (((uint32_t)l * 4096u + strow) * 8u + quad * 2) * 16u), tag, lane);
#pragma unroll 1
        for (int k = 8; k < 16; k++) c.step<192, 3>(acc, 1);
        c.drain();
        TL(wg, 1 + l * 24 + t * 2);
        bar_sync(2 + wg, 128);
        uint32_t pk[24][2];
#pragma unroll
        for (int b = 0; b < 24; b++) {
          const float2 cs = lds64f(csb + b * 32 + quad * 8);
          pk[b][0] = pack_bf16((acc[4 * b] - st.mean[0] * cs.x) * st.rstd[0], (acc[4 * b + 1] - st.mean[0] * cs.y) * st.rstd[0]);
          pk[b][1] = pack_bf16((acc[4 * b + 2] - st.mean[1] * cs.x) * st.rstd[1], (acc[4 * b + 3] - st.mean[1] * cs.y) * st.rstd[1]);
        }
        const uint32_t hoff = (uint32_t)(((l * 2 + t) * 16 + g) * 8 + j) * 4096u + lane * 16u;
        if (warp == 7 && g < 14) {
          uint4* hp = ptr_add(&g_halo[0], hoff);
#pragma unroll
          for (int i = 0; i < 8; i++) ll_store(hp + i * 32, pk[8 + i][1], pk[16 + i][1], tag);
        }
        mbar_wait(sb + BAR_SEMPTY + 8 * wg, c.sphase); c.sphase ^= 1;
#pragma unroll
        for (int i = 0; i < 4; i++) stsm4(stage + moff + (((i * 2) ^ msw) << 4), pk[16 + 2 * i][0], pk[16 + 2 * i][1], pk[17 + 2 * i][0], pk[17 + 2 * i][1]);
        {
          const uint32_t ka = stage + 8192 + (warp & 3) * 1024 + lane * 16;
          sts128(ka, pk[8][1], pk[9][1], pk[10][1], pk[11][1]);
          sts128(ka + 512, pk[12][1], pk[13][1], pk[14][1], pk[15][1]);
        }
        bar_sync(1, 256);
        uint32_t kH[8], vH[8], vL[8], vU[8];
        {
#pragma unroll
          for (int i = 0; i < 4; i++) ldsm4t(stage + moff + (((i * 2) ^ msw) << 4), vL[2 * i], vU[2 * i], vL[2 * i + 1], vU[2 * i + 1]);
          if (warp > 0) {
            const uint32_t pst = sb + SM_STAGE + ((warp - 1) >> 2) * PAGE;
            const uint32_t pw = (warp - 1) & 3;
            const uint32_t va = pst + (pw * 16 + 8 + (lane & 7)) * 128;
            ldsm4t(va + ((((lane >> 3)) ^ (lane & 7)) << 4), vH[0], vH[1], vH[2], vH[3]);
            ldsm4t(va + (((4 + (lane >> 3)) ^ (lane & 7)) << 4), vH[4], vH[5], vH[6], vH[7]);
            const uint32_t ka = pst + 8192 + pw * 1024 + lane * 16;
            lds128(ka, kH[0], kH[1], kH[2], kH[3]);
            lds128(ka + 512, kH[4], kH[5], kH[6], kH[7]);
          } else if (g >= 2) {
            const uint4* hp = ptr_add(&g_halo[0], hoff - 2 * 8 * 4096u);
            uint32_t spins = 0; bool ok;
            do {
              ok = true;
#pragma unroll
              for (int i = 0; i < 8; i++) { uint4 v = ll_load(hp + i * 32); kH[i] = v.x; vH[i] = v.z; ok = ok && v.y == tag && v.w == tag; }
              spin_check(++spins);
            } while (!__all_sync(0xffffffffu, ok));
#pragma unroll
            for (int i = 0; i < 8; i++) vH[i] = movm(vH[i]);
          } else {
#pragma unroll
            for (int i = 0; i < 8; i++) { kH[i] = 0; vH[i] = 0; }
          }
        }
        const bool nohalo = (warp == 0 && g < 2);
        const bool c0 = (2 * quad <= gr), c1 = (2 * quad + 1 <= gr);
        uint32_t op[8][2];
#pragma unroll
        for (int h = 0; h < 2; h++) {
          float sH[4] = {0, 0, 0, 0}, sL[4] = {0, 0, 0, 0}, sU[4] = {0, 0, 0, 0};
#pragma unroll
          for (int kk = 0; kk < 2; kk++) {
            const int b = h * 4 + kk * 2;
            mma16816(sH, pk[b][0], pk[b][1], pk[b + 1][0], pk[b + 1][1], kH[b], kH[b + 1]);
            mma16816(sL, pk[b][0], pk[b][1], pk[b + 1][0], pk[b + 1][1], pk[8 + b][0], pk[9 + b][0]);
            mma16816(sU, pk[b][0], pk[b][1], pk[b + 1][0], pk[b + 1][1], pk[8 + b][1], pk[9 + b][1]);
          }
          const float sc = 0.17677669529663687f * LOG2E;
          float a0 = (c0 ? sL[0] : sH[0]) * sc, a1 = (c1 ? sL[1] : sH[1]) * sc;
          float b0 = (c0 ? sU[2] : sL[2]) * sc, b1 = (c1 ? sU[3] : sL[3]) * sc;
          if (nohalo) { if (!c0) a0 = -1e9f * LOG2E; if (!c1) a1 = -1e9f * LOG2E; }
          float ma = fmaxf(a0, a1), mb = fmaxf(b0, b1);
          ma = fmaxf(ma, __shfl_xor_sync(0xffffffffu, ma, 1)); mb = fmaxf(mb, __shfl_xor_sync(0xffffffffu, mb, 1));
          ma = fmaxf(ma, __shfl_xor_sync(0xffffffffu, ma, 2)); mb = fmaxf(mb, __shfl_xor_sync(0xffffffffu, mb, 2));
          a0 = ex2(a0 - ma); a1 = ex2(a1 - ma); b0 = ex2(b0 - mb); b1 = ex2(b1 - mb);
          float sa = a0 + a1, sbb = b0 + b1;
          sa += __shfl_xor_sync(0xffffffffu, sa, 1); sbb += __shfl_xor_sync(0xffffffffu, sbb, 1);
          sa += __shfl_xor_sync(0xffffffffu, sa, 2); sbb += __shfl_xor_sync(0xffffffffu, sbb, 2);
          const float ra = rcp(sa), rb = rcp(sbb);
          a0 *= ra; a1 *= ra; b0 *= rb; b1 *= rb;
          const uint32_t pH = pack_bf16(c0 ? 0.f : a0, c1 ? 0.f : a1), pL0 = pack_bf16(c0 ? a0 : 0.f, c1 ? a1 : 0.f);
          const uint32_t pL1 = pack_bf16(c0 ? 0.f : b0, c1 ? 0.f : b1), pU = pack_bf16(c0 ? b0 : 0.f, c1 ? b1 : 0.f);
#pragma unroll
          for (int d = 0; d < 4; d++) {
            float o[4] = {0, 0, 0, 0};
            mma16816(o, pH, 0u, pL0, pL1, vH[h * 4 + d], vL[h * 4 + d]);
            mma1688(o, 0u, pU, vU[h * 4 + d]);
            op[h * 4 + d][0] = pack_bf16(o[0], o[1]); op[h * 4 + d][1] = pack_bf16(o[2], o[3]);
          }
        }
        bar_sync(1, 256);
#pragma unroll
        for (int i = 0; i < 4; i++) stsm4(stage + moff + (((i * 2) ^ msw) << 4), op[2 * i][0], op[2 * i][1], op[2 * i + 1][0], op[2 * i + 1][1]);
        fence_async_smem();
        __syncwarp();
        if (lane == 0) mbar_arrive(sb + BAR_SFULL + 8 * wg);
        TL(wg, 2 + l * 24 + t * 2);
      }
      {
        c.align2();
        float acc[64]; uint32_t res[32];
        c.step<128, 2>(acc, 0);
        c.step<128, 2>(acc, 1);
        residual_step(res);
#pragma unroll 1
        for (int k = 2; k < 16; k++) c.step<128, 2>(acc, 1);
        c.drain();
        TL(wg, 5 + l * 24);
        x_epilogue(acc, res, 1 + 2 * l);
        TL(wg, 6 + l * 24);
      }
      c.align3();
#pragma unroll 1
      for (int t = 0; t < 3; t++) {
        float acc[128];
        c.step<256, 3>(acc, 0);
        if (t == 0) TL(wg, 7 + l * 24);
        {
          const uint32_t c0 = 3072 + t * 1024 + j * 128 + tid;
          fetch_cs(csb + tid * 4, c0, tag);
          fetch_cs(csb + 512 + tid * 4, c0 + FF, tag);
          __syncwarp();
        }
#pragma unroll 1
        for (int k = 1; k < 8; k++) c.step<256, 3>(acc, 1);
        if (t == 0) st = load_stats(ptr_add(&g_stats[0], (((uint32_t)l * 4096u + 2048u + strow) * 8u + quad * 2) * 16u), tag, lane);
#pragma unroll 1
        for (int k = 8; k < 16; k++) c.step<256, 3>(acc, 1);
        c.drain();
        TL(wg, 8 + l * 24 + t * 2);
        bar_sync(2 + wg, 128);
        mbar_wait(sb + BAR_SEMPTY + 8 * wg, c.sphase); c.sphase ^= 1;
#pragma unroll
        for (int i = 0; i < 8; i++) {
          uint32_t hp[4];
#pragma unroll
          for (int e = 0; e < 2; e++) {
            const int b = 2 * i + e;
            const float2 cg = lds64f(csb + b * 32 + quad * 8), cu = lds64f(csb + 512 + b * 32 + quad * 8);
#pragma unroll
            for (int r = 0; r < 2; r++) {
              const float g0 = (acc[4 * b + 2 * r] - st.mean[r] * cg.x) * st.rstd[r], g1 = (acc[4 * b + 2 * r + 1] - st.mean[r] * cg.y) * st.rstd[r];
              const float u0 = (acc[64 + 4 * b + 2 * r] - st.mean[r] * cu.x) * st.rstd[r], u1 = (acc[64 + 4 * b + 2 * r + 1] - st.mean[r] * cu.y) * st.rstd[r];
              hp[2 * e + r] = pack_bf16(swiglu(g0, u0), swiglu(g1, u1));
            }
          }
          stsm4(stage + (i >> 2) * 8192 + moff + ((((i & 3) * 2) ^ msw) << 4), hp[0], hp[1], hp[2], hp[3]);
        }
        fence_async_smem();
        __syncwarp();
        if (lane == 0) mbar_arrive(sb + BAR_SFULL + 8 * wg);
        TL(wg, 9 + l * 24 + t * 2);
      }
      {
        c.align2();
        float acc[64];
        c.step<128, 2>(acc, 0);
        fetch_cs(csb + tid * 4, 3072 + (tid >> 6) * FF + 3072 + j * 64 + (tid & 63), tag);
        __syncwarp();
#pragma unroll 1
        for (int k = 1; k < 16; k++) c.step<128, 2>(acc, 1);
        c.drain();
        TL(wg, 14 + l * 24);
        bar_sync(2 + wg, 128);
        mbar_wait(sb + BAR_SEMPTY + 8 * wg, c.sphase); c.sphase ^= 1;
#pragma unroll
        for (int i = 0; i < 4; i++) {
          uint32_t hp[4];
#pragma unroll
          for (int e = 0; e < 2; e++) {
            const int b = 2 * i + e;
            const float2 cg = lds64f(csb + b * 32 + quad * 8), cu = lds64f(csb + 256 + b * 32 + quad * 8);
#pragma unroll
            for (int r = 0; r < 2; r++) {
              const float g0 = (acc[4 * b + 2 * r] - st.mean[r] * cg.x) * st.rstd[r], g1 = (acc[4 * b + 2 * r + 1] - st.mean[r] * cg.y) * st.rstd[r];
              const float u0 = (acc[32 + 4 * b + 2 * r] - st.mean[r] * cu.x) * st.rstd[r], u1 = (acc[32 + 4 * b + 2 * r + 1] - st.mean[r] * cu.y) * st.rstd[r];
              hp[2 * e + r] = pack_bf16(swiglu(g0, u0), swiglu(g1, u1));
            }
          }
          stsm4(stage + moff + (((i * 2) ^ msw) << 4), hp[0], hp[1], hp[2], hp[3]);
        }
        fence_async_smem();
        __syncwarp();
        if (lane == 0) mbar_arrive(sb + BAR_SFULL + 8 * wg);
        TL(wg, 15 + l * 24);
      }
      {
        float acc[64]; uint32_t res[32];
        c.step<128, 2>(acc, 0);
        c.step<128, 2>(acc, 1);
        residual_step(res);
#pragma unroll 1
        for (int k = 2; k < 56; k++) c.step<128, 2>(acc, 1);
        c.drain();
        TL(wg, 16 + l * 24);
        x_epilogue(acc, res, l == 0 ? 2 : -1);
        TL(wg, 17 + l * 24);
      }
    }
  }
}

__global__ void __launch_bounds__(256) colsum_kernel(const __nv_bfloat16* __restrict__ wqkv, const __nv_bfloat16* __restrict__ w1, const __nv_bfloat16* __restrict__ w3) {
  __shared__ float red[32][65];
  const int c0 = blockIdx.x * 64;
  const __nv_bfloat16* w; int ld, col;
  if (c0 < 3072) { w = wqkv; ld = 3072; col = c0; } else if (c0 < 3072 + FF) { w = w1; ld = FF; col = c0 - 3072; } else { w = w3; ld = FF; col = c0 - 3072 - FF; }
  const int r = threadIdx.x >> 3, q = threadIdx.x & 7;
  float s[8] = {0, 0, 0, 0, 0, 0, 0, 0};
#pragma unroll 8
  for (int k = r; k < DM; k += 32) {
    uint4 v = __ldg((const uint4*)(w + (size_t)k * ld + col + q * 8));
    s[0] += bf_lo(v.x); s[1] += bf_hi(v.x); s[2] += bf_lo(v.y); s[3] += bf_hi(v.y);
    s[4] += bf_lo(v.z); s[5] += bf_hi(v.z); s[6] += bf_lo(v.w); s[7] += bf_hi(v.w);
  }
  for (int e = 0; e < 8; e++) red[r][q * 8 + e] = s[e];
  __syncthreads();
  if (threadIdx.x < 64) {
    float t = 0;
    for (int i = 0; i < 32; i++) t += red[i][threadIdx.x];
    g_cs[c0 + threadIdx.x] = make_uint2(__float_as_uint(t), g_epoch[0] + 1);
  }
}

typedef CUresult (*EncodeFn)(CUtensorMap*, CUtensorMapDataType, cuuint32_t, void*, const cuuint64_t*, const cuuint64_t*, const cuuint32_t*,
                             const cuuint32_t*, CUtensorMapInterleave, CUtensorMapSwizzle, CUtensorMapL2promotion, CUtensorMapFloatOOBfill);

void encode(EncodeFn fn, CUtensorMap* m, const void* ptr, int rank, const cuuint64_t* dims, const cuuint64_t* strides, const cuuint32_t* box) {
  cuuint32_t es[5] = {1, 1, 1, 1, 1};
  fn(m, CU_TENSOR_MAP_DATA_TYPE_BFLOAT16, rank, const_cast<void*>(ptr), dims, strides, box, es, CU_TENSOR_MAP_INTERLEAVE_NONE,
     CU_TENSOR_MAP_SWIZZLE_128B, CU_TENSOR_MAP_L2_PROMOTION_L2_128B, CU_TENSOR_MAP_FLOAT_OOB_FILL_NONE);
}

}

extern "C" void kernel_launch(void* const* d_in, const int* in_sizes, int n_in, void* d_out, int out_size) {
  const __nv_bfloat16* x = (const __nv_bfloat16*)d_in[0];
  const __nv_bfloat16* wqkv = (const __nv_bfloat16*)d_in[1];
  const __nv_bfloat16* wo = (const __nv_bfloat16*)d_in[2];
  const __nv_bfloat16* w1 = (const __nv_bfloat16*)d_in[4];
  const __nv_bfloat16* w3 = (const __nv_bfloat16*)d_in[5];
  const __nv_bfloat16* w2 = (const __nv_bfloat16*)d_in[6];

  void* fnp = nullptr; cudaDriverEntryPointQueryResult qr;
  cudaGetDriverEntryPoint("cuTensorMapEncodeTiled", &fnp, cudaEnableDefault, &qr);
  EncodeFn fn = (EncodeFn)fnp;
  void *act, *h;
  cudaGetSymbolAddress(&act, g_act); cudaGetSymbolAddress(&h, g_h);

  Params P = {};
  { cuuint64_t d[3] = {DM, 2, SEQ / 2}, s[2] = {DM * 2, DM * 4}; cuuint32_t b[3] = {64, 1, 128}, b2[3] = {64, 1, 64};
    encode(fn, &P.map[M_XIN], x, 3, d, s, b); encode(fn, &P.map[M_OUT_ST], d_out, 3, d, s, b2); }
  { cuuint64_t d[2] = {DM, 3 * SEQ}, s[1] = {DM * 2}; cuuint32_t b[2] = {64, 128}, b2[2] = {64, 64};
    encode(fn, &P.map[M_ACT_LD], act, 2, d, s, b); encode(fn, &P.map[M_ACT_ST], act, 2, d, s, b2); }
  { cuuint64_t d[2] = {FF, SEQ}, s[1] = {FF * 2}; cuuint32_t b[2] = {64, 128}, b2[2] = {64, 64};
    encode(fn, &P.map[M_H_LD], h, 2, d, s, b); encode(fn, &P.map[M_H_ST], h, 2, d, s, b2); }
  { cuuint64_t d[4] = {64, DM, 3, 16}, s[3] = {3 * DM * 2, DM * 2, 128}; cuuint32_t b[4] = {64, 64, 3, 1};
    encode(fn, &P.map[M_WQKV], wqkv, 4, d, s, b); }
  { cuuint64_t d[3] = {64, DM, 16}, s[2] = {DM * 2, 128}; cuuint32_t b[3] = {64, 64, 2};
    encode(fn, &P.map[M_WO], wo, 3, d, s, b); }
  { cuuint64_t d[3] = {64, FF, 16}, s[2] = {DM * 2, 128}; cuuint32_t b[3] = {64, 64, 2};
    encode(fn, &P.map[M_W2], w2, 3, d, s, b); }
  {
    const bool sw = (uintptr_t)w3 < (uintptr_t)w1;
    const __nv_bfloat16* lo = sw ? w3 : w1;
    cuuint64_t diff = sw ? (uintptr_t)w1 - (uintptr_t)w3 : (uintptr_t)w3 - (uintptr_t)w1;
    cuuint64_t d[4] = {64, DM, FF / 64, 2}, s[3] = {FF * 2, 128, diff};
    cuuint32_t b[4] = {64, 64, 2, sw ? 1u : 2u}, b2[4] = {64, 64, 1, sw ? 1u : 2u};
    encode(fn, &P.map[M_W13], lo, 4, d, s, b); encode(fn, &P.map[M_W13H], lo, 4, d, s, b2);
    P.w13_swapped = sw;
  }
  P.xin = x;
  int dev = 0, sms = 0;
  cudaGetDevice(&dev);
  cudaDeviceGetAttribute(&sms, cudaDevAttrMultiProcessorCount, dev);
  P.use_smid = (sms == 132);
  for (int i = 0; i < 136; i++) P.role[i] = 255;
  for (int t = 0; t < 66; t++) {
    int q, i;
    if (t < 32) { q = t & 7; i = t >> 3; }
    else if (t < 60) { q = 1 + (t - 32) % 7; i = 4 + (t - 32) / 7; }
    else if (t < 62) continue;
    else { q = 0; i = 4 + (t - 62); }
    const int g = (q >> 1) * 4 + (i >> 1), j = (q & 1) * 4 + (i & 1) * 2;
    P.role[2 * t] = g * 8 + j; P.role[2 * t + 1] = g * 8 + j + 1;
  }
  cudaFuncSetAttribute(fused_kernel, cudaFuncAttributeMaxDynamicSharedMemorySize, SM_TOTAL);
  colsum_kernel<<<NCS / 64, 256>>>(wqkv, w1, w3);
  fused_kernel<<<P.use_smid ? 132 : 128, 384, SM_TOTAL>>>(P);
}
```

```cpp
#include <cuda_runtime.h>
#include <cuda_bf16.h>
#include <cuda.h>
#include <stdint.h>

namespace {

constexpr int SEQ = 2048, DM = 1024, FF = 3584;
constexpr float LN_EPS = 1e-5f;
constexpr float LOG2E = 1.4426950408889634f;

__device__ __align__(1024) __nv_bfloat16 g_act[3 * SEQ * DM];
__device__ __align__(1024) __nv_bfloat16 g_h[SEQ * FF];
__device__ __align__(128) uint2 g_stats[4 * SEQ * 8];
__device__ __align__(128) uint4 g_cs[3 * DM + 2 * FF];
__device__ __align__(128) uint4 g_halo[2 * 16 * 8 * 16 * 32];
__device__ __align__(128) uint32_t g_flags[16 * 32 * 8];
__device__ __align__(128) uint32_t g_sync[4 * 16 * 32];
#define ONES16 1, 1, 1, 1, 1, 1, 1, 1, 1, 1, 1, 1, 1, 1, 1, 1
__device__ uint32_t g_epoch[144] = {ONES16, ONES16, ONES16, ONES16, ONES16, ONES16, ONES16, ONES16, ONES16};

enum { M_XIN, M_XIN64, M_ACT_LD, M_ACT_ST, M_H_LD, M_H_ST, M_OUT_ST, M_WKV, M_WQ, M_WO, M_W1, M_W3, M_W1H, M_W3H, M_W2, M_COUNT };
struct alignas(64) Params {
  CUtensorMap map[M_COUNT];
  const __nv_bfloat16* wqkv;
  const __nv_bfloat16* wo;
  const __nv_bfloat16* w2;
  int use_smid;
};

constexpr uint32_t PAGE = 16384, NPAGE = 12;
constexpr uint32_t SM_STAGE = NPAGE * PAGE;
constexpr uint32_t SM_BAR = SM_STAGE + 2 * PAGE;
constexpr uint32_t SM_READY = SM_BAR + 256;
constexpr uint32_t SM_CS = SM_BAR + 384;
constexpr uint32_t SM_ROW = SM_CS + 1536;
constexpr uint32_t SM_TOTAL = SM_ROW + 1024;
static_assert(SM_TOTAL <= 232448, "shared memory");
constexpr uint32_t BAR_FULL = SM_BAR, BAR_EMPTY = SM_BAR + 64, BAR_SFULL = SM_BAR + 128, BAR_SEMPTY = SM_BAR + 160;
constexpr uint32_t BAR_XFULL = SM_BAR + 176, BAR_HALO = SM_BAR + 184, BAR_STAT = SM_BAR + 192, BAR_CSF = SM_BAR + 208;
constexpr uint32_t BAR_CSE = SM_BAR + 216, BAR_XIN = SM_BAR + 224, SM_ROLE = SM_BAR + 232;
enum { EV_OA, EV_OB, EV_XA, EV_XA2, EV_H0, EV_H3, EV_H1, EV_H2, EV_XB, EV_XB2, EV_N };

struct Sched { uint32_t pat[14]; uint32_t page0[14]; bool ok; };
constexpr int seg_steps(int seg) { return seg == 0 || seg == 3 ? 18 : seg == 1 || seg == 4 ? 14 : seg == 2 ? 17 : seg == 5 ? 32 : 56; }
constexpr int step_pages(int seg, int i) {
  return seg == 0 || seg == 3 ? (i < 2 ? 2 : i < 4 ? 1 : 3) : seg == 2 ? (i < 2 ? 1 : 2) : seg == 5 ? 3 : 2;
}
constexpr Sched make_sched() {
  Sched s = {};
  int owner[NPAGE] = {-1, -1, -1, -1, -1, -1, -1, -1, -1, -1, -1, -1};
  int n = 0, tail = 0, page = 0;
  s.ok = true;
  for (int sg = 0; sg < 14; sg++) {
    const int seg = sg % 7;
    if (seg == 5) page = (page + 2) / 3 * 3 % NPAGE;
    if (seg == 0) page = (page + 5) / 6 * 6 % NPAGE;
    s.page0[sg] = page;
    for (int i = 0; i < seg_steps(seg); i++) {
      const int p = step_pages(seg, i);
      if (page + p > (int)NPAGE) { s.ok = false; return s; }
      int need = n - 8;
      for (int q = 0; q < p; q++) { if (owner[page + q] > need) need = owner[page + q]; owner[page + q] = n; }
      int nw = need + 1 - tail; if (nw < 0) nw = 0;
      tail += nw;
      if (i < 16) s.pat[sg] |= (uint32_t)nw << (2 * i); else if (nw != 1) s.ok = false;
      if (nw > 3) s.ok = false;
      page = (page + p) % NPAGE; n++;
    }
  }
  for (int sg = 0; sg < 7; sg++) if (s.page0[sg] != s.page0[sg + 7] || (sg && s.pat[sg] != s.pat[sg + 7])) s.ok = false;
  return s;
}
constexpr Sched SCHED = make_sched();
static_assert(SCHED.ok && SCHED.page0[0] == 0 && SCHED.page0[3] == 0 && SCHED.page0[5] == 6 && (SCHED.pat[0] & 0xff) == 0, "ring schedule");
template <int SEG> struct Pat { static constexpr uint32_t v = SCHED.pat[SEG]; };

__device__ __forceinline__ uint32_t smem_u32(const void* p) { return (uint32_t)__cvta_generic_to_shared(p); }
__device__ __forceinline__ void mbar_init(uint32_t bar, uint32_t cnt) { asm volatile("mbarrier.init.shared::cta.b64 [%0], %1;" :: "r"(bar), "r"(cnt)); }
__device__ __forceinline__ void mbar_expect_tx(uint32_t bar, uint32_t bytes) { asm volatile("mbarrier.arrive.expect_tx.shared::cta.b64 _, [%0], %1;" :: "r"(bar), "r"(bytes) : "memory"); }
__device__ __forceinline__ void mbar_arrive(uint32_t bar) { asm volatile("mbarrier.arrive.shared::cta.b64 _, [%0];" :: "r"(bar) : "memory"); }
__device__ __forceinline__ void mbar_wait(uint32_t bar, uint32_t parity) {
  asm volatile("{\n.reg .pred p;\n.reg .u32 n;\nmov.u32 n, 0;\nLAB_WAIT:\n"
               "mbarrier.try_wait.parity.shared::cta.b64 p, [%0], %1;\n@p bra LAB_DONE;\n"
               "add.u32 n, n, 1;\nsetp.lt.u32 p, n, 4194304;\n@p bra LAB_WAIT;\ntrap;\nLAB_DONE:\n}" :: "r"(bar), "r"(parity) : "memory");
}
__device__ __forceinline__ void mbar_wait_fast(uint32_t bar, uint32_t parity) {
  asm volatile("{\n.reg .pred p;\nLAB_WAIT:\nmbarrier.try_wait.parity.shared::cta.b64 p, [%0], %1;\n@!p bra LAB_WAIT;\n}" :: "r"(bar), "r"(parity) : "memory");
}
__device__ __forceinline__ void spin_check(uint32_t n) { asm volatile("{\n.reg .pred p;\nsetp.ge.u32 p, %0, 4194304;\n@p st.volatile.global.u32 [%1], %0;\n}" :: "r"(n), "l"(0ull)); }
__device__ __forceinline__ void tma_ld2(uint32_t dst, const CUtensorMap* m, uint32_t bar, int c0, int c1) {
  asm volatile("cp.async.bulk.tensor.2d.shared::cluster.global.mbarrier::complete_tx::bytes [%0], [%1, {%3, %4}], [%2];" :: "r"(dst), "l"(m), "r"(bar), "r"(c0), "r"(c1) : "memory");
}
__device__ __forceinline__ void tma_ld3(uint32_t dst, const CUtensorMap* m, uint32_t bar, int c0, int c1, int c2) {
  asm volatile("cp.async.bulk.tensor.3d.shared::cluster.global.mbarrier::complete_tx::bytes [%0], [%1, {%3, %4, %5}], [%2];" :: "r"(dst), "l"(m), "r"(bar), "r"(c0), "r"(c1), "r"(c2) : "memory");
}
__device__ __forceinline__ void tma_ld3_mc(uint32_t dst, const CUtensorMap* m, uint32_t bar, int c0, int c1, int c2, uint16_t mask) {
  asm volatile("cp.async.bulk.tensor.3d.shared::cluster.global.mbarrier::complete_tx::bytes.multicast::cluster [%0], [%1, {%3, %4, %5}], [%2], %6;"
               :: "r"(dst), "l"(m), "r"(bar), "r"(c0), "r"(c1), "r"(c2), "h"(mask) : "memory");
}
__device__ __forceinline__ uint32_t mapa(uint32_t addr, uint32_t cta) { uint32_t r; asm("mapa.shared::cluster.u32 %0, %1, %2;" : "=r"(r) : "r"(addr), "r"(cta)); return r; }
__device__ __forceinline__ void mbar_arrive_cluster(uint32_t bar) { asm volatile("mbarrier.arrive.shared::cluster.b64 _, [%0];" :: "r"(bar) : "memory"); }
__device__ __forceinline__ void tma_st2(const CUtensorMap* m, uint32_t src, int c0, int c1) {
  asm volatile("cp.async.bulk.tensor.2d.global.shared::cta.bulk_group [%0, {%2, %3}], [%1];" :: "l"(m), "r"(src), "r"(c0), "r"(c1) : "memory");
}
__device__ __forceinline__ void tma_st3(const CUtensorMap* m, uint32_t src, int c0, int c1, int c2) {
  asm volatile("cp.async.bulk.tensor.3d.global.shared::cta.bulk_group [%0, {%2, %3, %4}], [%1];" :: "l"(m), "r"(src), "r"(c0), "r"(c1), "r"(c2) : "memory");
}
__device__ __forceinline__ void bulk_commit() { asm volatile("cp.async.bulk.commit_group;" ::: "memory"); }
template <int N> __device__ __forceinline__ void bulk_wait() { asm volatile("cp.async.bulk.wait_group %0;" :: "n"(N) : "memory"); }
__device__ __forceinline__ void fence_async_smem() { asm volatile("fence.proxy.async.shared::cta;" ::: "memory"); }
__device__ __forceinline__ void fence_async_global() { asm volatile("fence.proxy.async.global;" ::: "memory"); }
__device__ __forceinline__ bool elect_one() { uint32_t p; asm volatile("{\n.reg .pred P;\nelect.sync _|P, 0xffffffff;\nselp.u32 %0, 1, 0, P;\n}" : "=r"(p)); return p; }
__device__ __forceinline__ void prefetch_map(const CUtensorMap* m) { asm volatile("prefetch.tensormap [%0];" :: "l"(m) : "memory"); }
__device__ __forceinline__ void prefetch_l2(const void* p, uint32_t bytes) { asm volatile("cp.async.bulk.prefetch.L2.global [%0], %1;" :: "l"(p), "r"(bytes) : "memory"); }
__device__ __forceinline__ void wgmma_fence() { asm volatile("wgmma.fence.sync.aligned;" ::: "memory"); }
__device__ __forceinline__ void wgmma_commit() { asm volatile("wgmma.commit_group.sync.aligned;" ::: "memory"); }
template <int N> __device__ __forceinline__ void wgmma_wait() { asm volatile("wgmma.wait_group.sync.aligned %0;" :: "n"(N) : "memory"); }
__device__ __forceinline__ uint32_t desc_lo(uint32_t addr, uint32_t lbo) { return ((addr & 0x3FFFF) >> 4) | ((lbo >> 4) << 16); }
__device__ __forceinline__ uint64_t desc64(uint32_t lo) { uint64_t r; asm("mov.b64 %0, {%1, %2};" : "=l"(r) : "r"(lo), "r"(0x40000040u)); return r; }
__device__ __forceinline__ void bar_sync(int id, int n) { asm volatile("bar.sync %0, %1;" :: "r"(id), "r"(n) : "memory"); }
__device__ __forceinline__ uint32_t pack_bf16(float lo, float hi) { uint32_t r; asm("cvt.rn.bf16x2.f32 %0, %1, %2;" : "=r"(r) : "f"(hi), "f"(lo)); return r; }
__device__ __forceinline__ float bf_lo(uint32_t v) { return __uint_as_float(v << 16); }
__device__ __forceinline__ float bf_hi(uint32_t v) { return __uint_as_float(v & 0xffff0000u); }
__device__ __forceinline__ float ex2(float x) { float r; asm("ex2.approx.ftz.f32 %0, %1;" : "=f"(r) : "f"(x)); return r; }
__device__ __forceinline__ float rcp(float x) { float r; asm("rcp.approx.ftz.f32 %0, %1;" : "=f"(r) : "f"(x)); return r; }
__device__ __forceinline__ void stsm4(uint32_t a, uint32_t r0, uint32_t r1, uint32_t r2, uint32_t r3) {
  asm volatile("stmatrix.sync.aligned.m8n8.x4.shared.b16 [%0], {%1, %2, %3, %4};" :: "r"(a), "r"(r0), "r"(r1), "r"(r2), "r"(r3) : "memory");
}
__device__ __forceinline__ void ldsm4(uint32_t a, uint32_t& r0, uint32_t& r1, uint32_t& r2, uint32_t& r3) {
  asm volatile("ldmatrix.sync.aligned.m8n8.x4.shared.b16 {%0, %1, %2, %3}, [%4];" : "=r"(r0), "=r"(r1), "=r"(r2), "=r"(r3) : "r"(a) : "memory");
}
__device__ __forceinline__ uint32_t movm(uint32_t v) { uint32_t r; asm volatile("movmatrix.sync.aligned.m8n8.trans.b16 %0, %1;" : "=r"(r) : "r"(v)); return r; }
__device__ __forceinline__ void sts128(uint32_t a, uint32_t r0, uint32_t r1, uint32_t r2, uint32_t r3) {
  asm volatile("st.shared.v4.b32 [%0], {%1, %2, %3, %4};" :: "r"(a), "r"(r0), "r"(r1), "r"(r2), "r"(r3) : "memory");
}
__device__ __forceinline__ void lds128(uint32_t a, uint32_t& r0, uint32_t& r1, uint32_t& r2, uint32_t& r3) {
  asm volatile("ld.shared.v4.b32 {%0, %1, %2, %3}, [%4];" : "=r"(r0), "=r"(r1), "=r"(r2), "=r"(r3) : "r"(a) : "memory");
}
__device__ __forceinline__ float2 lds64f(uint32_t a) { float2 r; asm volatile("ld.shared.v2.f32 {%0, %1}, [%2];" : "=f"(r.x), "=f"(r.y) : "r"(a) : "memory"); return r; }
__device__ __forceinline__ void sts64f(uint32_t a, float x, float y) { asm volatile("st.shared.v2.f32 [%0], {%1, %2};" :: "r"(a), "f"(x), "f"(y) : "memory"); }
__device__ __forceinline__ uint32_t add_bf16x2(uint32_t a, uint32_t b) { uint32_t r; asm("add.rn.bf16x2 %0, %1, %2;" : "=r"(r) : "r"(a), "r"(b)); return r; }
__device__ __forceinline__ void sts32f(uint32_t a, float v) { asm volatile("st.shared.f32 [%0], %1;" :: "r"(a), "f"(v) : "memory"); }
__device__ __forceinline__ void mma16816(float (&c)[4], uint32_t a0, uint32_t a1, uint32_t a2, uint32_t a3, uint32_t b0, uint32_t b1) {
  asm("mma.sync.aligned.m16n8k16.row.col.f32.bf16.bf16.f32 {%0, %1, %2, %3}, {%4, %5, %6, %7}, {%8, %9}, {%0, %1, %2, %3};"
               : "+f"(c[0]), "+f"(c[1]), "+f"(c[2]), "+f"(c[3]) : "r"(a0), "r"(a1), "r"(a2), "r"(a3), "r"(b0), "r"(b1));
}
__device__ __forceinline__ void mma1688(float (&c)[4], uint32_t a0, uint32_t a1, uint32_t b0) {
  asm("mma.sync.aligned.m16n8k8.row.col.f32.bf16.bf16.f32 {%0, %1, %2, %3}, {%4, %5}, {%6}, {%0, %1, %2, %3};"
               : "+f"(c[0]), "+f"(c[1]), "+f"(c[2]), "+f"(c[3]) : "r"(a0), "r"(a1), "r"(b0));
}
__device__ __forceinline__ void ll_store(uint4* p, uint32_t a, uint32_t b, uint32_t tag) {
  asm volatile("st.relaxed.gpu.global.v2.b64 [%0], {%1, %2};" :: "l"(p), "l"((uint64_t)a | ((uint64_t)tag << 32)), "l"((uint64_t)b | ((uint64_t)tag << 32)) : "memory");
}
__device__ __forceinline__ uint4 ll_load(const uint4* p) {
  uint64_t a, b;
  asm volatile("ld.relaxed.gpu.global.v2.b64 {%0, %1}, [%2];" : "=l"(a), "=l"(b) : "l"(p) : "memory");
  return make_uint4((uint32_t)a, (uint32_t)(a >> 32), (uint32_t)b, (uint32_t)(b >> 32));
}
__device__ __forceinline__ uint32_t ld_relaxed(const uint32_t* p) { uint32_t v; asm volatile("ld.relaxed.gpu.global.u32 %0, [%1];" : "=r"(v) : "l"(p) : "memory"); return v; }
__device__ __forceinline__ uint4 ld_relaxed4(const void* p) { uint4 v; asm volatile("ld.relaxed.gpu.global.v4.u32 {%0, %1, %2, %3}, [%4];" : "=r"(v.x), "=r"(v.y), "=r"(v.z), "=r"(v.w) : "l"(p) : "memory"); return v; }
__device__ __forceinline__ void st_relaxed(uint32_t* p, uint32_t v) { asm volatile("st.relaxed.gpu.global.u32 [%0], %1;" :: "l"(p), "r"(v) : "memory"); }
__device__ __forceinline__ void st_relaxed2(void* p, uint32_t a, uint32_t b) { asm volatile("st.relaxed.gpu.global.v2.u32 [%0], {%1, %2};" :: "l"(p), "r"(a), "r"(b) : "memory"); }
__device__ __forceinline__ void st_release(uint32_t* p, uint32_t v) { asm volatile("st.release.gpu.global.u32 [%0], %1;" :: "l"(p), "r"(v) : "memory"); }
__device__ __forceinline__ uint32_t tagf(float v, uint32_t tag) { return (__float_as_uint(v) & ~15u) | (tag & 15u); }
__device__ __forceinline__ bool tag_ok4(const uint4& v, uint32_t tag) { return (((v.x ^ tag) | (v.y ^ tag) | (v.z ^ tag) | (v.w ^ tag)) & 15u) == 0; }
__device__ __forceinline__ float untag(uint32_t v) { return __uint_as_float(v & ~15u); }
template <typename T> __device__ __forceinline__ T* ptr_add(T* p, uint32_t bytes) {
  uint64_t r;
  asm("{\n.reg .u32 lo, hi;\nmov.b64 {lo, hi}, %1;\nadd.cc.u32 lo, lo, %2;\naddc.u32 hi, hi, 0;\nmov.b64 %0, {lo, hi};\n}" : "=l"(r) : "l"(p), "r"(bytes));
  return (T*)r;
}
#define TL(who, slot) do {} while (0)
#define ST(who, n) do {} while (0)
#define TLG(slot) do {} while (0)
#define STA() do {} while (0)
#define STB(n) do {} while (0)

__device__ __forceinline__ void wgmma_n128(float (&d)[64], uint64_t da, uint64_t db, int scale_d) {
  asm volatile("{\n.reg .pred p;\nsetp.ne.b32 p, %66, 0;\n"
    "wgmma.mma_async.sync.aligned.m64n128k16.f32.bf16.bf16 "
    "{%0, %1, %2, %3, %4, %5, %6, %7, %8, %9, %10, %11, %12, %13, %14, %15, "
    "%16, %17, %18, %19, %20, %21, %22, %23, %24, %25, %26, %27, %28, %29, %30, %31, "
    "%32, %33, %34, %35, %36, %37, %38, %39, %40, %41, %42, %43, %44, %45, %46, %47, "
    "%48, %49, %50, %51, %52, %53, %54, %55, %56, %57, %58, %59, %60, %61, %62, %63}, "
    "%64, %65, p, 1, 1, 0, 1;\n}\n"
    : "+f"(d[0]), "+f"(d[1]), "+f"(d[2]), "+f"(d[3]), "+f"(d[4]), "+f"(d[5]), "+f"(d[6]), "+f"(d[7]),
      "+f"(d[8]), "+f"(d[9]), "+f"(d[10]), "+f"(d[11]), "+f"(d[12]), "+f"(d[13]), "+f"(d[14]), "+f"(d[15]),
      "+f"(d[16]), "+f"(d[17]), "+f"(d[18]), "+f"(d[19]), "+f"(d[20]), "+f"(d[21]), "+f"(d[22]), "+f"(d[23]),
      "+f"(d[24]), "+f"(d[25]), "+f"(d[26]), "+f"(d[27]), "+f"(d[28]), "+f"(d[29]), "+f"(d[30]), "+f"(d[31]),
      "+f"(d[32]), "+f"(d[33]), "+f"(d[34]), "+f"(d[35]), "+f"(d[36]), "+f"(d[37]), "+f"(d[38]), "+f"(d[39]),
      "+f"(d[40]), "+f"(d[41]), "+f"(d[42]), "+f"(d[43]), "+f"(d[44]), "+f"(d[45]), "+f"(d[46]), "+f"(d[47]),
      "+f"(d[48]), "+f"(d[49]), "+f"(d[50]), "+f"(d[51]), "+f"(d[52]), "+f"(d[53]), "+f"(d[54]), "+f"(d[55]),
      "+f"(d[56]), "+f"(d[57]), "+f"(d[58]), "+f"(d[59]), "+f"(d[60]), "+f"(d[61]), "+f"(d[62]), "+f"(d[63])
    : "l"(da), "l"(db), "r"(scale_d));
}
__device__ __forceinline__ void wgmma_n256(float (&d)[128], uint64_t da, uint64_t db, int scale_d) {
  asm volatile("{\n.reg .pred p;\nsetp.ne.b32 p, %130, 0;\n"
    "wgmma.mma_async.sync.aligned.m64n256k16.f32.bf16.bf16 "
    "{%0, %1, %2, %3, %4, %5, %6, %7, %8, %9, %10, %11, %12, %13, %14, %15, "
    "%16, %17, %18, %19, %20, %21, %22, %23, %24, %25, %26, %27, %28, %29, %30, %31, "
    "%32, %33, %34, %35, %36, %37, %38, %39, %40, %41, %42, %43, %44, %45, %46, %47, "
    "%48, %49, %50, %51, %52, %53, %54, %55, %56, %57, %58, %59, %60, %61, %62, %63, "
    "%64, %65, %66, %67, %68, %69, %70, %71, %72, %73, %74, %75, %76, %77, %78, %79, "
    "%80, %81, %82, %83, %84, %85, %86, %87, %88, %89, %90, %91, %92, %93, %94, %95, "
    "%96, %97, %98, %99, %100, %101, %102, %103, %104, %105, %106, %107, %108, %109, %110, %111, "
    "%112, %113, %114, %115, %116, %117, %118, %119, %120, %121, %122, %123, %124, %125, %126, %127}, "
    "%128, %129, p, 1, 1, 0, 1;\n}\n"
    : "+f"(d[0]), "+f"(d[1]), "+f"(d[2]), "+f"(d[3]), "+f"(d[4]), "+f"(d[5]), "+f"(d[6]), "+f"(d[7]),
      "+f"(d[8]), "+f"(d[9]), "+f"(d[10]), "+f"(d[11]), "+f"(d[12]), "+f"(d[13]), "+f"(d[14]), "+f"(d[15]),
      "+f"(d[16]), "+f"(d[17]), "+f"(d[18]), "+f"(d[19]), "+f"(d[20]), "+f"(d[21]), "+f"(d[22]), "+f"(d[23]),
      "+f"(d[24]), "+f"(d[25]), "+f"(d[26]), "+f"(d[27]), "+f"(d[28]), "+f"(d[29]), "+f"(d[30]), "+f"(d[31]),
      "+f"(d[32]), "+f"(d[33]), "+f"(d[34]), "+f"(d[35]), "+f"(d[36]), "+f"(d[37]), "+f"(d[38]), "+f"(d[39]),
      "+f"(d[40]), "+f"(d[41]), "+f"(d[42]), "+f"(d[43]), "+f"(d[44]), "+f"(d[45]), "+f"(d[46]), "+f"(d[47]),
      "+f"(d[48]), "+f"(d[49]), "+f"(d[50]), "+f"(d[51]), "+f"(d[52]), "+f"(d[53]), "+f"(d[54]), "+f"(d[55]),
      "+f"(d[56]), "+f"(d[57]), "+f"(d[58]), "+f"(d[59]), "+f"(d[60]), "+f"(d[61]), "+f"(d[62]), "+f"(d[63]),
      "+f"(d[64]), "+f"(d[65]), "+f"(d[66]), "+f"(d[67]), "+f"(d[68]), "+f"(d[69]), "+f"(d[70]), "+f"(d[71]),
      "+f"(d[72]), "+f"(d[73]), "+f"(d[74]), "+f"(d[75]), "+f"(d[76]), "+f"(d[77]), "+f"(d[78]), "+f"(d[79]),
      "+f"(d[80]), "+f"(d[81]), "+f"(d[82]), "+f"(d[83]), "+f"(d[84]), "+f"(d[85]), "+f"(d[86]), "+f"(d[87]),
      "+f"(d[88]), "+f"(d[89]), "+f"(d[90]), "+f"(d[91]), "+f"(d[92]), "+f"(d[93]), "+f"(d[94]), "+f"(d[95]),
      "+f"(d[96]), "+f"(d[97]), "+f"(d[98]), "+f"(d[99]), "+f"(d[100]), "+f"(d[101]), "+f"(d[102]), "+f"(d[103]),
      "+f"(d[104]), "+f"(d[105]), "+f"(d[106]), "+f"(d[107]), "+f"(d[108]), "+f"(d[109]), "+f"(d[110]), "+f"(d[111]),
      "+f"(d[112]), "+f"(d[113]), "+f"(d[114]), "+f"(d[115]), "+f"(d[116]), "+f"(d[117]), "+f"(d[118]), "+f"(d[119]),
      "+f"(d[120]), "+f"(d[121]), "+f"(d[122]), "+f"(d[123]), "+f"(d[124]), "+f"(d[125]), "+f"(d[126]), "+f"(d[127])
    : "l"(da), "l"(db), "r"(scale_d));
}

template <int BN> __device__ __forceinline__ void wgmma(float (&d)[BN / 2], uint64_t a, uint64_t b, int s) {
  if constexpr (BN == 128) wgmma_n128(d, a, b, s);
  else wgmma_n256(d, a, b, s);
}

template <int N> __device__ __forceinline__ void acc_fence(float* a) {
#pragma unroll
  for (int i = 0; i < N; i++) asm volatile("" : "+f"(a[i]) :: "memory");
}

#define PACING 0
struct Prod {
  uint32_t sb, n, tail, addr, pat, ready;
  uint32_t* sync; uint32_t target, seen;
  __device__ __forceinline__ void pace_arrive() { if (PACING) asm volatile("red.relaxed.gpu.global.add.u32 [%0], 1;" :: "l"(sync) : "memory"); }
  __device__ __forceinline__ void pace_peek() { if (PACING) seen = ld_relaxed(sync); }
  __device__ __forceinline__ void pace_wait() {
    uint32_t spins = 0;
    if (PACING) while ((int32_t)(seen - target) < 0) { seen = ld_relaxed(sync); spin_check(++spins); }
    sync += 32;
  }
  uint32_t h0, h1; uint16_t mask;
  __device__ __forceinline__ void load_b(uint32_t dst, uint32_t half, const CUtensorMap* m, uint32_t mstep, uint32_t fb, int k, int ch, int cstep) {
#pragma unroll 1
    for (uint32_t h = h0; h <= h1; h++) tma_ld3_mc(dst + h * half, ptr_add(m, h * mstep), fb, 0, k * 64, ch + h * cstep, mask);
  }
  __device__ __forceinline__ void load_wide(const Params& P, int ffn, uint32_t dst, uint32_t fb, int k, int ch) {
    load_b(dst, PAGE, &P.map[ffn ? M_W1 : M_WKV], ffn ? 128 : 0, fb, k, ffn ? ch : ch + 16, ffn ? 0 : 16);
  }
  __device__ __forceinline__ void load_narrow(const Params& P, int ffn, uint32_t dst, uint32_t fb, int k, int j) {
    load_b(dst, 8192, &P.map[ffn ? M_W1H : M_WQ], ffn ? 128 : 0, fb, k, ffn ? 48 + j : 2 * j, ffn ? 0 : 1);
  }
  __device__ __forceinline__ void finish() {
#pragma unroll 1
    for (; tail < n; tail++) mbar_wait(sb + BAR_EMPTY + ((tail & 7) << 3), (tail >> 3) & 1);
  }
  template <int PAGES> __device__ __forceinline__ uint32_t acquire(uint32_t& fb) {
    uint32_t nw = pat & 3; pat = (pat >> 2) | 0x40000000u;
#pragma unroll 1
    for (; nw; nw--) { mbar_wait(sb + BAR_EMPTY + ((tail & 7) << 3), (tail >> 3) & 1); tail++; }
    ST(4, n);
    fb = sb + BAR_FULL + ((n & 7) << 3);
    mbar_expect_tx(fb, PAGES * PAGE);
    const uint32_t a = sb + addr;
    addr += PAGES * PAGE; if (addr >= NPAGE * PAGE) addr = 0;
    n++;
    return a;
  }
  __device__ __forceinline__ void need(uint32_t ev, uint32_t mask) {
    if ((ready & mask) != mask) {
      uint32_t spins = 0;
      do {
        asm volatile("ld.volatile.shared.u32 %0, [%1];" : "=r"(ready) : "r"(sb + SM_READY + ev * 4) : "memory");
        spin_check(++spins >> 4);
      } while ((ready & mask) != mask);
      fence_async_global();
    }
    ST(5, n - 1);
  }
};

struct Cons {
  uint32_t sb, n, off, prev;
  uint32_t ebar;
  uint32_t da0, db0;
  int lane;
  template <int PAGES> __device__ __forceinline__ void advance() {
    n++; off += PAGES << 10; if (off >= (NPAGE << 10)) off = 0;
    asm volatile("" : "+r"(n), "+r"(off));
  }
  template <int BN, int PAGES> __device__ __forceinline__ void step_ab(float (&acc)[BN / 2], uint32_t da, uint32_t db, int accumulate) {
    STA();
    mbar_wait_fast(sb + BAR_FULL + ((n & 7) << 3), (n >> 3) & 1);
    STB(n);
    const uint64_t da64 = desc64(da), db64 = desc64(db);
    wgmma_fence();
#pragma unroll
    for (int k = 0; k < 4; k++) wgmma<BN>(acc, da64 + 2 * k, db64 + 128 * k, k ? 1 : accumulate);
    wgmma_commit();
    wgmma_wait<1>();
    if (prev && lane < 2) mbar_arrive_cluster(ebar + prev);
    prev = 64 + ((n & 7) << 3);
    advance<PAGES>();
  }
  template <int BN> __device__ __forceinline__ void step(float (&acc)[BN / 2], int accumulate = 1) { step_ab<BN, BN / 128 + 1>(acc, da0 + off, db0 + 1024 + off, accumulate); }
  template <int BN> __device__ __forceinline__ void step_own(float (&acc)[BN / 2], uint32_t da, int accumulate) { step_ab<BN, BN / 128>(acc, da, db0 + off, accumulate); }
  template <int BN> __device__ __forceinline__ void steps(float (&acc)[BN / 2], int cnt) {
#pragma unroll 1
    for (int i = 0; i < cnt; i++) step<BN>(acc);
  }
  __device__ __forceinline__ void drain() {
    wgmma_wait<0>();
    if (lane < 2) mbar_arrive_cluster(ebar + prev);
    prev = 0;
  }
};

#define MAPPING 2
__device__ __forceinline__ uint32_t role_of_sm(uint32_t smid) {
  const uint32_t t = smid >> 1;
  uint32_t q, i;
  if (t < 32) { q = t & 7; i = t >> 3; }
  else if (t < 60) { const uint32_t u = t - 32, d = (u * 37) >> 8; q = 1 + u - d * 7; i = 4 + d; }
  else if (t < 62) return 128 + smid - 120;
  else { q = 0; i = t - 58; }
  return (q * 2 + (smid & 1)) * 8 + i;
}

__device__ __forceinline__ uint32_t* epoch_ptr() { uint32_t b; asm volatile("mov.u32 %0, %%ctaid.x;" : "=r"(b)); return ptr_add(&g_epoch[0], b * 4u); }

__global__ void __cluster_dims__(2, 1, 1) __launch_bounds__(384, 1) fused_kernel(const __grid_constant__ Params P) {
  extern __shared__ __align__(1024) uint8_t smem_raw[];
  const uint32_t sb = __shfl_sync(0xffffffffu, smem_u32(smem_raw), 0);
  const int warp = __shfl_sync(0xffffffffu, threadIdx.x >> 5, 0);
  const int lane = threadIdx.x & 31;
  uint32_t role = blockIdx.x < 128 ? ((blockIdx.x >> 4) * 2 + (blockIdx.x & 1)) * 8 + ((blockIdx.x >> 1) & 7) : blockIdx.x;
  if (P.use_smid) { uint32_t smid; asm volatile("mov.u32 %0, %%smid;" : "=r"(smid)); role = role_of_sm(smid); }
  const bool spare = role >= 128;
  const int g = role >> 3, j = role & 7;
  TLG(60);
  if (warp == 8) {
    if (elect_one()) {
      if (!spare) { prefetch_map(&P.map[M_XIN64]); prefetch_map(&P.map[M_WKV]); prefetch_map(&P.map[M_WQ]); prefetch_map(&P.map[M_XIN]); }
      spin_check((sb & 1023) << 22);
#pragma unroll
      for (int s = 0; s < 8; s++) { mbar_init(sb + BAR_FULL + 8 * s, 1); mbar_init(sb + BAR_EMPTY + 8 * s, 16); }
#pragma unroll
      for (int s = 0; s < 2; s++) {
        mbar_init(sb + BAR_SFULL + 16 * s, 4); mbar_init(sb + BAR_SFULL + 16 * s + 8, 4);
      }
      mbar_init(sb + BAR_SEMPTY, 1); mbar_init(sb + BAR_STAT, 1); mbar_init(sb + BAR_XFULL, 8); mbar_init(sb + BAR_HALO, 2); mbar_init(sb + BAR_CSF, 1); mbar_init(sb + BAR_CSE, 8); mbar_init(sb + BAR_XIN, 1);
      asm volatile("fence.mbarrier_init.release.cluster;" ::: "memory");
      fence_async_smem();
      if (!spare) {
        mbar_expect_tx(sb + BAR_XIN, 32768);
#pragma unroll
        for (int s = 0; s < 4; s++) tma_ld3(sb + SM_STAGE + s * 8192, &P.map[M_XIN64], sb + BAR_XIN, j * 128 + (s & 1) * 64, g & 1, (g >> 1) * 128 + (s >> 1) * 64);
      }
    }
  } else if (warp == 11) {
    asm volatile("st.shared.u32 [%0], %1;" :: "r"(sb + SM_READY + lane * 4), "r"(0) : "memory");
    asm volatile("st.shared.u32 [%0], %1;" :: "r"(sb + SM_ROLE), "r"(role) : "memory");
  }
  __syncwarp();
  asm volatile("barrier.cluster.arrive.release.aligned;\nbarrier.cluster.wait.acquire.aligned;" ::: "memory");
  uint32_t rank; asm("mov.u32 %0, %%cluster_ctarank;" : "=r"(rank));
  auto shared_b = [&]() {
    uint32_t peer;
    asm volatile("ld.shared::cluster.u32 %0, [%1];" : "=r"(peer) : "r"(mapa(sb + SM_ROLE, rank ^ 1)) : "memory");
    return !spare && peer < 128 && (peer & 7) == (uint32_t)j;
  };

  if (warp >= 8) {
    asm volatile("setmaxnreg.dec.sync.aligned.u32 40;");
    if (warp == 8) {
      if (elect_one()) {
        Prod p; p.sb = sb; p.n = 0; p.tail = 0; p.ready = 0; p.addr = 0;
        { const bool mc = shared_b(); p.h0 = mc ? rank : 0; p.h1 = mc ? rank : 1; p.mask = mc ? 3 : 1 << rank; }
        uint32_t fb;
        if (spare) {
          p.pat = 0x55555000u;
#pragma unroll 1
          for (int r = 0; r < 7; r++) {
            const int ch = ((r < 2 ? r : r == 2 ? 6 : r - 1) * 4 + j) * 2;
#pragma unroll 1
            for (int k = 0; k < 16; k++) { const uint32_t a = p.acquire<2>(fb); p.load_wide(P, 1, a, fb, k, ch); }
          }
        } else {
          const int row0 = g * 128, par = g & 1, pair0 = (g >> 1) * 128;
          TL(2, 0);
          p.sync = ptr_add(&g_sync[0], (uint32_t)(g >> 2) * 2048u);
#pragma unroll 1
          for (int hl = 0; hl < 4; hl++) {
            const int ffn = hl & 1, evb = (hl >> 1) * EV_N;
            const int xev = ffn ? evb + EV_XA : EV_XB, xrow = (ffn ? 0 : SEQ) + row0;
            auto load_x = [&](uint32_t dst, int k) {
              if (hl == 0) tma_ld3(dst, &P.map[M_XIN], fb, k * 64, par, pair0); else tma_ld2(dst, &P.map[M_ACT_LD], fb, k * 64, xrow);
            };
            p.pat = ffn ? Pat<3>::v : hl ? Pat<7>::v : Pat<0>::v; p.addr = 0;
#pragma unroll 1
            for (int s = 0; s < 2; s++) { const uint32_t a = p.acquire<2>(fb); p.load_wide(P, ffn, a, fb, 2 * j + s, 2 * j); }
#pragma unroll 1
            for (int s = 0; s < 2; s++) { const uint32_t a = p.acquire<1>(fb); p.load_narrow(P, ffn, a, fb, 2 * j + s, j); }
#pragma unroll 1
            for (int hf = 0; hf < 2; hf++) {
              p.ready = hl ? 0 : 0xffu;
#pragma unroll 1
              for (int m = 0; m < 7; m++) {
                const int jj = m == j ? 7 : m, k = 2 * jj + hf;
                if (m == (hf ? 5 : 1)) p.pace_arrive();
                if (m == (hf ? 6 : 2)) p.pace_peek();
                if (PACING && hl == 0 && hf == 0 && m == 2) p.target = ld_relaxed(epoch_ptr()) * 32;
                if (hf == 0 && m == 3) p.pace_wait();
                const uint32_t a = p.acquire<3>(fb);
                p.load_wide(P, ffn, a + PAGE, fb, k, 2 * j);
                p.need(xev + hf, 1u << jj);
                load_x(a, k);
              }
              p.need(xev + hf, 0xffu);
            }
            static_assert(Pat<1>::v == Pat<4>::v, "");
            p.pat = Pat<1>::v;
            p.pace_wait();
#pragma unroll 1
            for (int m = 0; m < 14; m++) {
              const int k = (m >> 1) == j ? 14 + (m & 1) : m;
              const uint32_t a = p.acquire<2>(fb);
              p.load_narrow(P, ffn, a + PAGE, fb, k, j);
              load_x(a, k);
            }
            if (!ffn) {
              p.pat = Pat<2>::v;
#pragma unroll 1
              for (int s = 0; s < 2; s++) { const uint32_t a = p.acquire<1>(fb); p.load_b(a, 8192, &P.map[M_WO], 0, fb, 2 * j + s, 2 * j, 1); }
              { const uint32_t a = p.acquire<2>(fb); load_x(a, 2 * j); load_x(a + PAGE, 2 * j + 1); }
#pragma unroll 1
              for (int hf = 0; hf < 2; hf++) {
                p.ready = 0;
#pragma unroll 1
                for (int m = 0; m < 7; m++) {
                  const int jj = m == j ? 7 : m, k = 2 * jj + hf;
                  const uint32_t a = p.acquire<2>(fb);
                  p.load_b(a + PAGE, 8192, &P.map[M_WO], 0, fb, k, 2 * j, 1);
                  p.need(evb + EV_OA + hf, 1u << jj);
                  tma_ld2(a, &P.map[M_ACT_LD], fb, k * 64, 2 * SEQ + row0);
                }
              }
            } else {
              p.pat = Pat<5>::v; p.addr = 6 * PAGE;
#pragma unroll 1
              for (int s = 16; s < 48; s++) {
                const int pi = (s >> 1) & 7;
                const int k = (s < 32 ? pi : pi == 4 ? j : pi == j ? 4 : pi) * 2 + (s & 1);
                if (s == 48 - 2) p.pace_arrive();
                if (s == 48 - 1) p.pace_peek();
                const uint32_t a = p.acquire<3>(fb);
                p.load_wide(P, 1, a + PAGE, fb, k, (s & 48) + 2 * j);
                tma_ld2(a, &P.map[M_ACT_LD], fb, k * 64, row0);
              }
              p.pat = Pat<6>::v;
              p.pace_wait();
#pragma unroll 1
              for (int s = 0; s < 56; s++) {
                if (s == 0 || s == 16 || s == 24 || s == 40) { p.ready = 0; p.need(evb + EV_H0 + ((s + 8) >> 4), 0xffu); }
                const int k = s < 16 ? s : s < 24 ? s + 32 : s - 8;
                const uint32_t a = p.acquire<2>(fb);
                p.load_b(a + PAGE, 8192, &P.map[M_W2], 0, fb, k, 2 * j, 1);
                tma_ld2(a, &P.map[M_H_LD], fb, k * 64, row0);
              }
            }
            TL(2, 1 + hl);
          }
        }
        p.finish();
      }
    } else if (!spare) {
      const uint32_t tag = ld_relaxed(epoch_ptr());
      mbar_wait(sb + BAR_XIN, 0);
      if (elect_one()) prefetch_l2(ptr_add(P.wqkv, (role * 3 + (warp - 9)) * 16384u), 16384);
#pragma unroll 1
      for (int r = 0; r < 2; r++) {
        const uint32_t u = role * 3 + (warp - 9) + r * 384;
        const uint32_t strip = u < 512 ? 64 + (u >> 2) : (u - 512) >> 2, part = u & 3;
        const uint32_t col = strip * 16 + (lane & 1) * 8;
        const uint4* wp = ptr_add((const uint4*)P.wqkv, (part * 256 + (lane >> 1)) * 6144u + col * 2);
        float s[8] = {0, 0, 0, 0, 0, 0, 0, 0};
        uint4 v[4];
#pragma unroll
        for (int i = 0; i < 4; i++) v[i] = __ldcg(wp + i * (16 * 6144 / 16));
#pragma unroll 1
        for (int b = 0; b < 4; b++) {
          wp += 64 * 6144 / 16;
#pragma unroll
          for (int i = 0; i < 4; i++) {
            s[0] += bf_lo(v[i].x); s[1] += bf_hi(v[i].x); s[2] += bf_lo(v[i].y); s[3] += bf_hi(v[i].y);
            s[4] += bf_lo(v[i].z); s[5] += bf_hi(v[i].z); s[6] += bf_lo(v[i].w); s[7] += bf_hi(v[i].w);
            if (b < 3) v[i] = __ldcg(wp + i * (16 * 6144 / 16));
          }
        }
#pragma unroll
        for (int e = 0; e < 4; e++) { const bool h = lane & 16; const float t = __shfl_xor_sync(0xffffffffu, h ? s[e] : s[e + 4], 16); s[e] = (h ? s[e + 4] : s[e]) + t; }
#pragma unroll
        for (int e = 0; e < 2; e++) { const bool h = lane & 8; const float t = __shfl_xor_sync(0xffffffffu, h ? s[e] : s[e + 2], 8); s[e] = (h ? s[e + 2] : s[e]) + t; }
        { const bool h = lane & 4; const float t = __shfl_xor_sync(0xffffffffu, h ? s[0] : s[1], 4); s[0] = (h ? s[1] : s[0]) + t; }
        s[0] += __shfl_xor_sync(0xffffffffu, s[0], 2);
        if (!(lane & 2)) st_relaxed(ptr_add((uint32_t*)&g_cs[0], (col + (lane >> 2)) * 16 + part * 4), tagf(s[0], tag));
        __syncwarp();
      }
      if (warp == 11 && lane == 0) TL(2, 30);
      if (warp <= 10) {
        const int w = warp - 9;
        if (elect_one()) {
          if (w == 0) { prefetch_map(&P.map[M_ACT_ST]); prefetch_map(&P.map[M_ACT_LD]); prefetch_map(&P.map[M_WO]); prefetch_map(&P.map[M_W1 + rank]); }
          else { prefetch_map(&P.map[M_H_ST]); prefetch_map(&P.map[M_H_LD]); prefetch_map(&P.map[M_W1H + rank]); prefetch_map(&P.map[M_W2]); prefetch_map(&P.map[M_OUT_ST]); }
        }
        uint32_t* fl = ptr_add(&g_flags[0], (uint32_t)(g * 256 + j) * 4u);
        int pe = 0;
#pragma unroll 1
        for (int hl = 0; hl < 4; hl++) {
          const int l = hl >> 1;
          if (w == 1) {
#pragma unroll 1
            for (int r = 0; r < 4; r++) {
              const uint2* sp = ptr_add(&g_stats[0], ((uint32_t)hl * 2048u + g * 128 + r * 32 + lane) * 64u);
              uint4 v[4]; uint32_t spins = 0; bool ok;
              do {
                ok = true;
#pragma unroll
                for (int m = 0; m < 4; m++) { v[m] = ld_relaxed4(sp + 2 * m); ok = ok && tag_ok4(v[m], tag); }
                spin_check(++spins);
              } while (__any_sync(0xffffffffu, !ok));
              float mean = 0, m2 = 0;
#pragma unroll
              for (int m = 0; m < 4; m++) mean += untag(v[m].x) + untag(v[m].z);
              mean *= 0.125f;
#pragma unroll
              for (int m = 0; m < 4; m++) {
                const float d0 = untag(v[m].x) - mean, d1 = untag(v[m].z) - mean;
                m2 += untag(v[m].y) + untag(v[m].w) + 128.0f * (d0 * d0 + d1 * d1);
              }
              sts64f(sb + SM_ROW + (r * 32 + lane) * 8, mean, rsqrtf(fmaxf(m2, 0.f) * (1.0f / DM) + LN_EPS));
            }
            __syncwarp();
            if (lane == 0) { mbar_arrive(sb + BAR_STAT); TL(2, 8 + hl); }
          }
          if (!(hl & 1)) {
              const uint32_t slot = sb + SM_STAGE + 7 * 4096 + w * 2048 + lane * 16;
              const uint32_t hoff = (uint32_t)((l * 16 + g) * 8 + j) * 8192u + w * 4096u + lane * 16u;
              mbar_wait(sb + BAR_XFULL, l);
              if (g < 14) {
                uint4* hp = ptr_add(&g_halo[0], hoff);
#pragma unroll
                for (int i = 0; i < 4; i++) { uint32_t a0, a1, a2, a3; lds128(slot + i * 512, a0, a1, a2, a3); ll_store(hp + i * 64, a0, a1, tag); ll_store(hp + i * 64 + 32, a2, a3, tag); }
              }
              const uint4* hp = ptr_add(&g_halo[0], hoff - 2 * 8 * 8192u);
#pragma unroll 1
              for (int i = 0; i < 2; i++) {
                uint4 v[4];
                v[0] = v[1] = v[2] = v[3] = make_uint4(0, 0, 0, 0);
                if (g >= 2) {
                  uint32_t spins = 0, bad;
                  do {
                    bad = 0;
#pragma unroll
                    for (int m = 0; m < 4; m++) { v[m] = ll_load(hp + m * 32); bad |= (v[m].y ^ tag) | (v[m].w ^ tag); }
                    spin_check(++spins);
                  } while (__any_sync(0xffffffffu, bad != 0));
                }
                sts128(slot + i * 1024, v[0].x, v[0].z, v[1].x, v[1].z);
                sts128(slot + i * 1024 + 512, v[2].x, v[2].z, v[3].x, v[3].z);
                hp += 128;
              }
              __syncwarp();
              if (lane == 0) mbar_arrive(sb + BAR_HALO);
          }
          if (w == 0) {
            if (elect_one()) {
#pragma unroll 1
              for (int q = (hl & 1) ? EV_H0 : EV_OA; q < ((hl & 1) ? EV_N : EV_H0); q++) {
                const bool is_h = q >= EV_H0 && q < EV_XB, last = hl == 3 && !is_h;
                const int e = l * EV_N + q;
#pragma unroll 1
                for (int hb = is_h ? q == EV_H3 : q & 1; hb <= (is_h ? 1 : q & 1); hb++) {
                  const int col = !is_h ? j * 128 + hb * 64 : q == EV_H3 ? 3072 + j * 64 : (q == EV_H0 ? 0 : q - EV_H3) * 1024 + j * 128 + hb * 64;
#pragma unroll 1
                  for (int wg = 0; wg < 2; wg++) {
                    mbar_wait(sb + BAR_SFULL + 16 * wg + 8 * (pe & 1), (pe >> 1) & 1);
                    if (wg == 0) TL(3, 20 + e);
                    const uint32_t src = sb + SM_STAGE + wg * PAGE + hb * 8192;
                    if (last) tma_st3(&P.map[M_OUT_ST], src, col, g & 1, (g >> 1) * 128 + wg * 64);
                    else if (is_h) tma_st2(&P.map[M_H_ST], src, col, g * 128 + wg * 64);
                    else tma_st2(&P.map[M_ACT_ST], src, col, (q < EV_XA ? 2 * SEQ : q < EV_H0 ? 0 : SEQ) + g * 128 + wg * 64);
                  }
                  pe++;
                }
                bulk_commit();
                if (!(last && q == EV_XB)) bulk_wait<0>();
                TL(3, 40 + e);
                if (is_h || (q & 1)) mbar_arrive(sb + BAR_SEMPTY);
                if (!last) st_release(fl, tag);
                TL(3, e);
                fl += 8;
              }
            }
            __syncwarp();
          }
        }
        if (w == 0 && lane == 0) *epoch_ptr() = tag + 1;
      } else {
        const uint32_t* fl = ptr_add(&g_flags[0], (uint32_t)(g * 256 + (lane & 7)) * 4u);
        const uint32_t cspos = sb + SM_CS + ((lane & 16) + ((lane >> 1) & 3) * 4 + ((lane >> 3) & 1) * 2 + (lane & 1)) * 4;
        int e = 0;
#pragma unroll 1
        for (int it = 0; it < 8; it++) {
          const int t = it & 3;
          if (it) mbar_wait(sb + BAR_CSE, (it - 1) & 1);
#pragma unroll 1
          for (int b = 0; b < (t < 2 ? 3 : 2); b++) {
            uint32_t c0, c1;
            if (b < 2) { c0 = (t ? 2048 + t * 1024 + b * FF : 1024 + b * 1024) + j * 128; c1 = c0 + 64; }
            else if (t) { c0 = 6144 + j * 64; c1 = c0 + FF; }
            else { c0 = j * 128; c1 = c0 + 64; }
            const uint4* p0 = ptr_add(&g_cs[0], (c0 + lane) * 16u);
            const uint4* p1 = ptr_add(&g_cs[0], (c1 + lane) * 16u);
            uint4 v[4]; uint32_t spins = 0; bool ok;
            do {
              v[0] = ld_relaxed4(p0); v[1] = ld_relaxed4(p0 + 32); v[2] = ld_relaxed4(p1); v[3] = ld_relaxed4(p1 + 32);
              ok = tag_ok4(v[0], tag) && tag_ok4(v[1], tag) && tag_ok4(v[2], tag) && tag_ok4(v[3], tag);
              spin_check(++spins);
            } while (__any_sync(0xffffffffu, !ok));
#pragma unroll
            for (int m = 0; m < 4; m++) sts32f(cspos + b * 512 + m * 128, (untag(v[m].x) + untag(v[m].y)) + (untag(v[m].z) + untag(v[m].w)));
          }
          __syncwarp();
          if (lane == 0) { mbar_arrive(sb + BAR_CSF); TL(2, 16 + it); }
          const int eend = e + (it == 0 ? 3 : t == 0 ? 5 : t == 1 ? 1 : 2);
#pragma unroll 1
          for (; e < eend; e++) {
            uint32_t seen = 0, spins = 0;
            do {
              uint32_t v;
              asm volatile("ld.acquire.gpu.global.u32 %0, [%1];" : "=r"(v) : "l"(fl) : "memory");
              const uint32_t m = __ballot_sync(0xffffffffu, v == tag) & 0xffu;
              if (m != seen) {
                seen = m;
                if (lane == 0) asm volatile("st.volatile.shared.u32 [%0], %1;" :: "r"(sb + SM_READY + e * 4), "r"(m) : "memory");
              }
              spin_check(++spins);
            } while (seen != 0xffu);
            fl += 8;
          }
        }
      }
    }
  } else {
    asm volatile("setmaxnreg.inc.sync.aligned.u32 232;");
    const int wg = warp >> 2;
    const int quad = lane & 3, gr = lane >> 2;
    Cons c; c.sb = sb; c.n = 0; c.off = 0; c.prev = 0; c.lane = lane;
    c.ebar = mapa(sb + BAR_EMPTY - 64, shared_b() ? lane & 1 : rank);
    const uint32_t stage = sb + SM_STAGE + wg * PAGE;
    const uint32_t dstage = desc_lo(stage, 16);
    if (spare) {
      const uint32_t tag = ld_relaxed(epoch_ptr());
      const int tid = threadIdx.x & 127;
#pragma unroll
      for (int i = 0; i < 4; i++) sts128(stage + (i * 128 + tid) * 16, 0x3f803f80u, 0x3f803f80u, 0x3f803f80u, 0x3f803f80u);
      fence_async_smem();
      bar_sync(2 + wg, 128);
      c.db0 = desc_lo(sb + wg * PAGE, 8192);
#pragma unroll 1
      for (int r = 0; r < 7; r++) {
        float acc[64];
#pragma unroll 1
        for (int k = 0; k < 16; k++) c.step_ab<128, 2>(acc, dstage, c.db0 + c.off, k);
        c.drain();
        acc_fence<64>(acc);
        if (tid < 16) {
          uint32_t* op = ptr_add((uint32_t*)&g_cs[0], (uint32_t)(3 * DM + wg * FF + ((r < 2 ? r : r == 2 ? 6 : r - 1) * 4 + j) * 128 + quad * 2) * 16u + gr * 4);
#pragma unroll
          for (int b = 0; b < 16; b++) { st_relaxed(op + b * 32, tagf(gr ? 0.f : acc[4 * b], tag)); st_relaxed(op + b * 32 + 4, tagf(gr ? 0.f : acc[4 * b + 1], tag)); }
        }
        __syncwarp();
      }
      if (wg == 0) {
        const uint32_t* p = ptr_add((const uint32_t*)&g_stats[0], (uint32_t)((tid >> 3) * 1024 + (tid & 7)) * 8u);
        uint32_t spins = 0;
        while (__any_sync(0xffffffffu, (ld_relaxed(p) ^ tag) & 15u)) spin_check(++spins);
      }
      bar_sync(1, 256);
      if (threadIdx.x == 0) *epoch_ptr() = tag + 1;
    } else {
    c.da0 = desc_lo(sb + wg * 8192, 16); c.db0 = desc_lo(sb, 8192);
    uint32_t sphase = 1, sfull = sb + BAR_SFULL + 16 * wg;
    const uint32_t maddr = stage + ((warp & 3) * 16 + (lane & 15)) * 128 + (((lane >> 4) ^ (lane & 7)) << 4);
    const uint32_t csaddr = sb + SM_CS + quad * 16;
    float mean[2] = {0, 0}, rstd[2] = {0, 0};
    const uint32_t tag = ld_relaxed(epoch_ptr());
    TL(wg, 0); TLG(62);

    auto stage_wait = [&]() { mbar_wait_fast(sb + BAR_SEMPTY, sphase); sphase ^= 1; };
    auto stage_publish = [&]() { fence_async_smem(); __syncwarp(); if (lane == 0) mbar_arrive(sfull); sfull ^= 8; };
    auto cs_load = [&](uint32_t (&cs)[16], int grp) {
#pragma unroll
      for (int i = 0; i < 4; i++) lds128(csaddr + grp * 256 + i * 64, cs[4 * i], cs[4 * i + 1], cs[4 * i + 2], cs[4 * i + 3]);
    };
    auto cs_apply = [&](float* acc, uint32_t (&cs)[16]) {
      acc_fence<32>(acc);
#pragma unroll
      for (int b = 0; b < 8; b++) {
        acc[4 * b] -= mean[0] * __uint_as_float(cs[2 * b]); acc[4 * b + 1] -= mean[0] * __uint_as_float(cs[2 * b + 1]);
        acc[4 * b + 2] -= mean[1] * __uint_as_float(cs[2 * b]); acc[4 * b + 3] -= mean[1] * __uint_as_float(cs[2 * b + 1]);
      }
      acc_fence<32>(acc);
    };
    auto glu_slice = [&](const uint32_t (&pk)[64], int i, bool scaled) {
      uint32_t hp[4];
#pragma unroll
      for (int e = 0; e < 4; e++) {
        const float g0 = bf_lo(pk[4 * i + e]), g1 = bf_hi(pk[4 * i + e]), u0 = bf_lo(pk[32 + 4 * i + e]), u1 = bf_hi(pk[32 + 4 * i + e]);
        if (scaled) hp[e] = pack_bf16(g0 * u0 * rcp(1.0f + ex2(g0 * -LOG2E)), g1 * u1 * rcp(1.0f + ex2(g1 * -LOG2E)));
        else {
          const float nl = -LOG2E * rstd[e & 1], r2 = rstd[e & 1] * rstd[e & 1];
          hp[e] = pack_bf16(g0 * u0 * r2 * rcp(1.0f + ex2(g0 * nl)), g1 * u1 * r2 * rcp(1.0f + ex2(g1 * nl)));
        }
      }
      stsm4((maddr ^ ((i & 3) << 5)) + (i >> 2) * 8192, hp[0], hp[1], hp[2], hp[3]);
    };

    mbar_wait_fast(sb + BAR_XIN, 0);
#pragma unroll 1
    for (int hl = 0; hl < 4; hl++) {
      int t = hl & 1;
      float acc[128], acc2[64];
      {
        c.off = 0; asm volatile("" : "+r"(c.off));
        float piv[2], s1[2] = {0, 0}, s2[2] = {0, 0};
#pragma unroll
        for (int s = 0; s < 4; s++) {
          if (s < 2) c.step_own<256>(acc, dstage + s * 512, s); else c.step_own<128>(acc2, dstage + (s - 2) * 512, s - 2);
#pragma unroll
          for (int i = (s < 2 ? 3 * s : 4 + s); i < (s < 2 ? 3 * s + 3 : 5 + s); i++) {
            uint32_t v[4];
            ldsm4((maddr ^ ((i & 3) << 5)) + (i >> 2) * 8192, v[0], v[1], v[2], v[3]);
            if (i == 0) { piv[0] = bf_lo(v[0]); piv[1] = bf_lo(v[1]); }
#pragma unroll
            for (int e = 0; e < 4; e++) {
              const float a = bf_lo(v[e]) - piv[e & 1], b = bf_hi(v[e]) - piv[e & 1];
              s1[e & 1] += a + b; s2[e & 1] += a * a; s2[e & 1] += b * b;
            }
          }
        }
#pragma unroll
        for (int r = 0; r < 2; r++) {
          const float mt = piv[r] + s1[r] * (1.0f / 32);
          float m = mt + __shfl_xor_sync(0xffffffffu, mt, 1); m += __shfl_xor_sync(0xffffffffu, m, 2); m *= 0.25f;
          float q = s2[r] - s1[r] * s1[r] * (1.0f / 32) + 32.0f * (mt - m) * (mt - m);
          q += __shfl_xor_sync(0xffffffffu, q, 1); q += __shfl_xor_sync(0xffffffffu, q, 2);
          if (quad == 0) st_relaxed2(ptr_add(&g_stats[0], (uint32_t)(hl * 2048 + g * 128 + warp * 16 + r * 8 + gr) * 64u + j * 8), tagf(m, tag), tagf(q, tag));
        }
        c.steps<256>(acc, 9);
        mbar_wait_fast(sb + BAR_STAT, t);
        {
          const uint32_t ra = sb + SM_ROW + (warp * 16 + gr) * 8;
          const float2 a = lds64f(ra), b = lds64f(ra + 64);
          mean[0] = a.x; rstd[0] = a.y; mean[1] = b.x; rstd[1] = b.y;
        }
      }
#pragma unroll 1
      for (;;) {
      const int it = (hl >> 1) * 4 + t;
#pragma unroll
      for (int s = 0; s < 4; s++) {
        uint32_t cs[16];
        c.step<256>(acc);
        if (s == 0) mbar_wait_fast(sb + BAR_CSF, t & 1);
        if (s >= 2 && t <= 1) { cs_load(cs, 2 + s); cs_apply(acc2 + 32 * (s - 2), cs); }
        cs_load(cs, s);
        c.drain();
        cs_apply(acc + 32 * s, cs);
      }
      c.step<256>(acc);
      if (lane == 0) mbar_arrive(sb + BAR_CSE);
      c.drain();
      acc_fence<128>(acc);
      TL(wg, 1 + it * 6);
      uint32_t pkB[64];
      if (t == 2) {
#pragma unroll
        for (int i = 0; i < 64; i++) pkB[i] = pack_bf16(acc[2 * i], acc[2 * i + 1]);
      } else {
      uint32_t pkA[64];
#pragma unroll
      for (int i = 0; i < 64; i++) pkA[i] = pack_bf16(acc[2 * i] * rstd[i & 1], acc[2 * i + 1] * rstd[i & 1]);
      if (t == 0) {
        const uint32_t xa = sb + SM_STAGE + lane * 16;
        c.step<128>(acc2);
        stage_wait();
#pragma unroll
        for (int i = 0; i < 4; i++) sts128(xa + warp * 4096 + i * 512, pkA[8 * i + 1], pkA[8 * i + 3], pkA[8 * i + 5], pkA[8 * i + 7]);
#pragma unroll
        for (int s = 0; s < 4; s++) {
          c.step<128>(acc2);
          if (s == 2) { __syncwarp(); if (lane == 0) mbar_arrive(sb + BAR_XFULL); }
#pragma unroll
          for (int i = 0; i < 8; i++) { const int r = 32 + (s & 1) * 16 + 2 * i + (s < 2); pkA[r] = movm(pkA[r]); }
          if (s < 2) {
#pragma unroll
            for (int i = 4 + 2 * s; i < 6 + 2 * s; i++) sts128(xa + warp * 4096 + i * 512, pkA[8 * i + 1], pkA[8 * i + 3], pkA[8 * i + 5], pkA[8 * i + 7]);
          }
        }
        c.steps<128>(acc2, 6);
        uint32_t kvH[32];
        mbar_wait_fast(sb + (warp ? BAR_XFULL : BAR_HALO), hl >> 1);
#pragma unroll
        for (int s = 0; s < 3; s++) {
          c.step<128>(acc2);
#pragma unroll
          for (int i = s * 3; i < s * 3 + 3 && i < 8; i++) lds128(xa + ((warp + 7) & 7) * 4096 + i * 512, kvH[4 * i], kvH[4 * i + 1], kvH[4 * i + 2], kvH[4 * i + 3]);
        }
        c.drain();
        acc_fence<64>(acc2);
        TL(wg, 2 + it * 6);
        uint32_t q[32];
#pragma unroll
        for (int i = 0; i < 32; i++) q[i] = pack_bf16(acc2[2 * i], acc2[2 * i + 1]);
        bar_sync(1, 256);
        const bool nohalo = (warp == 0 && g < 2);
        const bool c0 = (2 * quad <= gr), c1 = (2 * quad + 1 <= gr);
        const float sc0 = rstd[0] * (0.17677669529663687f * LOG2E), sc1 = rstd[1] * (0.17677669529663687f * LOG2E);
#pragma unroll
        for (int hf = 0; hf < 2; hf++) {
          uint32_t op[16];
#pragma unroll
          for (int hh = 0; hh < 2; hh++) {
            const int h = hf * 2 + hh;
            float sH[4] = {0, 0, 0, 0}, sL[4] = {0, 0, 0, 0}, sU[4] = {0, 0, 0, 0};
#pragma unroll
            for (int kk = 0; kk < 2; kk++) {
              const int b = h * 4 + kk * 2;
              mma16816(sH, q[2 * b], q[2 * b + 1], q[2 * b + 2], q[2 * b + 3], kvH[b], kvH[b + 1]);
              mma16816(sL, q[2 * b], q[2 * b + 1], q[2 * b + 2], q[2 * b + 3], pkA[2 * b], pkA[2 * b + 2]);
              mma16816(sU, q[2 * b], q[2 * b + 1], q[2 * b + 2], q[2 * b + 3], pkA[2 * b + 1], pkA[2 * b + 3]);
            }
            float a0 = (c0 ? sL[0] : sH[0]) * sc0, a1 = (c1 ? sL[1] : sH[1]) * sc0;
            float b0 = (c0 ? sU[2] : sL[2]) * sc1, b1 = (c1 ? sU[3] : sL[3]) * sc1;
            if (nohalo) { if (!c0) a0 = -1e9f * LOG2E; if (!c1) a1 = -1e9f * LOG2E; }
            float ma = fmaxf(a0, a1), mb = fmaxf(b0, b1);
            ma = fmaxf(ma, __shfl_xor_sync(0xffffffffu, ma, 1)); mb = fmaxf(mb, __shfl_xor_sync(0xffffffffu, mb, 1));
            ma = fmaxf(ma, __shfl_xor_sync(0xffffffffu, ma, 2)); mb = fmaxf(mb, __shfl_xor_sync(0xffffffffu, mb, 2));
            a0 = ex2(a0 - ma); a1 = ex2(a1 - ma); b0 = ex2(b0 - mb); b1 = ex2(b1 - mb);
            const uint32_t pa = pack_bf16(a0, a1), pb = pack_bf16(b0, b1);
            const uint32_t lm = (c0 ? 0xffffu : 0u) | (c1 ? 0xffff0000u : 0u);
            float sa = bf_lo(pa) + bf_hi(pa), sbb = bf_lo(pb) + bf_hi(pb);
            sa += __shfl_xor_sync(0xffffffffu, sa, 1); sbb += __shfl_xor_sync(0xffffffffu, sbb, 1);
            sa += __shfl_xor_sync(0xffffffffu, sa, 2); sbb += __shfl_xor_sync(0xffffffffu, sbb, 2);
            const float ra = rcp(sa), rb = rcp(sbb);
#pragma unroll
            for (int d = 0; d < 4; d++) {
              const int b = h * 4 + d;
              float o[4] = {0, 0, 0, 0};
              mma16816(o, pa & ~lm, 0u, pa & lm, pb & ~lm, kvH[16 + b], pkA[32 + 2 * b]);
              mma1688(o, 0u, pb & lm, pkA[32 + 2 * b + 1]);
              op[(hh * 4 + d) * 2] = pack_bf16(o[0] * ra, o[1] * ra); op[(hh * 4 + d) * 2 + 1] = pack_bf16(o[2] * rb, o[3] * rb);
            }
          }
#pragma unroll
          for (int i = 0; i < 4; i++) stsm4((maddr ^ (i << 5)) + hf * 8192, op[4 * i], op[4 * i + 1], op[4 * i + 2], op[4 * i + 3]);
          stage_publish();
        }
        bar_sync(1, 256);
        TL(wg, 3 + it * 6);
#pragma unroll
        for (int s = 0; s < 2; s++) c.step_own<128>(acc2, dstage + s * 512, s);
        {
          mbar_wait_fast(sb + BAR_FULL + ((c.n & 7) << 3), (c.n >> 3) & 1);
          const uint32_t ra = maddr - (SM_STAGE + wg * 8192) + (c.off << 4), rbar = 64 + ((c.n & 7) << 3);
          c.advance<2>();
          uint32_t res[32];
#pragma unroll
          for (int i = 0; i < 8; i++) ldsm4((ra ^ ((i & 3) << 5)) + (i >> 2) * PAGE, res[4 * i], res[4 * i + 1], res[4 * i + 2], res[4 * i + 3]);
          c.drain();
          acc_fence<64>(acc2);
#pragma unroll
          for (int i = 0; i < 32; i++) { acc2[2 * i] += bf_lo(res[i]); acc2[2 * i + 1] += bf_hi(res[i]); }
          acc_fence<64>(acc2);
          __syncwarp();
          if (lane < 2) mbar_arrive_cluster(c.ebar + rbar);
        }
        break;
      } else {
        c.steps<128>(acc2, 1 + wg);
        stage_wait();
        glu_slice(pkA, 0, true);
#pragma unroll
        for (int s = 1; s < 8; s++) { c.steps<128>(acc2, (s & 1) || t == 3 ? 2 : 1); if (s == 4) stage_publish(); glu_slice(pkA, s, true); }
        c.step<128>(acc2);
        stage_publish();
        c.steps<128>(acc2, 1 - wg);
        if (t == 3) break;
        {
          c.drain();
          acc_fence<64>(acc2);
        TL(wg, 2 + it * 6);
#pragma unroll
          for (int i = 0; i < 16; i++) {
            pkB[i] = 0; pkB[32 + i] = 0;
            pkB[16 + i] = pack_bf16(acc2[2 * i], acc2[2 * i + 1]);
            pkB[48 + i] = pack_bf16(acc2[32 + 2 * i], acc2[32 + 2 * i + 1]);
          }
        }
      }
      }
      t++;
        if (t == 2) { c.off = 6 << 10; asm volatile("" : "+r"(c.off)); }
        c.step<256>(acc, 0);
        if (t == 3) {
          stage_wait();
          glu_slice(pkB, 0, false);
#pragma unroll
          for (int s = 1; s < 4; s++) { c.step<256>(acc); glu_slice(pkB, s, false); }
        } else {
          c.steps<256>(acc, 3);
          stage_wait();
        }
#pragma unroll
        for (int s = 4; s < 8; s++) { c.step<256>(acc); if (s == 4 && t == 3) stage_publish(); glu_slice(pkB, s, false); }
#pragma unroll
        for (int s = 0; s < 2; s++) {
          const uint32_t ra = maddr - (SM_STAGE + wg * 8192) + (c.off << 4);
          c.step<256>(acc);
          if (s == 0) stage_publish();
#pragma unroll
          for (int i = 0; i < 4; i++) {
            uint32_t v[4];
            ldsm4(ra ^ (i << 5), v[0], v[1], v[2], v[3]);
#pragma unroll
            for (int e = 0; e < 4; e++) { acc2[32 * s + 8 * i + 2 * e] = bf_lo(v[e]); acc2[32 * s + 8 * i + 2 * e + 1] = bf_hi(v[e]); }
          }
          acc_fence<32>(acc2 + 32 * s);
        }
        c.step<256>(acc);
      }
      const int it = (hl >> 1) * 4 + t;
      c.steps<128>(acc2, t ? 39 : 14);
      stage_wait();
      c.drain();
      acc_fence<64>(acc2);
      TL(wg, 4 + it * 6);
#pragma unroll
      for (int hf = 0; hf < 2; hf++) {
#pragma unroll
        for (int i = 4 * hf; i < 4 * hf + 4; i++) {
          uint32_t v[4];
#pragma unroll
          for (int e = 0; e < 4; e++) v[e] = pack_bf16(acc2[8 * i + 2 * e], acc2[8 * i + 2 * e + 1]);
          stsm4((maddr ^ ((i & 3) << 5)) + hf * 8192, v[0], v[1], v[2], v[3]);
        }
        stage_publish();
      }
      bar_sync(2 + wg, 128);
      TL(wg, 5 + it * 6); TLG(63);
    }
    }
  }
}

typedef CUresult (*EncodeFn)(CUtensorMap*, CUtensorMapDataType, cuuint32_t, void*, const cuuint64_t*, const cuuint64_t*, const cuuint32_t*,
                             const cuuint32_t*, CUtensorMapInterleave, CUtensorMapSwizzle, CUtensorMapL2promotion, CUtensorMapFloatOOBfill);

void encode(EncodeFn fn, CUtensorMap* m, const void* ptr, int rank, const cuuint64_t* dims, const cuuint64_t* strides, const cuuint32_t* box) {
  cuuint32_t es[5] = {1, 1, 1, 1, 1};
  fn(m, CU_TENSOR_MAP_DATA_TYPE_BFLOAT16, rank, const_cast<void*>(ptr), dims, strides, box, es, CU_TENSOR_MAP_INTERLEAVE_NONE,
     CU_TENSOR_MAP_SWIZZLE_128B, CU_TENSOR_MAP_L2_PROMOTION_L2_128B, CU_TENSOR_MAP_FLOAT_OOB_FILL_NONE);
}

}

extern "C" void kernel_launch(void* const* d_in, const int* in_sizes, int n_in, void* d_out, int out_size) {
  const __nv_bfloat16* x = (const __nv_bfloat16*)d_in[0];
  const __nv_bfloat16* wqkv = (const __nv_bfloat16*)d_in[1];
  const __nv_bfloat16* wo = (const __nv_bfloat16*)d_in[2];
  const __nv_bfloat16* w1 = (const __nv_bfloat16*)d_in[4];
  const __nv_bfloat16* w3 = (const __nv_bfloat16*)d_in[5];
  const __nv_bfloat16* w2 = (const __nv_bfloat16*)d_in[6];

  void* fnp = nullptr; cudaDriverEntryPointQueryResult qr;
  cudaGetDriverEntryPoint("cuTensorMapEncodeTiled", &fnp, cudaEnableDefault, &qr);
  EncodeFn fn = (EncodeFn)fnp;
  void *act, *h;
  cudaGetSymbolAddress(&act, g_act); cudaGetSymbolAddress(&h, g_h);

  Params P = {};
  { cuuint64_t d[3] = {DM, 2, SEQ / 2}, s[2] = {DM * 2, DM * 4}; cuuint32_t b[3] = {64, 1, 128}, b2[3] = {64, 1, 64};
    encode(fn, &P.map[M_XIN], x, 3, d, s, b); encode(fn, &P.map[M_XIN64], x, 3, d, s, b2); encode(fn, &P.map[M_OUT_ST], d_out, 3, d, s, b2); }
  { cuuint64_t d[2] = {DM, 3 * SEQ}, s[1] = {DM * 2}; cuuint32_t b[2] = {64, 128}, b2[2] = {64, 64};
    encode(fn, &P.map[M_ACT_LD], act, 2, d, s, b); encode(fn, &P.map[M_ACT_ST], act, 2, d, s, b2); }
  { cuuint64_t d[2] = {FF, SEQ}, s[1] = {FF * 2}; cuuint32_t b[2] = {64, 128}, b2[2] = {64, 64};
    encode(fn, &P.map[M_H_LD], h, 2, d, s, b); encode(fn, &P.map[M_H_ST], h, 2, d, s, b2); }
  { const cuuint32_t b2[3] = {64, 64, 2}, b1[3] = {64, 64, 1};
    { cuuint64_t d[3] = {64, DM, 48}, s[2] = {3 * DM * 2, 128}; encode(fn, &P.map[M_WKV], wqkv, 3, d, s, b2); encode(fn, &P.map[M_WQ], wqkv, 3, d, s, b1); }
    { cuuint64_t d[3] = {64, DM, 16}, s[2] = {DM * 2, 128}; encode(fn, &P.map[M_WO], wo, 3, d, s, b1); }
    { cuuint64_t d[3] = {64, FF, 16}, s[2] = {DM * 2, 128}; encode(fn, &P.map[M_W2], w2, 3, d, s, b1); }
    { cuuint64_t d[3] = {64, DM, FF / 64}, s[2] = {FF * 2, 128};
      encode(fn, &P.map[M_W1], w1, 3, d, s, b2); encode(fn, &P.map[M_W3], w3, 3, d, s, b2);
      encode(fn, &P.map[M_W1H], w1, 3, d, s, b1); encode(fn, &P.map[M_W3H], w3, 3, d, s, b1); }
  }
  P.wqkv = wqkv; P.wo = wo; P.w2 = w2;
  int dev = 0, sms = 0;
  cudaGetDevice(&dev);
  cudaDeviceGetAttribute(&sms, cudaDevAttrMultiProcessorCount, dev);
  P.use_smid = (sms == 132);
  cudaFuncSetAttribute(fused_kernel, cudaFuncAttributeMaxDynamicSharedMemorySize, SM_TOTAL);
  fused_kernel<<<132, 384, SM_TOTAL>>>(P);
}
```

```cpp
#include <cuda_runtime.h>
#include <cuda_bf16.h>
#include <cuda.h>
#include <stdint.h>

namespace {

constexpr int SEQ = 2048, DM = 1024, FF = 3584;
constexpr float LN_EPS = 1e-5f;
constexpr float LOG2E = 1.4426950408889634f;

__device__ __align__(1024) __nv_bfloat16 g_act[3 * SEQ * DM];
__device__ __align__(1024) __nv_bfloat16 g_h[SEQ * FF];
__device__ __align__(128) uint2 g_stats[4 * SEQ * 8];
__device__ __align__(128) uint4 g_cs[3 * DM + 2 * FF];
__device__ __align__(128) uint4 g_halo[2 * 16 * 8 * 16 * 32];
__device__ __align__(128) uint32_t g_flags[16 * 32 * 8];
#define ONES16 1, 1, 1, 1, 1, 1, 1, 1, 1, 1, 1, 1, 1, 1, 1, 1
__device__ uint32_t g_epoch[144] = {ONES16, ONES16, ONES16, ONES16, ONES16, ONES16, ONES16, ONES16, ONES16};

enum { M_XIN, M_XIN64, M_ACT_LD, M_ACT_ST, M_H_LD, M_H_ST, M_OUT_ST, M_WKV, M_WQ, M_WO, M_W1, M_W3, M_W1H, M_W3H, M_W2, M_COUNT };
struct alignas(64) Params {
  CUtensorMap map[M_COUNT];
  const __nv_bfloat16* wqkv;
  const __nv_bfloat16* wo;
  const __nv_bfloat16* w2;
  int use_smid;
};

constexpr uint32_t PAGE = 16384, NPAGE = 12;
constexpr uint32_t SM_STAGE = NPAGE * PAGE;
constexpr uint32_t SM_BAR = SM_STAGE + 2 * PAGE;
constexpr uint32_t SM_READY = SM_BAR + 256;
constexpr uint32_t SM_CS = SM_BAR + 384;
constexpr uint32_t SM_TOTAL = SM_CS + 1536;
static_assert(SM_TOTAL <= 232448, "shared memory");
constexpr uint32_t BAR_FULL = SM_BAR, BAR_EMPTY = SM_BAR + 64, BAR_SFULL = SM_BAR + 128, BAR_SEMPTY = SM_BAR + 160;
constexpr uint32_t BAR_XFULL = SM_BAR + 176, BAR_HALO = SM_BAR + 184, BAR_CSF = SM_BAR + 192;
constexpr uint32_t BAR_CSE = SM_BAR + 216, BAR_XIN = SM_BAR + 224, SM_ROLE = SM_BAR + 232;
enum { EV_OA, EV_OB, EV_XA, EV_XA2, EV_H0, EV_H3, EV_H1, EV_H2, EV_XB, EV_XB2, EV_N };

struct Sched { uint32_t pat[14]; uint32_t page0[14]; bool ok; };
constexpr int seg_steps(int seg) { return seg == 0 || seg == 3 ? 18 : seg == 1 || seg == 4 ? 14 : seg == 2 ? 17 : seg == 5 ? 32 : 56; }
constexpr int step_pages(int seg, int i) {
  return seg == 0 || seg == 3 ? (i < 2 ? 2 : i < 4 ? 1 : 3) : seg == 2 ? (i < 2 ? 1 : 2) : seg == 5 ? 3 : 2;
}
constexpr Sched make_sched() {
  Sched s = {};
  int owner[NPAGE] = {-1, -1, -1, -1, -1, -1, -1, -1, -1, -1, -1, -1};
  int n = 0, tail = 0, page = 0;
  s.ok = true;
  for (int sg = 0; sg < 14; sg++) {
    const int seg = sg % 7;
    if (seg == 5) page = (page + 2) / 3 * 3 % NPAGE;
    if (seg == 0) page = (page + 5) / 6 * 6 % NPAGE;
    s.page0[sg] = page;
    for (int i = 0; i < seg_steps(seg); i++) {
      const int p = step_pages(seg, i);
      if (page + p > (int)NPAGE) { s.ok = false; return s; }
      int need = n - 8;
      for (int q = 0; q < p; q++) { if (owner[page + q] > need) need = owner[page + q]; owner[page + q] = n; }
      int nw = need + 1 - tail; if (nw < 0) nw = 0;
      tail += nw;
      if (i < 16) s.pat[sg] |= (uint32_t)nw << (2 * i); else if (nw != 1) s.ok = false;
      if (nw > 3) s.ok = false;
      page = (page + p) % NPAGE; n++;
    }
  }
  for (int sg = 0; sg < 7; sg++) if (s.page0[sg] != s.page0[sg + 7] || (sg && s.pat[sg] != s.pat[sg + 7])) s.ok = false;
  return s;
}
constexpr Sched SCHED = make_sched();
static_assert(SCHED.ok && SCHED.page0[0] == 0 && SCHED.page0[3] == 0 && SCHED.page0[5] == 6 && (SCHED.pat[0] & 0xff) == 0, "ring schedule");
template <int SEG> struct Pat { static constexpr uint32_t v = SCHED.pat[SEG]; };

__device__ __forceinline__ uint32_t smem_u32(const void* p) { return (uint32_t)__cvta_generic_to_shared(p); }
__device__ __forceinline__ void mbar_init(uint32_t bar, uint32_t cnt) { asm volatile("mbarrier.init.shared::cta.b64 [%0], %1;" :: "r"(bar), "r"(cnt)); }
__device__ __forceinline__ void mbar_expect_tx(uint32_t bar, uint32_t bytes) { asm volatile("mbarrier.arrive.expect_tx.shared::cta.b64 _, [%0], %1;" :: "r"(bar), "r"(bytes) : "memory"); }
__device__ __forceinline__ void mbar_arrive(uint32_t bar) { asm volatile("mbarrier.arrive.shared::cta.b64 _, [%0];" :: "r"(bar) : "memory"); }
__device__ __forceinline__ void mbar_wait(uint32_t bar, uint32_t parity) {
  asm volatile("{\n.reg .pred p;\n.reg .u32 n;\nmov.u32 n, 0;\nLAB_WAIT:\n"
               "mbarrier.try_wait.parity.shared::cta.b64 p, [%0], %1;\n@p bra LAB_DONE;\n"
               "add.u32 n, n, 1;\nsetp.lt.u32 p, n, 4194304;\n@p bra LAB_WAIT;\ntrap;\nLAB_DONE:\n}" :: "r"(bar), "r"(parity) : "memory");
}
__device__ __forceinline__ void mbar_wait_fast(uint32_t bar, uint32_t parity) {
  asm volatile("{\n.reg .pred p;\nLAB_WAIT:\nmbarrier.try_wait.parity.shared::cta.b64 p, [%0], %1;\n@!p bra LAB_WAIT;\n}" :: "r"(bar), "r"(parity) : "memory");
}
__device__ __forceinline__ void spin_check(uint32_t n) { asm volatile("{\n.reg .pred p;\nsetp.ge.u32 p, %0, 4194304;\n@p st.volatile.global.u32 [%1], %0;\n}" :: "r"(n), "l"(0ull)); }
__device__ __forceinline__ void tma_ld2(uint32_t dst, const CUtensorMap* m, uint32_t bar, int c0, int c1) {
  asm volatile("cp.async.bulk.tensor.2d.shared::cluster.global.mbarrier::complete_tx::bytes [%0], [%1, {%3, %4}], [%2];" :: "r"(dst), "l"(m), "r"(bar), "r"(c0), "r"(c1) : "memory");
}
__device__ __forceinline__ void tma_ld3(uint32_t dst, const CUtensorMap* m, uint32_t bar, int c0, int c1, int c2) {
  asm volatile("cp.async.bulk.tensor.3d.shared::cluster.global.mbarrier::complete_tx::bytes [%0], [%1, {%3, %4, %5}], [%2];" :: "r"(dst), "l"(m), "r"(bar), "r"(c0), "r"(c1), "r"(c2) : "memory");
}
__device__ __forceinline__ void tma_ld3_mc(uint32_t dst, const CUtensorMap* m, uint32_t bar, int c0, int c1, int c2, uint16_t mask) {
  asm volatile("cp.async.bulk.tensor.3d.shared::cluster.global.mbarrier::complete_tx::bytes.multicast::cluster [%0], [%1, {%3, %4, %5}], [%2], %6;"
               :: "r"(dst), "l"(m), "r"(bar), "r"(c0), "r"(c1), "r"(c2), "h"(mask) : "memory");
}
__device__ __forceinline__ uint32_t mapa(uint32_t addr, uint32_t cta) { uint32_t r; asm("mapa.shared::cluster.u32 %0, %1, %2;" : "=r"(r) : "r"(addr), "r"(cta)); return r; }
__device__ __forceinline__ void mbar_arrive_cluster(uint32_t bar) { asm volatile("mbarrier.arrive.shared::cluster.b64 _, [%0];" :: "r"(bar) : "memory"); }
__device__ __forceinline__ void tma_st2(const CUtensorMap* m, uint32_t src, int c0, int c1) {
  asm volatile("cp.async.bulk.tensor.2d.global.shared::cta.bulk_group [%0, {%2, %3}], [%1];" :: "l"(m), "r"(src), "r"(c0), "r"(c1) : "memory");
}
__device__ __forceinline__ void tma_st3(const CUtensorMap* m, uint32_t src, int c0, int c1, int c2) {
  asm volatile("cp.async.bulk.tensor.3d.global.shared::cta.bulk_group [%0, {%2, %3, %4}], [%1];" :: "l"(m), "r"(src), "r"(c0), "r"(c1), "r"(c2) : "memory");
}
__device__ __forceinline__ void bulk_commit() { asm volatile("cp.async.bulk.commit_group;" ::: "memory"); }
template <int N> __device__ __forceinline__ void bulk_wait() { asm volatile("cp.async.bulk.wait_group %0;" :: "n"(N) : "memory"); }
__device__ __forceinline__ void fence_async_smem() { asm volatile("fence.proxy.async.shared::cta;" ::: "memory"); }
__device__ __forceinline__ void fence_async_global() { asm volatile("fence.proxy.async.global;" ::: "memory"); }
__device__ __forceinline__ bool elect_one() { uint32_t p; asm volatile("{\n.reg .pred P;\nelect.sync _|P, 0xffffffff;\nselp.u32 %0, 1, 0, P;\n}" : "=r"(p)); return p; }
__device__ __forceinline__ void prefetch_map(const CUtensorMap* m) { asm volatile("prefetch.tensormap [%0];" :: "l"(m) : "memory"); }
__device__ __forceinline__ void prefetch_l2(const void* p, uint32_t bytes) { asm volatile("cp.async.bulk.prefetch.L2.global [%0], %1;" :: "l"(p), "r"(bytes) : "memory"); }
__device__ __forceinline__ void wgmma_fence() { asm volatile("wgmma.fence.sync.aligned;" ::: "memory"); }
__device__ __forceinline__ void wgmma_commit() { asm volatile("wgmma.commit_group.sync.aligned;" ::: "memory"); }
template <int N> __device__ __forceinline__ void wgmma_wait() { asm volatile("wgmma.wait_group.sync.aligned %0;" :: "n"(N) : "memory"); }
__device__ __forceinline__ uint32_t desc_lo(uint32_t addr, uint32_t lbo) { return ((addr & 0x3FFFF) >> 4) | ((lbo >> 4) << 16); }
__device__ __forceinline__ uint64_t desc64(uint32_t lo) { uint64_t r; asm("mov.b64 %0, {%1, %2};" : "=l"(r) : "r"(lo), "r"(0x40000040u)); return r; }
__device__ __forceinline__ void bar_sync(int id, int n) { asm volatile("bar.sync %0, %1;" :: "r"(id), "r"(n) : "memory"); }
__device__ __forceinline__ uint32_t pack_bf16(float lo, float hi) { uint32_t r; asm("cvt.rn.bf16x2.f32 %0, %1, %2;" : "=r"(r) : "f"(hi), "f"(lo)); return r; }
__device__ __forceinline__ float bf_lo(uint32_t v) { return __uint_as_float(v << 16); }
__device__ __forceinline__ float bf_hi(uint32_t v) { return __uint_as_float(v & 0xffff0000u); }
__device__ __forceinline__ float ex2(float x) { float r; asm("ex2.approx.ftz.f32 %0, %1;" : "=f"(r) : "f"(x)); return r; }
__device__ __forceinline__ float rcp(float x) { float r; asm("rcp.approx.ftz.f32 %0, %1;" : "=f"(r) : "f"(x)); return r; }
__device__ __forceinline__ void stsm4(uint32_t a, uint32_t r0, uint32_t r1, uint32_t r2, uint32_t r3) {
  asm volatile("stmatrix.sync.aligned.m8n8.x4.shared.b16 [%0], {%1, %2, %3, %4};" :: "r"(a), "r"(r0), "r"(r1), "r"(r2), "r"(r3) : "memory");
}
__device__ __forceinline__ void ldsm4(uint32_t a, uint32_t& r0, uint32_t& r1, uint32_t& r2, uint32_t& r3) {
  asm volatile("ldmatrix.sync.aligned.m8n8.x4.shared.b16 {%0, %1, %2, %3}, [%4];" : "=r"(r0), "=r"(r1), "=r"(r2), "=r"(r3) : "r"(a) : "memory");
}
__device__ __forceinline__ uint32_t movm(uint32_t v) { uint32_t r; asm volatile("movmatrix.sync.aligned.m8n8.trans.b16 %0, %1;" : "=r"(r) : "r"(v)); return r; }
__device__ __forceinline__ void sts128(uint32_t a, uint32_t r0, uint32_t r1, uint32_t r2, uint32_t r3) {
  asm volatile("st.shared.v4.b32 [%0], {%1, %2, %3, %4};" :: "r"(a), "r"(r0), "r"(r1), "r"(r2), "r"(r3) : "memory");
}
__device__ __forceinline__ void lds128(uint32_t a, uint32_t& r0, uint32_t& r1, uint32_t& r2, uint32_t& r3) {
  asm volatile("ld.shared.v4.b32 {%0, %1, %2, %3}, [%4];" : "=r"(r0), "=r"(r1), "=r"(r2), "=r"(r3) : "r"(a) : "memory");
}
__device__ __forceinline__ float2 lds64f(uint32_t a) { float2 r; asm volatile("ld.shared.v2.f32 {%0, %1}, [%2];" : "=f"(r.x), "=f"(r.y) : "r"(a) : "memory"); return r; }
__device__ __forceinline__ void sts64f(uint32_t a, float x, float y) { asm volatile("st.shared.v2.f32 [%0], {%1, %2};" :: "r"(a), "f"(x), "f"(y) : "memory"); }
__device__ __forceinline__ uint32_t add_bf16x2(uint32_t a, uint32_t b) { uint32_t r; asm("add.rn.bf16x2 %0, %1, %2;" : "=r"(r) : "r"(a), "r"(b)); return r; }
__device__ __forceinline__ void sts32f(uint32_t a, float v) { asm volatile("st.shared.f32 [%0], %1;" :: "r"(a), "f"(v) : "memory"); }
__device__ __forceinline__ void mma16816(float (&c)[4], uint32_t a0, uint32_t a1, uint32_t a2, uint32_t a3, uint32_t b0, uint32_t b1) {
  asm("mma.sync.aligned.m16n8k16.row.col.f32.bf16.bf16.f32 {%0, %1, %2, %3}, {%4, %5, %6, %7}, {%8, %9}, {%0, %1, %2, %3};"
               : "+f"(c[0]), "+f"(c[1]), "+f"(c[2]), "+f"(c[3]) : "r"(a0), "r"(a1), "r"(a2), "r"(a3), "r"(b0), "r"(b1));
}
__device__ __forceinline__ void mma1688(float (&c)[4], uint32_t a0, uint32_t a1, uint32_t b0) {
  asm("mma.sync.aligned.m16n8k8.row.col.f32.bf16.bf16.f32 {%0, %1, %2, %3}, {%4, %5}, {%6}, {%0, %1, %2, %3};"
               : "+f"(c[0]), "+f"(c[1]), "+f"(c[2]), "+f"(c[3]) : "r"(a0), "r"(a1), "r"(b0));
}
__device__ __forceinline__ void ll_store(uint4* p, uint32_t a, uint32_t b, uint32_t tag) {
  asm volatile("st.relaxed.gpu.global.v2.b64 [%0], {%1, %2};" :: "l"(p), "l"((uint64_t)a | ((uint64_t)tag << 32)), "l"((uint64_t)b | ((uint64_t)tag << 32)) : "memory");
}
__device__ __forceinline__ uint4 ll_load(const uint4* p) {
  uint64_t a, b;
  asm volatile("ld.relaxed.gpu.global.v2.b64 {%0, %1}, [%2];" : "=l"(a), "=l"(b) : "l"(p) : "memory");
  return make_uint4((uint32_t)a, (uint32_t)(a >> 32), (uint32_t)b, (uint32_t)(b >> 32));
}
__device__ __forceinline__ uint32_t ld_relaxed(const uint32_t* p) { uint32_t v; asm volatile("ld.relaxed.gpu.global.u32 %0, [%1];" : "=r"(v) : "l"(p) : "memory"); return v; }
__device__ __forceinline__ uint4 ld_relaxed4(const void* p) { uint4 v; asm volatile("ld.relaxed.gpu.global.v4.u32 {%0, %1, %2, %3}, [%4];" : "=r"(v.x), "=r"(v.y), "=r"(v.z), "=r"(v.w) : "l"(p) : "memory"); return v; }
__device__ __forceinline__ void st_relaxed(uint32_t* p, uint32_t v) { asm volatile("st.relaxed.gpu.global.u32 [%0], %1;" :: "l"(p), "r"(v) : "memory"); }
__device__ __forceinline__ void st_relaxed2(void* p, uint32_t a, uint32_t b) { asm volatile("st.relaxed.gpu.global.v2.u32 [%0], {%1, %2};" :: "l"(p), "r"(a), "r"(b) : "memory"); }
__device__ __forceinline__ void st_release(uint32_t* p, uint32_t v) { asm volatile("st.release.gpu.global.u32 [%0], %1;" :: "l"(p), "r"(v) : "memory"); }
__device__ __forceinline__ uint32_t tagf(float v, uint32_t tag) { return (__float_as_uint(v) & ~15u) | (tag & 15u); }
__device__ __forceinline__ bool tag_ok4(const uint4& v, uint32_t tag) { return (((v.x ^ tag) | (v.y ^ tag) | (v.z ^ tag) | (v.w ^ tag)) & 15u) == 0; }
__device__ __forceinline__ float untag(uint32_t v) { return __uint_as_float(v & ~15u); }
template <typename T> __device__ __forceinline__ T* ptr_add(T* p, uint32_t bytes) {
  uint64_t r;
  asm("{\n.reg .u32 lo, hi;\nmov.b64 {lo, hi}, %1;\nadd.cc.u32 lo, lo, %2;\naddc.u32 hi, hi, 0;\nmov.b64 %0, {lo, hi};\n}" : "=l"(r) : "l"(p), "r"(bytes));
  return (T*)r;
}
#define TL(who, slot) do {} while (0)
#define ST(who, n) do {} while (0)
#define TLG(slot) do {} while (0)
#define STA() do {} while (0)
#define STB(n) do {} while (0)

__device__ __forceinline__ void wgmma_n128(float (&d)[64], uint64_t da, uint64_t db, int scale_d) {
  asm volatile("{\n.reg .pred p;\nsetp.ne.b32 p, %66, 0;\n"
    "wgmma.mma_async.sync.aligned.m64n128k16.f32.bf16.bf16 "
    "{%0, %1, %2, %3, %4, %5, %6, %7, %8, %9, %10, %11, %12, %13, %14, %15, "
    "%16, %17, %18, %19, %20, %21, %22, %23, %24, %25, %26, %27, %28, %29, %30, %31, "
    "%32, %33, %34, %35, %36, %37, %38, %39, %40, %41, %42, %43, %44, %45, %46, %47, "
    "%48, %49, %50, %51, %52, %53, %54, %55, %56, %57, %58, %59, %60, %61, %62, %63}, "
    "%64, %65, p, 1, 1, 0, 1;\n}\n"
    : "+f"(d[0]), "+f"(d[1]), "+f"(d[2]), "+f"(d[3]), "+f"(d[4]), "+f"(d[5]), "+f"(d[6]), "+f"(d[7]),
      "+f"(d[8]), "+f"(d[9]), "+f"(d[10]), "+f"(d[11]), "+f"(d[12]), "+f"(d[13]), "+f"(d[14]), "+f"(d[15]),
      "+f"(d[16]), "+f"(d[17]), "+f"(d[18]), "+f"(d[19]), "+f"(d[20]), "+f"(d[21]), "+f"(d[22]), "+f"(d[23]),
      "+f"(d[24]), "+f"(d[25]), "+f"(d[26]), "+f"(d[27]), "+f"(d[28]), "+f"(d[29]), "+f"(d[30]), "+f"(d[31]),
      "+f"(d[32]), "+f"(d[33]), "+f"(d[34]), "+f"(d[35]), "+f"(d[36]), "+f"(d[37]), "+f"(d[38]), "+f"(d[39]),
      "+f"(d[40]), "+f"(d[41]), "+f"(d[42]), "+f"(d[43]), "+f"(d[44]), "+f"(d[45]), "+f"(d[46]), "+f"(d[47]),
      "+f"(d[48]), "+f"(d[49]), "+f"(d[50]), "+f"(d[51]), "+f"(d[52]), "+f"(d[53]), "+f"(d[54]), "+f"(d[55]),
      "+f"(d[56]), "+f"(d[57]), "+f"(d[58]), "+f"(d[59]), "+f"(d[60]), "+f"(d[61]), "+f"(d[62]), "+f"(d[63])
    : "l"(da), "l"(db), "r"(scale_d));
}
__device__ __forceinline__ void wgmma_n256(float (&d)[128], uint64_t da, uint64_t db, int scale_d) {
  asm volatile("{\n.reg .pred p;\nsetp.ne.b32 p, %130, 0;\n"
    "wgmma.mma_async.sync.aligned.m64n256k16.f32.bf16.bf16 "
    "{%0, %1, %2, %3, %4, %5, %6, %7, %8, %9, %10, %11, %12, %13, %14, %15, "
    "%16, %17, %18, %19, %20, %21, %22, %23, %24, %25, %26, %27, %28, %29, %30, %31, "
    "%32, %33, %34, %35, %36, %37, %38, %39, %40, %41, %42, %43, %44, %45, %46, %47, "
    "%48, %49, %50, %51, %52, %53, %54, %55, %56, %57, %58, %59, %60, %61, %62, %63, "
    "%64, %65, %66, %67, %68, %69, %70, %71, %72, %73, %74, %75, %76, %77, %78, %79, "
    "%80, %81, %82, %83, %84, %85, %86, %87, %88, %89, %90, %91, %92, %93, %94, %95, "
    "%96, %97, %98, %99, %100, %101, %102, %103, %104, %105, %106, %107, %108, %109, %110, %111, "
    "%112, %113, %114, %115, %116, %117, %118, %119, %120, %121, %122, %123, %124, %125, %126, %127}, "
    "%128, %129, p, 1, 1, 0, 1;\n}\n"
    : "+f"(d[0]), "+f"(d[1]), "+f"(d[2]), "+f"(d[3]), "+f"(d[4]), "+f"(d[5]), "+f"(d[6]), "+f"(d[7]),
      "+f"(d[8]), "+f"(d[9]), "+f"(d[10]), "+f"(d[11]), "+f"(d[12]), "+f"(d[13]), "+f"(d[14]), "+f"(d[15]),
      "+f"(d[16]), "+f"(d[17]), "+f"(d[18]), "+f"(d[19]), "+f"(d[20]), "+f"(d[21]), "+f"(d[22]), "+f"(d[23]),
      "+f"(d[24]), "+f"(d[25]), "+f"(d[26]), "+f"(d[27]), "+f"(d[28]), "+f"(d[29]), "+f"(d[30]), "+f"(d[31]),
      "+f"(d[32]), "+f"(d[33]), "+f"(d[34]), "+f"(d[35]), "+f"(d[36]), "+f"(d[37]), "+f"(d[38]), "+f"(d[39]),
      "+f"(d[40]), "+f"(d[41]), "+f"(d[42]), "+f"(d[43]), "+f"(d[44]), "+f"(d[45]), "+f"(d[46]), "+f"(d[47]),
      "+f"(d[48]), "+f"(d[49]), "+f"(d[50]), "+f"(d[51]), "+f"(d[52]), "+f"(d[53]), "+f"(d[54]), "+f"(d[55]),
      "+f"(d[56]), "+f"(d[57]), "+f"(d[58]), "+f"(d[59]), "+f"(d[60]), "+f"(d[61]), "+f"(d[62]), "+f"(d[63]),
      "+f"(d[64]), "+f"(d[65]), "+f"(d[66]), "+f"(d[67]), "+f"(d[68]), "+f"(d[69]), "+f"(d[70]), "+f"(d[71]),
      "+f"(d[72]), "+f"(d[73]), "+f"(d[74]), "+f"(d[75]), "+f"(d[76]), "+f"(d[77]), "+f"(d[78]), "+f"(d[79]),
      "+f"(d[80]), "+f"(d[81]), "+f"(d[82]), "+f"(d[83]), "+f"(d[84]), "+f"(d[85]), "+f"(d[86]), "+f"(d[87]),
      "+f"(d[88]), "+f"(d[89]), "+f"(d[90]), "+f"(d[91]), "+f"(d[92]), "+f"(d[93]), "+f"(d[94]), "+f"(d[95]),
      "+f"(d[96]), "+f"(d[97]), "+f"(d[98]), "+f"(d[99]), "+f"(d[100]), "+f"(d[101]), "+f"(d[102]), "+f"(d[103]),
      "+f"(d[104]), "+f"(d[105]), "+f"(d[106]), "+f"(d[107]), "+f"(d[108]), "+f"(d[109]), "+f"(d[110]), "+f"(d[111]),
      "+f"(d[112]), "+f"(d[113]), "+f"(d[114]), "+f"(d[115]), "+f"(d[116]), "+f"(d[117]), "+f"(d[118]), "+f"(d[119]),
      "+f"(d[120]), "+f"(d[121]), "+f"(d[122]), "+f"(d[123]), "+f"(d[124]), "+f"(d[125]), "+f"(d[126]), "+f"(d[127])
    : "l"(da), "l"(db), "r"(scale_d));
}

template <int BN> __device__ __forceinline__ void wgmma(float (&d)[BN / 2], uint64_t a, uint64_t b, int s) {
  if constexpr (BN == 128) wgmma_n128(d, a, b, s);
  else wgmma_n256(d, a, b, s);
}

template <int N> __device__ __forceinline__ void acc_fence(float* a) {
#pragma unroll
  for (int i = 0; i < N; i++) asm volatile("" : "+f"(a[i]) :: "memory");
}

struct Prod {
  uint32_t sb, n, tail, addr, pat, ready;
  uint32_t h0, h1; uint16_t mask;
  __device__ __forceinline__ void load_b(uint32_t dst, uint32_t half, const CUtensorMap* m, uint32_t mstep, uint32_t fb, int k, int ch, int cstep) {
#pragma unroll 1
    for (uint32_t h = h0; h <= h1; h++) tma_ld3_mc(dst + h * half, ptr_add(m, h * mstep), fb, 0, k * 64, ch + h * cstep, mask);
  }
  __device__ __forceinline__ void load_wide(const Params& P, int ffn, uint32_t dst, uint32_t fb, int k, int ch) {
    load_b(dst, PAGE, &P.map[ffn ? M_W1 : M_WKV], ffn ? 128 : 0, fb, k, ffn ? ch : ch + 16, ffn ? 0 : 16);
  }
  __device__ __forceinline__ void load_narrow(const Params& P, int ffn, uint32_t dst, uint32_t fb, int k, int j) {
    load_b(dst, 8192, &P.map[ffn ? M_W1H : M_WQ], ffn ? 128 : 0, fb, k, ffn ? 48 + j : 2 * j, ffn ? 0 : 1);
  }
  __device__ __forceinline__ void finish() {
#pragma unroll 1
    for (; tail < n; tail++) mbar_wait(sb + BAR_EMPTY + ((tail & 7) << 3), (tail >> 3) & 1);
  }
  template <int PAGES> __device__ __forceinline__ uint32_t acquire(uint32_t& fb) {
    uint32_t nw = pat & 3; pat = (pat >> 2) | 0x40000000u;
#pragma unroll 1
    for (; nw; nw--) { mbar_wait(sb + BAR_EMPTY + ((tail & 7) << 3), (tail >> 3) & 1); tail++; }
    ST(4, n);
    fb = sb + BAR_FULL + ((n & 7) << 3);
    mbar_expect_tx(fb, PAGES * PAGE);
    const uint32_t a = sb + addr;
    addr += PAGES * PAGE; if (addr >= NPAGE * PAGE) addr = 0;
    n++;
    return a;
  }
  __device__ __forceinline__ void need(uint32_t ev, uint32_t mask) {
    if ((ready & mask) != mask) {
      uint32_t spins = 0;
      do {
        asm volatile("ld.volatile.shared.u32 %0, [%1];" : "=r"(ready) : "r"(sb + SM_READY + ev * 4) : "memory");
        spin_check(++spins >> 4);
      } while ((ready & mask) != mask);
      fence_async_global();
    }
    ST(5, n - 1);
  }
};

struct Cons {
  uint32_t sb, n, off, prev;
  uint32_t ebar;
  uint32_t da0, db0;
  int lane;
  template <int PAGES> __device__ __forceinline__ void advance() {
    n++; off += PAGES << 10; if (off >= (NPAGE << 10)) off = 0;
    asm volatile("" : "+r"(n), "+r"(off));
  }
  template <int BN, int PAGES> __device__ __forceinline__ void step_ab(float (&acc)[BN / 2], uint32_t da, uint32_t db, int accumulate) {
    STA();
    mbar_wait_fast(sb + BAR_FULL + ((n & 7) << 3), (n >> 3) & 1);
    STB(n);
    const uint64_t da64 = desc64(da), db64 = desc64(db);
    wgmma_fence();
#pragma unroll
    for (int k = 0; k < 4; k++) wgmma<BN>(acc, da64 + 2 * k, db64 + 128 * k, k ? 1 : accumulate);
    wgmma_commit();
    wgmma_wait<1>();
    if (prev && lane < 2) mbar_arrive_cluster(ebar + prev);
    prev = 64 + ((n & 7) << 3);
    advance<PAGES>();
  }
  template <int BN> __device__ __forceinline__ void step(float (&acc)[BN / 2], int accumulate = 1) { step_ab<BN, BN / 128 + 1>(acc, da0 + off, db0 + 1024 + off, accumulate); }
  template <int BN> __device__ __forceinline__ void step_own(float (&acc)[BN / 2], uint32_t da, int accumulate) { step_ab<BN, BN / 128>(acc, da, db0 + off, accumulate); }
  template <int BN> __device__ __forceinline__ void steps(float (&acc)[BN / 2], int cnt) {
#pragma unroll 1
    for (int i = 0; i < cnt; i++) step<BN>(acc);
  }
  __device__ __forceinline__ void drain() {
    wgmma_wait<0>();
    if (lane < 2) mbar_arrive_cluster(ebar + prev);
    prev = 0;
  }
};

#define MAPPING 2
__device__ __forceinline__ uint32_t role_of_sm(uint32_t smid) {
  const uint32_t t = smid >> 1;
  uint32_t q, i;
  if (t < 32) { q = t & 7; i = t >> 3; }
  else if (t < 60) { const uint32_t u = t - 32, d = (u * 37) >> 8; q = 1 + u - d * 7; i = 4 + d; }
  else if (t < 62) return 128 + smid - 120;
  else { q = 0; i = t - 58; }
  return (q * 2 + (smid & 1)) * 8 + i;
}

__device__ __forceinline__ uint32_t* epoch_ptr() { uint32_t b; asm volatile("mov.u32 %0, %%ctaid.x;" : "=r"(b)); return ptr_add(&g_epoch[0], b * 4u); }

__global__ void __cluster_dims__(2, 1, 1) __launch_bounds__(384, 1) fused_kernel(const __grid_constant__ Params P) {
  extern __shared__ __align__(1024) uint8_t smem_raw[];
  const uint32_t sb = __shfl_sync(0xffffffffu, smem_u32(smem_raw), 0);
  const int warp = __shfl_sync(0xffffffffu, threadIdx.x >> 5, 0);
  const int lane = threadIdx.x & 31;
  uint32_t role = blockIdx.x < 128 ? ((blockIdx.x >> 4) * 2 + (blockIdx.x & 1)) * 8 + ((blockIdx.x >> 1) & 7) : blockIdx.x;
  if (P.use_smid) { uint32_t smid; asm volatile("mov.u32 %0, %%smid;" : "=r"(smid)); role = role_of_sm(smid); }
  const bool spare = role >= 128;
  const int g = role >> 3, j = role & 7;
  TLG(60);
  if (warp == 8) {
    if (elect_one()) {
      if (!spare) { prefetch_map(&P.map[M_XIN64]); prefetch_map(&P.map[M_WKV]); prefetch_map(&P.map[M_WQ]); prefetch_map(&P.map[M_XIN]); }
      spin_check((sb & 1023) << 22);
#pragma unroll
      for (int s = 0; s < 8; s++) { mbar_init(sb + BAR_FULL + 8 * s, 1); mbar_init(sb + BAR_EMPTY + 8 * s, 16); }
#pragma unroll
      for (int s = 0; s < 2; s++) {
        mbar_init(sb + BAR_SFULL + 16 * s, 4); mbar_init(sb + BAR_SFULL + 16 * s + 8, 4);
      }
      mbar_init(sb + BAR_SEMPTY, 1); mbar_init(sb + BAR_XFULL, 8); mbar_init(sb + BAR_HALO, 2); mbar_init(sb + BAR_CSF, 1); mbar_init(sb + BAR_CSF + 8, 1); mbar_init(sb + BAR_CSE, 8); mbar_init(sb + BAR_XIN, 1);
      asm volatile("st.shared.u32 [%0], %1;" :: "r"(sb + SM_ROLE), "r"(role) : "memory");
#pragma unroll
      for (int s = 0; s < 5; s++) sts128(sb + SM_READY + s * 16, 0, 0, 0, 0);
      asm volatile("fence.acq_rel.cluster;" ::: "memory");
      fence_async_smem();
    }
    __syncwarp();
  }
  asm volatile("barrier.cluster.arrive.relaxed.aligned;" ::: "memory");
  if (warp == 8 && !spare) {
    if (elect_one()) {
      mbar_expect_tx(sb + BAR_XIN, 32768);
#pragma unroll
      for (int s = 0; s < 4; s++) tma_ld3(sb + SM_STAGE + (s & 1) * PAGE + (s >> 1) * 8192, &P.map[M_XIN64], sb + BAR_XIN, j * 128 + (s >> 1) * 64, g & 1, (g >> 1) * 128 + (s & 1) * 64);
    }
    __syncwarp();
  }
  asm volatile("barrier.cluster.wait.acquire.aligned;" ::: "memory");
  uint32_t rank; asm("mov.u32 %0, %%cluster_ctarank;" : "=r"(rank));
  auto shared_b = [&]() {
    uint32_t peer;
    asm volatile("ld.shared::cluster.u32 %0, [%1];" : "=r"(peer) : "r"(mapa(sb + SM_ROLE, rank ^ 1)) : "memory");
    return !spare && peer < 128 && (peer & 7) == (uint32_t)j;
  };

  if (warp >= 8) {
    asm volatile("setmaxnreg.dec.sync.aligned.u32 40;");
    if (warp == 8) {
      if (elect_one()) {
        Prod p; p.sb = sb; p.n = 0; p.tail = 0; p.ready = 0; p.addr = 0;
        { const bool mc = shared_b(); p.h0 = mc ? rank : 0; p.h1 = mc ? rank : 1; p.mask = mc ? 3 : 1 << rank; }
        uint32_t fb;
        if (spare) {
          p.pat = 0x55555000u;
#pragma unroll 1
          for (int r = 0; r < 7; r++) {
            const int ch = ((r < 2 ? r : r == 2 ? 6 : r - 1) * 4 + j) * 2;
#pragma unroll 1
            for (int k = 0; k < 16; k++) { const uint32_t a = p.acquire<2>(fb); p.load_wide(P, 1, a, fb, k, ch); }
          }
        } else {
          const int row0 = g * 128, par = g & 1, pair0 = (g >> 1) * 128;
          TL(2, 0);
#pragma unroll 1
          for (int hl = 0; hl < 4; hl++) {
            const int ffn = hl & 1, evb = (hl >> 1) * EV_N;
            const int xev = ffn ? evb + EV_XA : EV_XB, xrow = (ffn ? 0 : SEQ) + row0;
            auto load_x = [&](uint32_t dst, int k) {
              if (hl == 0) tma_ld3(dst, &P.map[M_XIN], fb, k * 64, par, pair0); else tma_ld2(dst, &P.map[M_ACT_LD], fb, k * 64, xrow);
            };
            p.pat = ffn ? Pat<3>::v : hl ? Pat<7>::v : Pat<0>::v; p.addr = 0;
#pragma unroll 1
            for (int s = 0; s < 2; s++) { const uint32_t a = p.acquire<2>(fb); p.load_wide(P, ffn, a, fb, 2 * j + s, 2 * j); }
#pragma unroll 1
            for (int s = 0; s < 2; s++) { const uint32_t a = p.acquire<1>(fb); p.load_narrow(P, ffn, a, fb, 2 * j + s, j); }
            {
              const int j0 = j == 0 ? 7 : 0, j1 = j == 1 ? 7 : 1;
              uint32_t fb0;
              const uint32_t a0 = p.acquire<3>(fb0); p.load_wide(P, ffn, a0 + PAGE, fb0, 2 * j0, 2 * j);
              const uint32_t a1 = p.acquire<3>(fb); p.load_wide(P, ffn, a1 + PAGE, fb, 2 * j1, 2 * j);
              const uint32_t fb1 = fb;
              p.ready = hl ? 0 : 0xffu;
              p.need(xev, (1u << j0) | (1u << j)); fb = fb0; load_x(a0, 2 * j0);
              p.need(xev, 1u << j1); fb = fb1; load_x(a1, 2 * j1);
            }
#pragma unroll 1
            for (int m = 2; m < 14; m++) {
              const int hf = m >= 7, mm = m - 7 * hf, jj = mm == j ? 7 : mm, k = 2 * jj + hf;
              if (m == 7 && hl) p.ready = 0;
              const uint32_t a = p.acquire<3>(fb);
              p.load_wide(P, ffn, a + PAGE, fb, k, 2 * j);
              p.need(xev + hf, 1u << jj);
              load_x(a, k);
            }
            p.need(xev + 1, 0xffu);
            static_assert(Pat<1>::v == Pat<4>::v, "");
            p.pat = Pat<1>::v;
#pragma unroll 1
            for (int m = 0; m < 14; m++) {
              const int k = (m >> 1) == j ? 14 + (m & 1) : m;
              const uint32_t a = p.acquire<2>(fb);
              p.load_narrow(P, ffn, a + PAGE, fb, k, j);
              load_x(a, k);
            }
            if (!ffn) {
              p.pat = Pat<2>::v;
#pragma unroll 1
              for (int s = 0; s < 2; s++) { const uint32_t a = p.acquire<1>(fb); p.load_b(a, 8192, &P.map[M_WO], 0, fb, 2 * j + s, 2 * j, 1); }
              { const uint32_t a = p.acquire<2>(fb); load_x(a, 2 * j); load_x(a + PAGE, 2 * j + 1); }
#pragma unroll 1
              for (int hf = 0; hf < 2; hf++) {
                p.ready = 0;
#pragma unroll 1
                for (int m = 0; m < 7; m++) {
                  const int jj = m == j ? 7 : m, k = 2 * jj + hf;
                  const uint32_t a = p.acquire<2>(fb);
                  p.load_b(a + PAGE, 8192, &P.map[M_WO], 0, fb, k, 2 * j, 1);
                  p.need(evb + EV_OA + hf, (1u << jj) | (hf ? 0 : 1u << j));
                  tma_ld2(a, &P.map[M_ACT_LD], fb, k * 64, 2 * SEQ + row0);
                }
              }
            } else {
              p.pat = Pat<5>::v; p.addr = 6 * PAGE;
#pragma unroll 1
              for (int s = 16; s < 48; s++) {
                const int pi = (s >> 1) & 7;
                const int k = (s < 32 ? pi : pi == 4 ? j : pi == j ? 4 : pi) * 2 + (s & 1);
                const uint32_t a = p.acquire<3>(fb);
                p.load_wide(P, 1, a + PAGE, fb, k, (s & 48) + 2 * j);
                tma_ld2(a, &P.map[M_ACT_LD], fb, k * 64, row0);
              }
              p.pat = Pat<6>::v;
  #pragma unroll 1
              for (int s = 0; s < 56; s++) {
                if (s == 0 || s == 16 || s == 24 || s == 40) { p.ready = 0; p.need(evb + EV_H0 + ((s + 8) >> 4), 0xffu); }
                const int k = s < 16 ? s : s < 24 ? s + 32 : s - 8;
                const uint32_t a = p.acquire<2>(fb);
                p.load_b(a + PAGE, 8192, &P.map[M_W2], 0, fb, k, 2 * j, 1);
                tma_ld2(a, &P.map[M_H_LD], fb, k * 64, row0);
              }
            }
            TL(2, 1 + hl);
          }
        }
        p.finish();
      }
    } else if (!spare) {
      const uint32_t tag = ld_relaxed(epoch_ptr());
      mbar_wait(sb + BAR_XIN, 0);
      if (elect_one()) prefetch_l2(ptr_add(P.wqkv, (role * 3 + (warp - 9)) * 16384u), 16384);
#pragma unroll 1
      for (int r = 0; r < 2; r++) {
        const uint32_t u = role * 3 + (warp - 9) + r * 384;
        const uint32_t strip = u < 512 ? 64 + (u >> 2) : (u - 512) >> 2, part = u & 3;
        const uint32_t col = strip * 16 + (lane & 1) * 8;
        const uint4* wp = ptr_add((const uint4*)P.wqkv, (part * 256 + (lane >> 1)) * 6144u + col * 2);
        float s[8] = {0, 0, 0, 0, 0, 0, 0, 0};
        uint4 v[4];
#pragma unroll
        for (int i = 0; i < 4; i++) v[i] = __ldcg(wp + i * (16 * 6144 / 16));
#pragma unroll 1
        for (int b = 0; b < 4; b++) {
          wp += 64 * 6144 / 16;
#pragma unroll
          for (int i = 0; i < 4; i++) {
            s[0] += bf_lo(v[i].x); s[1] += bf_hi(v[i].x); s[2] += bf_lo(v[i].y); s[3] += bf_hi(v[i].y);
            s[4] += bf_lo(v[i].z); s[5] += bf_hi(v[i].z); s[6] += bf_lo(v[i].w); s[7] += bf_hi(v[i].w);
            if (b < 3) v[i] = __ldcg(wp + i * (16 * 6144 / 16));
          }
        }
#pragma unroll
        for (int e = 0; e < 4; e++) { const bool h = lane & 16; const float t = __shfl_xor_sync(0xffffffffu, h ? s[e] : s[e + 4], 16); s[e] = (h ? s[e + 4] : s[e]) + t; }
#pragma unroll
        for (int e = 0; e < 2; e++) { const bool h = lane & 8; const float t = __shfl_xor_sync(0xffffffffu, h ? s[e] : s[e + 2], 8); s[e] = (h ? s[e + 2] : s[e]) + t; }
        { const bool h = lane & 4; const float t = __shfl_xor_sync(0xffffffffu, h ? s[0] : s[1], 4); s[0] = (h ? s[1] : s[0]) + t; }
        s[0] += __shfl_xor_sync(0xffffffffu, s[0], 2);
        if (!(lane & 2)) st_relaxed(ptr_add((uint32_t*)&g_cs[0], (col + (lane >> 2)) * 16 + part * 4), tagf(s[0], tag));
        __syncwarp();
      }
      if (warp == 11 && lane == 0) TL(2, 30);
      if (warp <= 10) {
        const int w = warp - 9;
        if (elect_one()) {
          if (w == 0) { prefetch_map(&P.map[M_ACT_ST]); prefetch_map(&P.map[M_ACT_LD]); prefetch_map(&P.map[M_WO]); prefetch_map(&P.map[M_W1 + rank]); }
          else { prefetch_map(&P.map[M_H_ST]); prefetch_map(&P.map[M_H_LD]); prefetch_map(&P.map[M_W1H + rank]); prefetch_map(&P.map[M_W2]); prefetch_map(&P.map[M_OUT_ST]); }
        }
        uint32_t* fl = ptr_add(&g_flags[0], (uint32_t)(g * 256 + j) * 4u);
        int pe = 0;
#pragma unroll 1
        for (int hl = 0; hl < 4; hl++) {
          const int l = hl >> 1;
          if (w == 1) {
          const uint32_t cspos = sb + SM_CS + ((lane & 16) + ((lane >> 1) & 3) * 4 + ((lane >> 3) & 1) * 2 + (lane & 1)) * 4;
#pragma unroll 1
          for (int t = hl & 1; t < ((hl & 1) ? 4 : 1); t++) {
          const int it = l * 4 + t;
          if (it) mbar_wait(sb + BAR_CSE, (it - 1) & 1);
#pragma unroll 1
          for (int b = 0; b < (t < 2 ? 3 : 2); b++) {
            uint32_t c0, c1;
            if (b < 2) { c0 = (t ? 2048 + t * 1024 + b * FF : 1024 + b * 1024) + j * 128; c1 = c0 + 64; }
            else if (t) { c0 = 6144 + j * 64; c1 = c0 + FF; }
            else { c0 = j * 128; c1 = c0 + 64; }
            const uint4* p0 = ptr_add(&g_cs[0], (c0 + lane) * 16u);
            const uint4* p1 = ptr_add(&g_cs[0], (c1 + lane) * 16u);
            uint4 v[4]; uint32_t spins = 0; bool ok;
            do {
              if (spins) __nanosleep(200);
              v[0] = ld_relaxed4(p0); v[1] = ld_relaxed4(p0 + 32); v[2] = ld_relaxed4(p1); v[3] = ld_relaxed4(p1 + 32);
              ok = tag_ok4(v[0], tag) && tag_ok4(v[1], tag) && tag_ok4(v[2], tag) && tag_ok4(v[3], tag);
              spin_check(++spins);
            } while (__any_sync(0xffffffffu, !ok));
#pragma unroll
            for (int m = 0; m < 4; m++) sts32f(cspos + b * 512 + m * 128, (untag(v[m].x) + untag(v[m].y)) + (untag(v[m].z) + untag(v[m].w)));
            if (b == 0) { __syncwarp(); if (lane == 0) mbar_arrive(sb + BAR_CSF); }
          }
          __syncwarp();
          if (lane == 0) { mbar_arrive(sb + BAR_CSF + 8); TL(2, 16 + it); }
          }
          }
          if (!(hl & 1)) {
              const uint32_t slot = sb + SM_STAGE + 7 * 4096 + w * 2048 + lane * 16;
              const uint32_t hoff = (uint32_t)((l * 16 + g) * 8 + j) * 8192u + w * 4096u + lane * 16u;
              mbar_wait(sb + BAR_XFULL, l);
              if (g < 14) {
                uint4* hp = ptr_add(&g_halo[0], hoff);
#pragma unroll
                for (int i = 0; i < 4; i++) { uint32_t a0, a1, a2, a3; lds128(slot + i * 512, a0, a1, a2, a3); ll_store(hp + i * 64, a0, a1, tag); ll_store(hp + i * 64 + 32, a2, a3, tag); }
              }
              const uint4* hp = ptr_add(&g_halo[0], hoff - 2 * 8 * 8192u);
              if (g >= 2) {
                const uint32_t* lp = (const uint32_t*)ptr_add(&g_halo[0], hoff - 2 * 8 * 8192u - lane * 16u + 7 * 512u + 4u);
                uint32_t spins = 0;
                while (ld_relaxed(lp) != tag) spin_check(++spins);
              }
#pragma unroll 1
              for (int i = 0; i < 2; i++) {
                uint4 v[4];
                v[0] = v[1] = v[2] = v[3] = make_uint4(0, 0, 0, 0);
                if (g >= 2) {
                  uint32_t spins = 0, bad;
                  do {
                    bad = 0;
#pragma unroll
                    for (int m = 0; m < 4; m++) { v[m] = ll_load(hp + m * 32); bad |= (v[m].y ^ tag) | (v[m].w ^ tag); }
                    spin_check(++spins);
                  } while (__any_sync(0xffffffffu, bad != 0));
                }
                sts128(slot + i * 1024, v[0].x, v[0].z, v[1].x, v[1].z);
                sts128(slot + i * 1024 + 512, v[2].x, v[2].z, v[3].x, v[3].z);
                hp += 128;
              }
              __syncwarp();
              if (lane == 0) mbar_arrive(sb + BAR_HALO);
          }
          if (w == 0) {
            if (elect_one()) {
#pragma unroll 1
              for (int q = (hl & 1) ? EV_H0 : EV_OA; q < ((hl & 1) ? EV_N : EV_H0); q++) {
                const bool is_h = q >= EV_H0 && q < EV_XB, last = hl == 3 && !is_h;
                const int e = l * EV_N + q;
#pragma unroll 1
                for (int hb = is_h ? q == EV_H3 : q & 1; hb <= (is_h ? 1 : q & 1); hb++) {
                  const int col = !is_h ? j * 128 + hb * 64 : q == EV_H3 ? 3072 + j * 64 : (q == EV_H0 ? 0 : q - EV_H3) * 1024 + j * 128 + hb * 64;
#pragma unroll 1
                  for (int wg = 0; wg < 2; wg++) {
                    mbar_wait(sb + BAR_SFULL + 16 * wg + 8 * (pe & 1), (pe >> 1) & 1);
                    if (wg == 0) TL(3, 20 + e);
                    const uint32_t src = sb + SM_STAGE + wg * PAGE + hb * 8192;
                    if (last) tma_st3(&P.map[M_OUT_ST], src, col, g & 1, (g >> 1) * 128 + wg * 64);
                    else if (is_h) tma_st2(&P.map[M_H_ST], src, col, g * 128 + wg * 64);
                    else tma_st2(&P.map[M_ACT_ST], src, col, (q < EV_XA ? 2 * SEQ : q < EV_H0 ? 0 : SEQ) + g * 128 + wg * 64);
                  }
                  pe++;
                }
                bulk_commit();
                if (!(last && q == EV_XB)) bulk_wait<0>();
                TL(3, 40 + e);
                if (is_h || (q & 1)) mbar_arrive(sb + BAR_SEMPTY);
                if (!last) st_release(fl, tag);
                TL(3, e);
                fl += 8;
              }
            }
            __syncwarp();
          }
        }
        if (w == 0 && lane == 0) *epoch_ptr() = tag + 1;
      } else {
        const uint32_t* fl = ptr_add(&g_flags[0], (uint32_t)(g * 256 + (lane & 7)) * 4u);
#pragma unroll 1
          for (int e = 0; e < 18; e++) {
            uint32_t seen = 0, spins = 0;
            do {
              uint32_t v;
              asm volatile("ld.acquire.gpu.global.u32 %0, [%1];" : "=r"(v) : "l"(fl) : "memory");
              const uint32_t m = __ballot_sync(0xffffffffu, v == tag) & 0xffu;
              if (m != seen) {
                seen = m;
                if (lane == 0) asm volatile("st.volatile.shared.u32 [%0], %1;" :: "r"(sb + SM_READY + e * 4), "r"(m) : "memory");
              }
              spin_check(++spins);
            } while (seen != 0xffu);
            fl += 8;
          }
      }
    }
  } else {
    asm volatile("setmaxnreg.inc.sync.aligned.u32 232;");
    const int wg = warp >> 2;
    const int quad = lane & 3, gr = lane >> 2;
    Cons c; c.sb = sb; c.n = 0; c.off = 0; c.prev = 0; c.lane = lane;
    c.ebar = mapa(sb + BAR_EMPTY - 64, shared_b() ? lane & 1 : rank);
    const uint32_t stage = sb + SM_STAGE + wg * PAGE;
    const uint32_t dstage = desc_lo(stage, 16);
    if (spare) {
      const uint32_t tag = ld_relaxed(epoch_ptr());
      const int tid = threadIdx.x & 127;
#pragma unroll
      for (int i = 0; i < 4; i++) sts128(stage + (i * 128 + tid) * 16, 0x3f803f80u, 0x3f803f80u, 0x3f803f80u, 0x3f803f80u);
      fence_async_smem();
      bar_sync(2 + wg, 128);
      c.db0 = desc_lo(sb + wg * PAGE, 8192);
#pragma unroll 1
      for (int r = 0; r < 7; r++) {
        float acc[64];
#pragma unroll 1
        for (int k = 0; k < 16; k++) c.step_ab<128, 2>(acc, dstage, c.db0 + c.off, k);
        c.drain();
        acc_fence<64>(acc);
        if (tid < 16) {
          uint32_t* op = ptr_add((uint32_t*)&g_cs[0], (uint32_t)(3 * DM + wg * FF + ((r < 2 ? r : r == 2 ? 6 : r - 1) * 4 + j) * 128 + quad * 2) * 16u + gr * 4);
#pragma unroll
          for (int b = 0; b < 16; b++) { st_relaxed(op + b * 32, tagf(gr ? 0.f : acc[4 * b], tag)); st_relaxed(op + b * 32 + 4, tagf(gr ? 0.f : acc[4 * b + 1], tag)); }
        }
        __syncwarp();
      }
      if (wg == 0) {
        const uint32_t* p = ptr_add((const uint32_t*)&g_stats[0], (uint32_t)((tid >> 3) * 1024 + (tid & 7)) * 8u);
        uint32_t spins = 0;
        while (__any_sync(0xffffffffu, (ld_relaxed(p) ^ tag) & 15u)) spin_check(++spins);
      }
      bar_sync(1, 256);
      if (threadIdx.x == 0) *epoch_ptr() = tag + 1;
    } else {
    c.da0 = desc_lo(sb + wg * 8192, 16); c.db0 = desc_lo(sb, 8192);
    uint32_t sphase = 1, sfull = sb + BAR_SFULL + 16 * wg;
    const uint32_t maddr = stage + ((warp & 3) * 16 + (lane & 15)) * 128 + (((lane >> 4) ^ (lane & 7)) << 4);
    const uint32_t csaddr = sb + SM_CS + quad * 16;
    float mean[2] = {0, 0}, rstd[2] = {0, 0};
    const uint32_t tag = ld_relaxed(epoch_ptr());
    TL(wg, 0); TLG(62);

    auto stage_wait = [&]() { mbar_wait_fast(sb + BAR_SEMPTY, sphase); sphase ^= 1; };
    auto stage_publish = [&]() { fence_async_smem(); __syncwarp(); if (lane == 0) mbar_arrive(sfull); sfull ^= 8; };
    auto cs_load = [&](uint32_t (&cs)[16], int grp) {
#pragma unroll
      for (int i = 0; i < 4; i++) lds128(csaddr + grp * 256 + i * 64, cs[4 * i], cs[4 * i + 1], cs[4 * i + 2], cs[4 * i + 3]);
    };
    auto cs_apply = [&](float* acc, uint32_t (&cs)[16]) {
      acc_fence<32>(acc);
#pragma unroll
      for (int b = 0; b < 8; b++) {
        acc[4 * b] -= mean[0] * __uint_as_float(cs[2 * b]); acc[4 * b + 1] -= mean[0] * __uint_as_float(cs[2 * b + 1]);
        acc[4 * b + 2] -= mean[1] * __uint_as_float(cs[2 * b]); acc[4 * b + 3] -= mean[1] * __uint_as_float(cs[2 * b + 1]);
      }
      acc_fence<32>(acc);
    };
    auto glu_slice = [&](const uint32_t (&pk)[64], int i, bool scaled) {
      uint32_t hp[4];
#pragma unroll
      for (int e = 0; e < 4; e++) {
        const float g0 = bf_lo(pk[4 * i + e]), g1 = bf_hi(pk[4 * i + e]), u0 = bf_lo(pk[32 + 4 * i + e]), u1 = bf_hi(pk[32 + 4 * i + e]);
        if (scaled) hp[e] = pack_bf16(g0 * u0 * rcp(1.0f + ex2(g0 * -LOG2E)), g1 * u1 * rcp(1.0f + ex2(g1 * -LOG2E)));
        else {
          const float nl = -LOG2E * rstd[e & 1], r2 = rstd[e & 1] * rstd[e & 1];
          hp[e] = pack_bf16(g0 * u0 * r2 * rcp(1.0f + ex2(g0 * nl)), g1 * u1 * r2 * rcp(1.0f + ex2(g1 * nl)));
        }
      }
      stsm4((maddr ^ ((i & 3) << 5)) + (i >> 2) * 8192, hp[0], hp[1], hp[2], hp[3]);
    };

    mbar_wait_fast(sb + BAR_XIN, 0);
#pragma unroll 1
    for (int hl = 0; hl < 4; hl++) {
      int t = hl & 1;
      float acc[128], acc2[64];
      {
        c.off = 0; asm volatile("" : "+r"(c.off));
        float piv[2], s1[2] = {0, 0}, s2[2] = {0, 0};
#pragma unroll
        for (int s = 0; s < 4; s++) {
          if (s < 2) c.step_own<256>(acc, dstage + s * 512, s); else c.step_own<128>(acc2, dstage + (s - 2) * 512, s - 2);
#pragma unroll
          for (int i = (s < 2 ? 3 * s : 4 + s); i < (s < 2 ? 3 * s + 3 : 5 + s); i++) {
            uint32_t v[4];
            ldsm4((maddr ^ ((i & 3) << 5)) + (i >> 2) * 8192, v[0], v[1], v[2], v[3]);
            if (i == 0) { piv[0] = bf_lo(v[0]); piv[1] = bf_lo(v[1]); }
#pragma unroll
            for (int e = 0; e < 4; e++) {
              const float a = bf_lo(v[e]) - piv[e & 1], b = bf_hi(v[e]) - piv[e & 1];
              s1[e & 1] += a + b; s2[e & 1] += a * a; s2[e & 1] += b * b;
            }
          }
        }
#pragma unroll
        for (int r = 0; r < 2; r++) {
          const float mt = piv[r] + s1[r] * (1.0f / 32);
          float m = mt + __shfl_xor_sync(0xffffffffu, mt, 1); m += __shfl_xor_sync(0xffffffffu, m, 2); m *= 0.25f;
          float q = s2[r] - s1[r] * s1[r] * (1.0f / 32) + 32.0f * (mt - m) * (mt - m);
          q += __shfl_xor_sync(0xffffffffu, q, 1); q += __shfl_xor_sync(0xffffffffu, q, 2);
          if (quad == 0) st_relaxed2(ptr_add(&g_stats[0], (uint32_t)(hl * 2048 + g * 128 + warp * 16 + r * 8 + gr) * 64u + j * 8), tagf(m, tag), tagf(q, tag));
        }
        c.steps<256>(acc, 4);
        const uint2* sp = ptr_add(&g_stats[0], (uint32_t)(hl * 2048 + g * 128 + warp * 16 + gr) * 64u + quad * 16);
        uint4 a = ld_relaxed4(sp), b = ld_relaxed4(sp + 64);
        c.steps<256>(acc, 3);
        uint32_t spins = 0;
        while (__any_sync(0xffffffffu, !(tag_ok4(a, tag) && tag_ok4(b, tag)))) { a = ld_relaxed4(sp); b = ld_relaxed4(sp + 64); spin_check(++spins); }
#pragma unroll
        for (int r = 0; r < 2; r++) {
          const uint4 v = r ? b : a;
          const float m0 = untag(v.x), m1 = untag(v.z);
          float m = m0 + m1; m += __shfl_xor_sync(0xffffffffu, m, 1); m += __shfl_xor_sync(0xffffffffu, m, 2); m *= 0.125f;
          float q = untag(v.y) + untag(v.w) + 128.0f * ((m0 - m) * (m0 - m) + (m1 - m) * (m1 - m));
          q += __shfl_xor_sync(0xffffffffu, q, 1); q += __shfl_xor_sync(0xffffffffu, q, 2);
          mean[r] = m; rstd[r] = rsqrtf(fmaxf(q, 0.f) * (1.0f / DM) + LN_EPS);
        }
        c.steps<256>(acc, 2);
      }
#pragma unroll 1
      for (;;) {
      const int it = (hl >> 1) * 4 + t;
#pragma unroll
      for (int s = 0; s < 4; s++) {
        uint32_t cs[16];
        c.step<256>(acc);
        if (!(s & 1)) mbar_wait_fast(sb + BAR_CSF + 4 * s, t & 1);
        if (s >= 2 && t <= 1) { cs_load(cs, 2 + s); cs_apply(acc2 + 32 * (s - 2), cs); }
        cs_load(cs, s);
        c.drain();
        cs_apply(acc + 32 * s, cs);
      }
      c.step<256>(acc);
      if (lane == 0) mbar_arrive(sb + BAR_CSE);
      c.drain();
      acc_fence<128>(acc);
      TL(wg, 1 + it * 6);
      uint32_t pkB[64];
      if (t == 2) {
#pragma unroll
        for (int i = 0; i < 64; i++) pkB[i] = pack_bf16(acc[2 * i], acc[2 * i + 1]);
      } else {
      uint32_t pkA[64];
#pragma unroll
      for (int i = 0; i < 64; i++) pkA[i] = pack_bf16(acc[2 * i] * rstd[i & 1], acc[2 * i + 1] * rstd[i & 1]);
      if (t == 0) {
        const uint32_t xa = sb + SM_STAGE + lane * 16;
        c.step<128>(acc2);
        stage_wait();
#pragma unroll
        for (int i = 0; i < 4; i++) sts128(xa + warp * 4096 + i * 512, pkA[8 * i + 1], pkA[8 * i + 3], pkA[8 * i + 5], pkA[8 * i + 7]);
#pragma unroll
        for (int s = 0; s < 4; s++) {
          c.step<128>(acc2);
          if (s == 2) { __syncwarp(); if (lane == 0) mbar_arrive(sb + BAR_XFULL); }
#pragma unroll
          for (int i = 0; i < 8; i++) { const int r = 32 + (s & 1) * 16 + 2 * i + (s < 2); pkA[r] = movm(pkA[r]); }
          if (s < 2) {
#pragma unroll
            for (int i = 4 + 2 * s; i < 6 + 2 * s; i++) sts128(xa + warp * 4096 + i * 512, pkA[8 * i + 1], pkA[8 * i + 3], pkA[8 * i + 5], pkA[8 * i + 7]);
          }
        }
        c.steps<128>(acc2, 6);
        uint32_t kvH[32];
        mbar_wait_fast(sb + (warp ? BAR_XFULL : BAR_HALO), hl >> 1);
#pragma unroll
        for (int s = 0; s < 3; s++) {
          c.step<128>(acc2);
#pragma unroll
          for (int i = s * 3; i < s * 3 + 3 && i < 8; i++) lds128(xa + ((warp + 7) & 7) * 4096 + i * 512, kvH[4 * i], kvH[4 * i + 1], kvH[4 * i + 2], kvH[4 * i + 3]);
        }
        c.drain();
        acc_fence<64>(acc2);
        TL(wg, 2 + it * 6);
        uint32_t q[32];
#pragma unroll
        for (int i = 0; i < 32; i++) q[i] = pack_bf16(acc2[2 * i], acc2[2 * i + 1]);
        bar_sync(1, 256);
        const bool nohalo = (warp == 0 && g < 2);
        const bool c0 = (2 * quad <= gr), c1 = (2 * quad + 1 <= gr);
        const float sc0 = rstd[0] * (0.17677669529663687f * LOG2E), sc1 = rstd[1] * (0.17677669529663687f * LOG2E);
#pragma unroll
        for (int hf = 0; hf < 2; hf++) {
          uint32_t op[16];
#pragma unroll
          for (int hh = 0; hh < 2; hh++) {
            const int h = hf * 2 + hh;
            float sH[4] = {0, 0, 0, 0}, sL[4] = {0, 0, 0, 0}, sU[4] = {0, 0, 0, 0};
#pragma unroll
            for (int kk = 0; kk < 2; kk++) {
              const int b = h * 4 + kk * 2;
              mma16816(sH, q[2 * b], q[2 * b + 1], q[2 * b + 2], q[2 * b + 3], kvH[b], kvH[b + 1]);
              mma16816(sL, q[2 * b], q[2 * b + 1], q[2 * b + 2], q[2 * b + 3], pkA[2 * b], pkA[2 * b + 2]);
              mma16816(sU, q[2 * b], q[2 * b + 1], q[2 * b + 2], q[2 * b + 3], pkA[2 * b + 1], pkA[2 * b + 3]);
            }
            float a0 = (c0 ? sL[0] : sH[0]) * sc0, a1 = (c1 ? sL[1] : sH[1]) * sc0;
            float b0 = (c0 ? sU[2] : sL[2]) * sc1, b1 = (c1 ? sU[3] : sL[3]) * sc1;
            if (nohalo) { if (!c0) a0 = -1e9f * LOG2E; if (!c1) a1 = -1e9f * LOG2E; }
            float ma = fmaxf(a0, a1), mb = fmaxf(b0, b1);
            ma = fmaxf(ma, __shfl_xor_sync(0xffffffffu, ma, 1)); mb = fmaxf(mb, __shfl_xor_sync(0xffffffffu, mb, 1));
            ma = fmaxf(ma, __shfl_xor_sync(0xffffffffu, ma, 2)); mb = fmaxf(mb, __shfl_xor_sync(0xffffffffu, mb, 2));
            a0 = ex2(a0 - ma); a1 = ex2(a1 - ma); b0 = ex2(b0 - mb); b1 = ex2(b1 - mb);
            const uint32_t pa = pack_bf16(a0, a1), pb = pack_bf16(b0, b1);
            const uint32_t lm = (c0 ? 0xffffu : 0u) | (c1 ? 0xffff0000u : 0u);
            float sa = bf_lo(pa) + bf_hi(pa), sbb = bf_lo(pb) + bf_hi(pb);
            sa += __shfl_xor_sync(0xffffffffu, sa, 1); sbb += __shfl_xor_sync(0xffffffffu, sbb, 1);
            sa += __shfl_xor_sync(0xffffffffu, sa, 2); sbb += __shfl_xor_sync(0xffffffffu, sbb, 2);
            const float ra = rcp(sa), rb = rcp(sbb);
#pragma unroll
            for (int d = 0; d < 4; d++) {
              const int b = h * 4 + d;
              float o[4] = {0, 0, 0, 0};
              mma16816(o, pa & ~lm, 0u, pa & lm, pb & ~lm, kvH[16 + b], pkA[32 + 2 * b]);
              mma1688(o, 0u, pb & lm, pkA[32 + 2 * b + 1]);
              op[(hh * 4 + d) * 2] = pack_bf16(o[0] * ra, o[1] * ra); op[(hh * 4 + d) * 2 + 1] = pack_bf16(o[2] * rb, o[3] * rb);
            }
          }
#pragma unroll
          for (int i = 0; i < 4; i++) stsm4((maddr ^ (i << 5)) + hf * 8192, op[4 * i], op[4 * i + 1], op[4 * i + 2], op[4 * i + 3]);
          stage_publish();
        }
        bar_sync(1, 256);
        TL(wg, 3 + it * 6);
#pragma unroll
        for (int s = 0; s < 2; s++) c.step_own<128>(acc2, dstage + s * 512, s);
        {
          mbar_wait_fast(sb + BAR_FULL + ((c.n & 7) << 3), (c.n >> 3) & 1);
          const uint32_t ra = maddr - (SM_STAGE + wg * 8192) + (c.off << 4), rbar = 64 + ((c.n & 7) << 3);
          c.advance<2>();
          uint32_t res[32];
#pragma unroll
          for (int i = 0; i < 8; i++) ldsm4((ra ^ ((i & 3) << 5)) + (i >> 2) * PAGE, res[4 * i], res[4 * i + 1], res[4 * i + 2], res[4 * i + 3]);
          c.drain();
          acc_fence<64>(acc2);
#pragma unroll
          for (int i = 0; i < 32; i++) { acc2[2 * i] += bf_lo(res[i]); acc2[2 * i + 1] += bf_hi(res[i]); }
          acc_fence<64>(acc2);
          __syncwarp();
          if (lane < 2) mbar_arrive_cluster(c.ebar + rbar);
        }
        break;
      } else {
        c.steps<128>(acc2, 1 + wg);
        stage_wait();
        glu_slice(pkA, 0, true);
#pragma unroll
        for (int s = 1; s < 8; s++) { c.steps<128>(acc2, (s & 1) || t == 3 ? 2 : 1); if (s == 4) stage_publish(); glu_slice(pkA, s, true); }
        c.step<128>(acc2);
        stage_publish();
        c.steps<128>(acc2, 1 - wg);
        if (t == 3) break;
        {
          c.drain();
          acc_fence<64>(acc2);
        TL(wg, 2 + it * 6);
#pragma unroll
          for (int i = 0; i < 16; i++) {
            pkB[i] = 0; pkB[32 + i] = 0;
            pkB[16 + i] = pack_bf16(acc2[2 * i], acc2[2 * i + 1]);
            pkB[48 + i] = pack_bf16(acc2[32 + 2 * i], acc2[32 + 2 * i + 1]);
          }
        }
      }
      }
      t++;
        if (t == 2) { c.off = 6 << 10; asm volatile("" : "+r"(c.off)); }
        c.step<256>(acc, 0);
        if (t == 3) {
          stage_wait();
          glu_slice(pkB, 0, false);
#pragma unroll
          for (int s = 1; s < 4; s++) { c.step<256>(acc); glu_slice(pkB, s, false); }
        } else {
          c.steps<256>(acc, 3);
          stage_wait();
        }
#pragma unroll
        for (int s = 4; s < 8; s++) { c.step<256>(acc); if (s == 4 && t == 3) stage_publish(); glu_slice(pkB, s, false); }
#pragma unroll
        for (int s = 0; s < 2; s++) {
          const uint32_t ra = maddr - (SM_STAGE + wg * 8192) + (c.off << 4);
          c.step<256>(acc);
          if (s == 0) stage_publish();
#pragma unroll
          for (int i = 0; i < 4; i++) {
            uint32_t v[4];
            ldsm4(ra ^ (i << 5), v[0], v[1], v[2], v[3]);
#pragma unroll
            for (int e = 0; e < 4; e++) { acc2[32 * s + 8 * i + 2 * e] = bf_lo(v[e]); acc2[32 * s + 8 * i + 2 * e + 1] = bf_hi(v[e]); }
          }
          acc_fence<32>(acc2 + 32 * s);
        }
        c.step<256>(acc);
      }
      const int it = (hl >> 1) * 4 + t;
      c.steps<128>(acc2, t ? 39 : 14);
      stage_wait();
      c.drain();
      acc_fence<64>(acc2);
      TL(wg, 4 + it * 6);
#pragma unroll
      for (int hf = 0; hf < 2; hf++) {
#pragma unroll
        for (int i = 4 * hf; i < 4 * hf + 4; i++) {
          uint32_t v[4];
#pragma unroll
          for (int e = 0; e < 4; e++) v[e] = pack_bf16(acc2[8 * i + 2 * e], acc2[8 * i + 2 * e + 1]);
          stsm4((maddr ^ ((i & 3) << 5)) + hf * 8192, v[0], v[1], v[2], v[3]);
        }
        stage_publish();
      }
      bar_sync(2 + wg, 128);
      TL(wg, 5 + it * 6); TLG(63);
    }
    }
  }
}

typedef CUresult (*EncodeFn)(CUtensorMap*, CUtensorMapDataType, cuuint32_t, void*, const cuuint64_t*, const cuuint64_t*, const cuuint32_t*,
                             const cuuint32_t*, CUtensorMapInterleave, CUtensorMapSwizzle, CUtensorMapL2promotion, CUtensorMapFloatOOBfill);

void encode(EncodeFn fn, CUtensorMap* m, const void* ptr, int rank, const cuuint64_t* dims, const cuuint64_t* strides, const cuuint32_t* box) {
  cuuint32_t es[5] = {1, 1, 1, 1, 1};
  fn(m, CU_TENSOR_MAP_DATA_TYPE_BFLOAT16, rank, const_cast<void*>(ptr), dims, strides, box, es, CU_TENSOR_MAP_INTERLEAVE_NONE,
     CU_TENSOR_MAP_SWIZZLE_128B, CU_TENSOR_MAP_L2_PROMOTION_L2_128B, CU_TENSOR_MAP_FLOAT_OOB_FILL_NONE);
}

}

extern "C" void kernel_launch(void* const* d_in, const int* in_sizes, int n_in, void* d_out, int out_size) {
  const __nv_bfloat16* x = (const __nv_bfloat16*)d_in[0];
  const __nv_bfloat16* wqkv = (const __nv_bfloat16*)d_in[1];
  const __nv_bfloat16* wo = (const __nv_bfloat16*)d_in[2];
  const __nv_bfloat16* w1 = (const __nv_bfloat16*)d_in[4];
  const __nv_bfloat16* w3 = (const __nv_bfloat16*)d_in[5];
  const __nv_bfloat16* w2 = (const __nv_bfloat16*)d_in[6];

  void* fnp = nullptr; cudaDriverEntryPointQueryResult qr;
  cudaGetDriverEntryPoint("cuTensorMapEncodeTiled", &fnp, cudaEnableDefault, &qr);
  EncodeFn fn = (EncodeFn)fnp;
  void *act, *h;
  cudaGetSymbolAddress(&act, g_act); cudaGetSymbolAddress(&h, g_h);

  Params P = {};
  { cuuint64_t d[3] = {DM, 2, SEQ / 2}, s[2] = {DM * 2, DM * 4}; cuuint32_t b[3] = {64, 1, 128}, b2[3] = {64, 1, 64};
    encode(fn, &P.map[M_XIN], x, 3, d, s, b); encode(fn, &P.map[M_XIN64], x, 3, d, s, b2); encode(fn, &P.map[M_OUT_ST], d_out, 3, d, s, b2); }
  { cuuint64_t d[2] = {DM, 3 * SEQ}, s[1] = {DM * 2}; cuuint32_t b[2] = {64, 128}, b2[2] = {64, 64};
    encode(fn, &P.map[M_ACT_LD], act, 2, d, s, b); encode(fn, &P.map[M_ACT_ST], act, 2, d, s, b2); }
  { cuuint64_t d[2] = {FF, SEQ}, s[1] = {FF * 2}; cuuint32_t b[2] = {64, 128}, b2[2] = {64, 64};
    encode(fn, &P.map[M_H_LD], h, 2, d, s, b); encode(fn, &P.map[M_H_ST], h, 2, d, s, b2); }
  { const cuuint32_t b2[3] = {64, 64, 2}, b1[3] = {64, 64, 1};
    { cuuint64_t d[3] = {64, DM, 48}, s[2] = {3 * DM * 2, 128}; encode(fn, &P.map[M_WKV], wqkv, 3, d, s, b2); encode(fn, &P.map[M_WQ], wqkv, 3, d, s, b1); }
    { cuuint64_t d[3] = {64, DM, 16}, s[2] = {DM * 2, 128}; encode(fn, &P.map[M_WO], wo, 3, d, s, b1); }
    { cuuint64_t d[3] = {64, FF, 16}, s[2] = {DM * 2, 128}; encode(fn, &P.map[M_W2], w2, 3, d, s, b1); }
    { cuuint64_t d[3] = {64, DM, FF / 64}, s[2] = {FF * 2, 128};
      encode(fn, &P.map[M_W1], w1, 3, d, s, b2); encode(fn, &P.map[M_W3], w3, 3, d, s, b2);
      encode(fn, &P.map[M_W1H], w1, 3, d, s, b1); encode(fn, &P.map[M_W3H], w3, 3, d, s, b1); }
  }
  P.wqkv = wqkv; P.wo = wo; P.w2 = w2;
  int dev = 0, sms = 0;
  cudaGetDevice(&dev);
  cudaDeviceGetAttribute(&sms, cudaDevAttrMultiProcessorCount, dev);
  P.use_smid = (sms == 132);
  cudaFuncSetAttribute(fused_kernel, cudaFuncAttributeMaxDynamicSharedMemorySize, SM_TOTAL);
  fused_kernel<<<132, 384, SM_TOTAL>>>(P);
}
```

```cpp
#include <cuda_runtime.h>
#include <cuda_bf16.h>
#include <cuda.h>
#include <stdint.h>
#include <math.h>

namespace {

constexpr int SEQ = 2048, DM = 1024, FF = 3584;
constexpr float LN_EPS = 1e-5f;
constexpr float LOG2E = 1.4426950408889634f;

constexpr uint32_t G_BLOCK = 2u << 20;
constexpr uint32_t G_H = 0;
constexpr uint32_t G_XA = G_H + 128 * FF * 2;
constexpr uint32_t G_O = G_XA + 128 * DM * 2;
constexpr uint32_t G_STATS = G_O + 2 * 128 * DM * 2;
constexpr uint32_t G_FLAGS = G_STATS + 4 * 128 * 64;
static_assert(G_FLAGS + 2048 <= G_BLOCK, "");
constexpr uint32_t G_HALO = 16 * G_BLOCK;
constexpr uint32_t G_CS = G_HALO + 2 * 16 * 8 * 4096;
constexpr uint32_t G_EPOCH = G_CS + (3 * DM + 2 * FF) * 16;
__device__ __align__(1024) uint8_t g_scratch[18 * G_BLOCK];

enum { M_XIN, M_XIN64, M_XA_LD, M_XA_ST, M_H_LD, M_H_ST, M_OUT_LD, M_OUT_ST, M_WKV, M_WQ, M_WO, M_W1, M_W3, M_W1H, M_W3H, M_W2, M_COUNT };
struct alignas(64) Params {
  CUtensorMap map[M_COUNT];
  uint8_t* scratch;
  const __nv_bfloat16* wqkv;
  const __nv_bfloat16* wo;
  const __nv_bfloat16* w2;
  int use_smid;
};

constexpr uint32_t PAGE = 16384, NPAGE = 12;
constexpr uint32_t SM_STAGE = NPAGE * PAGE;
constexpr uint32_t SM_BAR = SM_STAGE + 2 * PAGE;
constexpr uint32_t SM_CS = SM_BAR + 256;
constexpr uint32_t SM_TOTAL = SM_CS + 1536;
constexpr uint32_t SM_ALLOC = SM_TOTAL;
static_assert(SM_ALLOC <= 232448, "shared memory");
constexpr uint32_t BAR_FULL = SM_BAR, BAR_EMPTY = SM_BAR + 64, BAR_SFULL = SM_BAR + 128;
constexpr uint32_t BAR_XFULL = SM_BAR + 160, BAR_CSE = SM_BAR + 168;
constexpr uint32_t BAR_SEMPTY = SM_BAR + 176, BAR_CSF = SM_BAR + 184, BAR_XIN = SM_BAR + 200;
constexpr uint32_t SM_ROLE = SM_BAR + 216;
enum { EV_XA, EV_XA2, EV_H0, EV_H3, EV_H1, EV_H2, EV_XB, EV_XB2, EV_N };

struct Sched { uint32_t pat[14]; uint32_t page0[14]; bool ok; };
constexpr int seg_steps(int seg) { return seg == 0 || seg == 3 ? 18 : seg == 1 || seg == 4 ? 14 : seg == 2 ? 17 : seg == 5 ? 32 : 56; }
constexpr int step_pages(int seg, int i) {
  return seg == 0 || seg == 3 ? (i < 2 ? 2 : i < 4 ? 1 : 3) : seg == 2 ? (i == 0 ? 2 : 1) : seg == 5 ? 3 : 2;
}
constexpr Sched make_sched() {
  Sched s = {};
  int owner[NPAGE] = {-1, -1, -1, -1, -1, -1, -1, -1, -1, -1, -1, -1};
  int n = 0, tail = 0, page = 0;
  s.ok = true;
  for (int sg = 0; sg < 14; sg++) {
    const int seg = sg % 7;
    if (seg == 5) page = (page + 2) / 3 * 3 % NPAGE;
    if (seg == 0 || seg == 3) page = (page + 5) / 6 * 6 % NPAGE;
    s.page0[sg] = page;
    for (int i = 0; i < seg_steps(seg); i++) {
      const int p = step_pages(seg, i);
      if (page + p > (int)NPAGE) { s.ok = false; return s; }
      int need = n - 8;
      for (int q = 0; q < p; q++) { if (owner[page + q] > need) need = owner[page + q]; owner[page + q] = n; }
      int nw = need + 1 - tail; if (nw < 0) nw = 0;
      tail += nw;
      if (i < 16) s.pat[sg] |= (uint32_t)nw << (2 * i); else if (nw != 1) s.ok = false;
      if (nw > 3) s.ok = false;
      page = (page + p) % NPAGE; n++;
    }
  }
  for (int sg = 0; sg < 7; sg++) if (s.page0[sg] != s.page0[sg + 7] || (sg && s.pat[sg] != s.pat[sg + 7])) s.ok = false;
  return s;
}
constexpr Sched SCHED = make_sched();
static_assert(SCHED.ok && SCHED.page0[0] == 0 && SCHED.page0[3] == 0 && SCHED.page0[5] == 6 && (SCHED.pat[0] & 0xff) == 0, "ring schedule");
template <int SEG> struct Pat { static constexpr uint32_t v = SCHED.pat[SEG]; };

__device__ __forceinline__ uint32_t smem_u32(const void* p) { return (uint32_t)__cvta_generic_to_shared(p); }
__device__ __forceinline__ void mbar_init(uint32_t bar, uint32_t cnt) { asm volatile("mbarrier.init.shared::cta.b64 [%0], %1;" :: "r"(bar), "r"(cnt)); }
__device__ __forceinline__ void mbar_expect_tx(uint32_t bar, uint32_t bytes) { asm volatile("mbarrier.arrive.expect_tx.shared::cta.b64 _, [%0], %1;" :: "r"(bar), "r"(bytes) : "memory"); }
__device__ __forceinline__ void mbar_arrive(uint32_t bar) { asm volatile("mbarrier.arrive.shared::cta.b64 _, [%0];" :: "r"(bar) : "memory"); }
__device__ __forceinline__ void mbar_wait(uint32_t bar, uint32_t parity) {
  asm volatile("{\n.reg .pred p;\n.reg .u32 n;\nmov.u32 n, 0;\nLAB_WAIT:\n"
               "mbarrier.try_wait.parity.shared::cta.b64 p, [%0], %1;\n@p bra LAB_DONE;\n"
               "add.u32 n, n, 1;\nsetp.lt.u32 p, n, 4194304;\n@p bra LAB_WAIT;\ntrap;\nLAB_DONE:\n}" :: "r"(bar), "r"(parity) : "memory");
}
__device__ __forceinline__ void mbar_wait_fast(uint32_t bar, uint32_t parity) {
  asm volatile("{\n.reg .pred p;\nLAB_WAIT:\nmbarrier.try_wait.parity.shared::cta.b64 p, [%0], %1;\n@!p bra LAB_WAIT;\n}" :: "r"(bar), "r"(parity) : "memory");
}
__device__ __forceinline__ void spin_check(uint32_t n) { asm volatile("{\n.reg .pred p;\nsetp.ge.u32 p, %0, 4194304;\n@p st.volatile.global.u32 [%1], %0;\n}" :: "r"(n), "l"(0ull)); }
__device__ __forceinline__ void tma_ld3(uint32_t dst, const CUtensorMap* m, uint32_t bar, int c0, int c1, int c2) {
  asm volatile("cp.async.bulk.tensor.3d.shared::cluster.global.mbarrier::complete_tx::bytes [%0], [%1, {%3, %4, %5}], [%2];" :: "r"(dst), "l"(m), "r"(bar), "r"(c0), "r"(c1), "r"(c2) : "memory");
}
__device__ __forceinline__ void tma_ld3_mc(uint32_t dst, const CUtensorMap* m, uint32_t bar, int c0, int c1, int c2, uint16_t mask) {
  asm volatile("cp.async.bulk.tensor.3d.shared::cluster.global.mbarrier::complete_tx::bytes.multicast::cluster [%0], [%1, {%3, %4, %5}], [%2], %6;"
               :: "r"(dst), "l"(m), "r"(bar), "r"(c0), "r"(c1), "r"(c2), "h"(mask) : "memory");
}
__device__ __forceinline__ uint32_t mapa(uint32_t addr, uint32_t cta) { uint32_t r; asm("mapa.shared::cluster.u32 %0, %1, %2;" : "=r"(r) : "r"(addr), "r"(cta)); return r; }
__device__ __forceinline__ void mbar_arrive_cluster(uint32_t bar) { asm volatile("mbarrier.arrive.shared::cluster.b64 _, [%0];" :: "r"(bar) : "memory"); }
__device__ __forceinline__ void tma_st3(const CUtensorMap* m, uint32_t src, int c0, int c1, int c2) {
  asm volatile("cp.async.bulk.tensor.3d.global.shared::cta.bulk_group [%0, {%2, %3, %4}], [%1];" :: "l"(m), "r"(src), "r"(c0), "r"(c1), "r"(c2) : "memory");
}
__device__ __forceinline__ void bulk_commit() { asm volatile("cp.async.bulk.commit_group;" ::: "memory"); }
template <int N> __device__ __forceinline__ void bulk_wait() { asm volatile("cp.async.bulk.wait_group %0;" :: "n"(N) : "memory"); }
__device__ __forceinline__ void fence_async_smem() { asm volatile("fence.proxy.async.shared::cta;" ::: "memory"); }
__device__ __forceinline__ void fence_async_global() { asm volatile("fence.proxy.async.global;" ::: "memory"); }
__device__ __forceinline__ bool elect_one() { uint32_t p; asm volatile("{\n.reg .pred P;\nelect.sync _|P, 0xffffffff;\nselp.u32 %0, 1, 0, P;\n}" : "=r"(p)); return p; }
__device__ __forceinline__ void prefetch_map(const CUtensorMap* m) { asm volatile("prefetch.tensormap [%0];" :: "l"(m) : "memory"); }
__device__ __forceinline__ void prefetch_l2(const void* p, uint32_t bytes) { asm volatile("cp.async.bulk.prefetch.L2.global [%0], %1;" :: "l"(p), "r"(bytes) : "memory"); }
__device__ __forceinline__ void wgmma_fence() { asm volatile("wgmma.fence.sync.aligned;" ::: "memory"); }
__device__ __forceinline__ void wgmma_commit() { asm volatile("wgmma.commit_group.sync.aligned;" ::: "memory"); }
template <int N> __device__ __forceinline__ void wgmma_wait() { asm volatile("wgmma.wait_group.sync.aligned %0;" :: "n"(N) : "memory"); }
__device__ __forceinline__ uint32_t desc_lo(uint32_t addr, uint32_t lbo) { return ((addr & 0x3FFFF) >> 4) | ((lbo >> 4) << 16); }
__device__ __forceinline__ uint64_t desc64(uint32_t lo) { uint64_t r; asm("mov.b64 %0, {%1, %2};" : "=l"(r) : "r"(lo), "r"(0x40000040u)); return r; }
__device__ __forceinline__ void bar_sync(int id, int n) { asm volatile("bar.sync %0, %1;" :: "r"(id), "r"(n) : "memory"); }
__device__ __forceinline__ uint32_t pack_bf16(float lo, float hi) { uint32_t r; asm("cvt.rn.bf16x2.f32 %0, %1, %2;" : "=r"(r) : "f"(hi), "f"(lo)); return r; }
__device__ __forceinline__ float bf_lo(uint32_t v) { return __uint_as_float(v << 16); }
__device__ __forceinline__ float bf_hi(uint32_t v) { return __uint_as_float(v & 0xffff0000u); }
__device__ __forceinline__ float ex2(float x) { float r; asm("ex2.approx.ftz.f32 %0, %1;" : "=f"(r) : "f"(x)); return r; }
__device__ __forceinline__ float rcp(float x) { float r; asm("rcp.approx.ftz.f32 %0, %1;" : "=f"(r) : "f"(x)); return r; }
__device__ __forceinline__ void stsm4(uint32_t a, uint32_t r0, uint32_t r1, uint32_t r2, uint32_t r3) {
  asm volatile("stmatrix.sync.aligned.m8n8.x4.shared.b16 [%0], {%1, %2, %3, %4};" :: "r"(a), "r"(r0), "r"(r1), "r"(r2), "r"(r3) : "memory");
}
__device__ __forceinline__ void ldsm4(uint32_t a, uint32_t& r0, uint32_t& r1, uint32_t& r2, uint32_t& r3) {
  asm volatile("ldmatrix.sync.aligned.m8n8.x4.shared.b16 {%0, %1, %2, %3}, [%4];" : "=r"(r0), "=r"(r1), "=r"(r2), "=r"(r3) : "r"(a) : "memory");
}
__device__ __forceinline__ uint32_t movm(uint32_t v) { uint32_t r; asm volatile("movmatrix.sync.aligned.m8n8.trans.b16 %0, %1;" : "=r"(r) : "r"(v)); return r; }
__device__ __forceinline__ void sts128(uint32_t a, uint32_t r0, uint32_t r1, uint32_t r2, uint32_t r3) {
  asm volatile("st.shared.v4.b32 [%0], {%1, %2, %3, %4};" :: "r"(a), "r"(r0), "r"(r1), "r"(r2), "r"(r3) : "memory");
}
__device__ __forceinline__ void lds128(uint32_t a, uint32_t& r0, uint32_t& r1, uint32_t& r2, uint32_t& r3) {
  asm volatile("ld.shared.v4.b32 {%0, %1, %2, %3}, [%4];" : "=r"(r0), "=r"(r1), "=r"(r2), "=r"(r3) : "r"(a) : "memory");
}
__device__ __forceinline__ void sts32f(uint32_t a, float v) { asm volatile("st.shared.f32 [%0], %1;" :: "r"(a), "f"(v) : "memory"); }
__device__ __forceinline__ void mma16816(float (&d)[4], uint32_t a0, uint32_t a1, uint32_t a2, uint32_t a3, uint32_t b0, uint32_t b1, const float (&c)[4]) {
  asm("mma.sync.aligned.m16n8k16.row.col.f32.bf16.bf16.f32 {%0, %1, %2, %3}, {%4, %5, %6, %7}, {%8, %9}, {%10, %11, %12, %13};"
      : "=f"(d[0]), "=f"(d[1]), "=f"(d[2]), "=f"(d[3]) : "r"(a0), "r"(a1), "r"(a2), "r"(a3), "r"(b0), "r"(b1), "f"(c[0]), "f"(c[1]), "f"(c[2]), "f"(c[3]));
}
__device__ __forceinline__ void mma1688(float (&d)[4], uint32_t a0, uint32_t a1, uint32_t b0, const float (&c)[4]) {
  asm("mma.sync.aligned.m16n8k8.row.col.f32.bf16.bf16.f32 {%0, %1, %2, %3}, {%4, %5}, {%6}, {%7, %8, %9, %10};"
      : "=f"(d[0]), "=f"(d[1]), "=f"(d[2]), "=f"(d[3]) : "r"(a0), "r"(a1), "r"(b0), "f"(c[0]), "f"(c[1]), "f"(c[2]), "f"(c[3]));
}
__device__ __forceinline__ void mma16816z(float (&d)[4], uint32_t a0, uint32_t a1, uint32_t a2, uint32_t a3, uint32_t b0, uint32_t b1) {
  asm("mma.sync.aligned.m16n8k16.row.col.f32.bf16.bf16.f32 {%0, %1, %2, %3}, {%4, %5, %6, %7}, {%8, %9}, {0f00000000, 0f00000000, 0f00000000, 0f00000000};"
      : "=f"(d[0]), "=f"(d[1]), "=f"(d[2]), "=f"(d[3]) : "r"(a0), "r"(a1), "r"(a2), "r"(a3), "r"(b0), "r"(b1));
}
__device__ __forceinline__ void mma1688z(float (&d)[4], uint32_t a0, uint32_t a1, uint32_t b0) {
  asm("mma.sync.aligned.m16n8k8.row.col.f32.bf16.bf16.f32 {%0, %1, %2, %3}, {%4, %5}, {%6}, {0f00000000, 0f00000000, 0f00000000, 0f00000000};"
      : "=f"(d[0]), "=f"(d[1]), "=f"(d[2]), "=f"(d[3]) : "r"(a0), "r"(a1), "r"(b0));
}
__device__ __forceinline__ uint32_t bar_sync_zero(int id, int n) {
  uint32_t r;
  asm volatile("{\n.reg .pred p;\nsetp.eq.u32 p, %1, 0;\nbarrier.cta.red.popc.aligned.u32 %0, %1, %2, p;\n}" : "=r"(r) : "r"(id), "r"(n) : "memory");
  return r;
}
__device__ __forceinline__ uint32_t late_zero(uint32_t zm) { uint32_t c; asm volatile("mov.u32 %0, %%clock;" : "=r"(c) :: "memory"); return c & zm; }
#define CS_START 0
#define EARLY_FETCH 0
__device__ __forceinline__ void st_b128(uint4* p, uint32_t a, uint32_t b, uint32_t c, uint32_t d) {
  asm volatile("{\n.reg .b128 t;\n.reg .b64 lo, hi;\nmov.b64 lo, {%0, %1};\nmov.b64 hi, {%2, %3};\nmov.b128 t, {lo, hi};\nst.relaxed.gpu.global.b128 [%4], t;\n}"
               :: "r"(a), "r"(b), "r"(c), "r"(d), "l"(p) : "memory");
}
__device__ __forceinline__ uint32_t pkt_head(uint32_t a) { return a ? a : 0x8000u; }
__device__ __forceinline__ void gen_store(uint4* p, uint32_t a, uint32_t b, uint32_t c, uint32_t d) {
  asm volatile("{\n.reg .b128 t;\n.reg .b64 lo, hi;\nmov.b64 lo, {%0, %1};\nmov.b64 hi, {%2, %3};\nmov.b128 t, {lo, hi};\nst.relaxed.gpu.b128 [%4], t;\n}"
               :: "r"(a), "r"(b), "r"(c), "r"(d), "l"(p) : "memory");
}
__device__ __forceinline__ void gen_load(const uint4* p, uint32_t* v) {
  asm volatile("{\n.reg .b128 t;\n.reg .b64 lo, hi;\nld.relaxed.gpu.b128 t, [%4];\nmov.b128 {lo, hi}, t;\nmov.b64 {%0, %1}, lo;\nmov.b64 {%2, %3}, hi;\n}"
               : "=r"(v[0]), "=r"(v[1]), "=r"(v[2]), "=r"(v[3]) : "l"(p) : "memory");
}
__device__ __forceinline__ void pkt_load(const uint4* p, uint32_t* v) {
  asm volatile("{\n.reg .b128 t;\n.reg .b64 lo, hi;\nld.relaxed.gpu.global.b128 t, [%4];\nmov.b128 {lo, hi}, t;\nmov.b64 {%0, %1}, lo;\nmov.b64 {%2, %3}, hi;\n}"
               : "=r"(v[0]), "=r"(v[1]), "=r"(v[2]), "=r"(v[3]) : "l"(p) : "memory");
}
__device__ __forceinline__ uint32_t ld_relaxed(const uint32_t* p) { uint32_t v; asm volatile("ld.relaxed.gpu.global.u32 %0, [%1];" : "=r"(v) : "l"(p) : "memory"); return v; }
__device__ __forceinline__ uint4 ld_relaxed4(const void* p) { uint4 v; asm volatile("ld.relaxed.gpu.global.v4.u32 {%0, %1, %2, %3}, [%4];" : "=r"(v.x), "=r"(v.y), "=r"(v.z), "=r"(v.w) : "l"(p) : "memory"); return v; }
__device__ __forceinline__ void st_relaxed(uint32_t* p, uint32_t v) { asm volatile("st.relaxed.gpu.global.u32 [%0], %1;" :: "l"(p), "r"(v) : "memory"); }
__device__ __forceinline__ void st_relaxed2(void* p, uint32_t a, uint32_t b) { asm volatile("st.relaxed.gpu.global.v2.u32 [%0], {%1, %2};" :: "l"(p), "r"(a), "r"(b) : "memory"); }
__device__ __forceinline__ void red_release(uint32_t* p, uint32_t v) { asm volatile("red.release.gpu.global.add.u32 [%0], %1;" :: "l"(p), "r"(v) : "memory"); }
__device__ __forceinline__ uint32_t tagf(float v, uint32_t tag) { return (__float_as_uint(v) & ~15u) | (tag & 15u); }
__device__ __forceinline__ bool tag_ok4(const uint4& v, uint32_t tag) { return (((v.x ^ tag) | (v.y ^ tag) | (v.z ^ tag) | (v.w ^ tag)) & 15u) == 0; }
__device__ __forceinline__ float untag(uint32_t v) { return __uint_as_float(v & ~15u); }
template <typename T> __device__ __forceinline__ T* ptr_add(T* p, uint32_t bytes) {
  uint64_t r;
  asm("{\n.reg .u32 lo, hi;\nmov.b64 {lo, hi}, %1;\nadd.cc.u32 lo, lo, %2;\naddc.u32 hi, hi, 0;\nmov.b64 %0, {lo, hi};\n}" : "=l"(r) : "l"(p), "r"(bytes));
  return (T*)r;
}
#define TL(who, slot) do {} while (0)
#define ST(who, n) do {} while (0)
#define SP(v) do {} while (0)
#define SPW(who, slot, v) do {} while (0)
#define TLG(slot) do {} while (0)
#define STA() do {} while (0)
#define STB(n) do {} while (0)

__device__ __forceinline__ void wgmma_n128(float (&d)[64], uint64_t da, uint64_t db, int scale_d) {
  asm volatile("{\n.reg .pred p;\nsetp.ne.b32 p, %66, 0;\n"
    "wgmma.mma_async.sync.aligned.m64n128k16.f32.bf16.bf16 "
    "{%0, %1, %2, %3, %4, %5, %6, %7, %8, %9, %10, %11, %12, %13, %14, %15, "
    "%16, %17, %18, %19, %20, %21, %22, %23, %24, %25, %26, %27, %28, %29, %30, %31, "
    "%32, %33, %34, %35, %36, %37, %38, %39, %40, %41, %42, %43, %44, %45, %46, %47, "
    "%48, %49, %50, %51, %52, %53, %54, %55, %56, %57, %58, %59, %60, %61, %62, %63}, "
    "%64, %65, p, 1, 1, 0, 1;\n}\n"
    : "+f"(d[0]), "+f"(d[1]), "+f"(d[2]), "+f"(d[3]), "+f"(d[4]), "+f"(d[5]), "+f"(d[6]), "+f"(d[7]),
      "+f"(d[8]), "+f"(d[9]), "+f"(d[10]), "+f"(d[11]), "+f"(d[12]), "+f"(d[13]), "+f"(d[14]), "+f"(d[15]),
      "+f"(d[16]), "+f"(d[17]), "+f"(d[18]), "+f"(d[19]), "+f"(d[20]), "+f"(d[21]), "+f"(d[22]), "+f"(d[23]),
      "+f"(d[24]), "+f"(d[25]), "+f"(d[26]), "+f"(d[27]), "+f"(d[28]), "+f"(d[29]), "+f"(d[30]), "+f"(d[31]),
      "+f"(d[32]), "+f"(d[33]), "+f"(d[34]), "+f"(d[35]), "+f"(d[36]), "+f"(d[37]), "+f"(d[38]), "+f"(d[39]),
      "+f"(d[40]), "+f"(d[41]), "+f"(d[42]), "+f"(d[43]), "+f"(d[44]), "+f"(d[45]), "+f"(d[46]), "+f"(d[47]),
      "+f"(d[48]), "+f"(d[49]), "+f"(d[50]), "+f"(d[51]), "+f"(d[52]), "+f"(d[53]), "+f"(d[54]), "+f"(d[55]),
      "+f"(d[56]), "+f"(d[57]), "+f"(d[58]), "+f"(d[59]), "+f"(d[60]), "+f"(d[61]), "+f"(d[62]), "+f"(d[63])
    : "l"(da), "l"(db), "r"(scale_d));
}
__device__ __forceinline__ void wgmma_n256(float (&d)[128], uint64_t da, uint64_t db, int scale_d) {
  asm volatile("{\n.reg .pred p;\nsetp.ne.b32 p, %130, 0;\n"
    "wgmma.mma_async.sync.aligned.m64n256k16.f32.bf16.bf16 "
    "{%0, %1, %2, %3, %4, %5, %6, %7, %8, %9, %10, %11, %12, %13, %14, %15, "
    "%16, %17, %18, %19, %20, %21, %22, %23, %24, %25, %26, %27, %28, %29, %30, %31, "
    "%32, %33, %34, %35, %36, %37, %38, %39, %40, %41, %42, %43, %44, %45, %46, %47, "
    "%48, %49, %50, %51, %52, %53, %54, %55, %56, %57, %58, %59, %60, %61, %62, %63, "
    "%64, %65, %66, %67, %68, %69, %70, %71, %72, %73, %74, %75, %76, %77, %78, %79, "
    "%80, %81, %82, %83, %84, %85, %86, %87, %88, %89, %90, %91, %92, %93, %94, %95, "
    "%96, %97, %98, %99, %100, %101, %102, %103, %104, %105, %106, %107, %108, %109, %110, %111, "
    "%112, %113, %114, %115, %116, %117, %118, %119, %120, %121, %122, %123, %124, %125, %126, %127}, "
    "%128, %129, p, 1, 1, 0, 1;\n}\n"
    : "+f"(d[0]), "+f"(d[1]), "+f"(d[2]), "+f"(d[3]), "+f"(d[4]), "+f"(d[5]), "+f"(d[6]), "+f"(d[7]),
      "+f"(d[8]), "+f"(d[9]), "+f"(d[10]), "+f"(d[11]), "+f"(d[12]), "+f"(d[13]), "+f"(d[14]), "+f"(d[15]),
      "+f"(d[16]), "+f"(d[17]), "+f"(d[18]), "+f"(d[19]), "+f"(d[20]), "+f"(d[21]), "+f"(d[22]), "+f"(d[23]),
      "+f"(d[24]), "+f"(d[25]), "+f"(d[26]), "+f"(d[27]), "+f"(d[28]), "+f"(d[29]), "+f"(d[30]), "+f"(d[31]),
      "+f"(d[32]), "+f"(d[33]), "+f"(d[34]), "+f"(d[35]), "+f"(d[36]), "+f"(d[37]), "+f"(d[38]), "+f"(d[39]),
      "+f"(d[40]), "+f"(d[41]), "+f"(d[42]), "+f"(d[43]), "+f"(d[44]), "+f"(d[45]), "+f"(d[46]), "+f"(d[47]),
      "+f"(d[48]), "+f"(d[49]), "+f"(d[50]), "+f"(d[51]), "+f"(d[52]), "+f"(d[53]), "+f"(d[54]), "+f"(d[55]),
      "+f"(d[56]), "+f"(d[57]), "+f"(d[58]), "+f"(d[59]), "+f"(d[60]), "+f"(d[61]), "+f"(d[62]), "+f"(d[63]),
      "+f"(d[64]), "+f"(d[65]), "+f"(d[66]), "+f"(d[67]), "+f"(d[68]), "+f"(d[69]), "+f"(d[70]), "+f"(d[71]),
      "+f"(d[72]), "+f"(d[73]), "+f"(d[74]), "+f"(d[75]), "+f"(d[76]), "+f"(d[77]), "+f"(d[78]), "+f"(d[79]),
      "+f"(d[80]), "+f"(d[81]), "+f"(d[82]), "+f"(d[83]), "+f"(d[84]), "+f"(d[85]), "+f"(d[86]), "+f"(d[87]),
      "+f"(d[88]), "+f"(d[89]), "+f"(d[90]), "+f"(d[91]), "+f"(d[92]), "+f"(d[93]), "+f"(d[94]), "+f"(d[95]),
      "+f"(d[96]), "+f"(d[97]), "+f"(d[98]), "+f"(d[99]), "+f"(d[100]), "+f"(d[101]), "+f"(d[102]), "+f"(d[103]),
      "+f"(d[104]), "+f"(d[105]), "+f"(d[106]), "+f"(d[107]), "+f"(d[108]), "+f"(d[109]), "+f"(d[110]), "+f"(d[111]),
      "+f"(d[112]), "+f"(d[113]), "+f"(d[114]), "+f"(d[115]), "+f"(d[116]), "+f"(d[117]), "+f"(d[118]), "+f"(d[119]),
      "+f"(d[120]), "+f"(d[121]), "+f"(d[122]), "+f"(d[123]), "+f"(d[124]), "+f"(d[125]), "+f"(d[126]), "+f"(d[127])
    : "l"(da), "l"(db), "r"(scale_d));
}
__device__ __forceinline__ void wgmma_rs_n128(float (&d)[64], const uint32_t* a, uint64_t db, int scale_d) {
  asm volatile("{\n.reg .pred p;\nsetp.ne.b32 p, %69, 0;\n"
    "wgmma.mma_async.sync.aligned.m64n128k16.f32.bf16.bf16 "
    "{%0, %1, %2, %3, %4, %5, %6, %7, %8, %9, %10, %11, %12, %13, %14, %15, "
    "%16, %17, %18, %19, %20, %21, %22, %23, %24, %25, %26, %27, %28, %29, %30, %31, "
    "%32, %33, %34, %35, %36, %37, %38, %39, %40, %41, %42, %43, %44, %45, %46, %47, "
    "%48, %49, %50, %51, %52, %53, %54, %55, %56, %57, %58, %59, %60, %61, %62, %63}, "
    "{%64, %65, %66, %67}, %68, p, 1, 1, 1;\n}\n"
    : "+f"(d[0]), "+f"(d[1]), "+f"(d[2]), "+f"(d[3]), "+f"(d[4]), "+f"(d[5]), "+f"(d[6]), "+f"(d[7]),
      "+f"(d[8]), "+f"(d[9]), "+f"(d[10]), "+f"(d[11]), "+f"(d[12]), "+f"(d[13]), "+f"(d[14]), "+f"(d[15]),
      "+f"(d[16]), "+f"(d[17]), "+f"(d[18]), "+f"(d[19]), "+f"(d[20]), "+f"(d[21]), "+f"(d[22]), "+f"(d[23]),
      "+f"(d[24]), "+f"(d[25]), "+f"(d[26]), "+f"(d[27]), "+f"(d[28]), "+f"(d[29]), "+f"(d[30]), "+f"(d[31]),
      "+f"(d[32]), "+f"(d[33]), "+f"(d[34]), "+f"(d[35]), "+f"(d[36]), "+f"(d[37]), "+f"(d[38]), "+f"(d[39]),
      "+f"(d[40]), "+f"(d[41]), "+f"(d[42]), "+f"(d[43]), "+f"(d[44]), "+f"(d[45]), "+f"(d[46]), "+f"(d[47]),
      "+f"(d[48]), "+f"(d[49]), "+f"(d[50]), "+f"(d[51]), "+f"(d[52]), "+f"(d[53]), "+f"(d[54]), "+f"(d[55]),
      "+f"(d[56]), "+f"(d[57]), "+f"(d[58]), "+f"(d[59]), "+f"(d[60]), "+f"(d[61]), "+f"(d[62]), "+f"(d[63])
    : "r"(a[0]), "r"(a[1]), "r"(a[2]), "r"(a[3]), "l"(db), "r"(scale_d));
}

template <int BN> __device__ __forceinline__ void wgmma(float (&d)[BN / 2], uint64_t a, uint64_t b, int s) {
  if constexpr (BN == 128) wgmma_n128(d, a, b, s);
  else wgmma_n256(d, a, b, s);
}

template <int N> __device__ __forceinline__ void acc_fence(float* a) {
#pragma unroll
  for (int i = 0; i < N; i++) asm volatile("" : "+f"(a[i]) :: "memory");
}

struct Prod {
  uint32_t sb, n, tail, addr, pat, ready;
  uint32_t rank, flip; uint16_t mask;
  __device__ __forceinline__ void load_b(uint32_t dst, uint32_t half, const CUtensorMap* m, uint32_t mstep, uint32_t fb, int k, int ch, int cstep) {
    uint32_t h = rank;
    do { tma_ld3_mc(dst + h * half, ptr_add(m, h * mstep), fb, 0, k * 64, ch + h * cstep, mask); h ^= flip; } while (h != rank);
  }
  __device__ __forceinline__ void load_wide(const Params& P, int ffn, uint32_t dst, uint32_t fb, int k, int ch) {
    load_b(dst, PAGE, &P.map[ffn ? M_W1 : M_WKV], ffn ? 128 : 0, fb, k, ffn ? ch : ch + 16, ffn ? 0 : 16);
  }
  __device__ __forceinline__ void load_narrow(const Params& P, int ffn, uint32_t dst, uint32_t fb, int k, int j) {
    load_b(dst, 8192, &P.map[ffn ? M_W1H : M_WQ], ffn ? 128 : 0, fb, k, ffn ? 48 + j : 2 * j, ffn ? 0 : 1);
  }
  __device__ __forceinline__ void finish() {
#pragma unroll 1
    for (; tail < n; tail++) mbar_wait(sb + BAR_EMPTY + ((tail & 7) << 3), (tail >> 3) & 1);
  }
  template <int PAGES> __device__ __forceinline__ uint32_t acquire(uint32_t& fb) {
    uint32_t nw = pat & 3; pat = (pat >> 2) | 0x40000000u;
#pragma unroll 1
    for (; nw; nw--) { mbar_wait(sb + BAR_EMPTY + ((tail & 7) << 3), (tail >> 3) & 1); tail++; }
    ST(4, n);
    fb = sb + BAR_FULL + ((n & 7) << 3);
    mbar_expect_tx(fb, PAGES * PAGE);
    const uint32_t a = sb + addr;
    addr += PAGES * PAGE; if (addr >= NPAGE * PAGE) addr = 0;
    n++;
    return a;
  }
  const uint32_t* flag; uint32_t base, peeked;
  __device__ __forceinline__ void peek() { peeked = ld_relaxed(flag + 32); }
  __device__ __forceinline__ void acquire_fence() { asm volatile("fence.acquire.gpu;" ::: "memory"); fence_async_global(); }
  __device__ __forceinline__ void next() { flag += 32; ready = peeked - base; acquire_fence(); }
  __device__ __forceinline__ void need(uint32_t mask) {
    if ((ready & mask) != mask) {
      uint32_t spins = 0;
      do { ready = ld_relaxed(flag) - base; spin_check(++spins); } while ((ready & mask) != mask);
      acquire_fence();
    }
    ST(5, n - 1);
  }
};

struct Cons {
  uint32_t sb, n, off, prev;
  uint32_t ebar;
  uint32_t da0, db0;
  int lane;
  template <int PAGES> __device__ __forceinline__ void advance() {
    n++; off += PAGES << 10; if (off >= (NPAGE << 10)) off = 0;
    asm volatile("" : "+r"(n), "+r"(off));
  }
  template <int BN, int PAGES> __device__ __forceinline__ void step_ab(float (&acc)[BN / 2], uint32_t da, uint32_t db, int accumulate) {
    STA();
    mbar_wait_fast(sb + BAR_FULL + ((n & 7) << 3), (n >> 3) & 1);
    STB(n);
    const uint64_t da64 = desc64(da), db64 = desc64(db);
    wgmma_fence();
#pragma unroll
    for (int k = 0; k < 4; k++) wgmma<BN>(acc, da64 + 2 * k, db64 + 128 * k, k ? 1 : accumulate);
    wgmma_commit();
    wgmma_wait<1>();
    if (prev && lane < 2) mbar_arrive_cluster(ebar + prev);
    prev = 64 + ((n & 7) << 3);
    advance<PAGES>();
  }
  template <int BN> __device__ __forceinline__ void step(float (&acc)[BN / 2], int accumulate = 1) { step_ab<BN, BN / 128 + 1>(acc, da0 + off, db0 + 1024 + off, accumulate); }
  template <int BN> __device__ __forceinline__ void step_own(float (&acc)[BN / 2], uint32_t da, int accumulate) { step_ab<BN, BN / 128>(acc, da, db0 + off, accumulate); }
  __device__ __forceinline__ void wait_full() { mbar_wait_fast(sb + BAR_FULL + ((n & 7) << 3), (n >> 3) & 1); }
  __device__ __forceinline__ void issue_rs(float (&acc)[64], uint32_t (&a)[16]) {
    STA(); STB(n);
    const uint64_t db64 = desc64(db0 + off);
    wgmma_fence();
#pragma unroll
    for (int k = 0; k < 4; k++) wgmma_rs_n128(acc, a + 4 * k, db64 + 128 * k, 1);
    wgmma_commit();
    wgmma_wait<1>();
    if (prev && lane < 2) mbar_arrive_cluster(ebar + prev);
    prev = 64 + ((n & 7) << 3);
    advance<1>();
  }
  template <int BN> __device__ __forceinline__ void steps(float (&acc)[BN / 2], int cnt) {
#pragma unroll 1
    for (int i = 0; i < cnt; i++) step<BN>(acc);
  }
  __device__ __forceinline__ void drain() {
    wgmma_wait<0>();
    if (lane < 2) mbar_arrive_cluster(ebar + prev);
    prev = 0;
  }
};

#define MAPPING 2
__device__ __forceinline__ uint32_t role_of_sm(uint32_t smid) {
  const uint32_t t = smid >> 1;
  uint32_t q, i;
  if (t < 32) { q = t & 7; i = t >> 3; }
  else if (t < 60) { const uint32_t u = t - 32, d = (u * 37) >> 8; q = 1 + u - d * 7; i = 4 + d; }
  else if (t < 62) return 128 + smid - 120;
  else { q = 0; i = t - 58; }
  return (q * 2 + (smid & 1)) * 8 + i;
}

template <typename T> __device__ __forceinline__ T* scratch(const Params& P, uint32_t off) { return (T*)ptr_add(P.scratch, off); }
__device__ __forceinline__ uint32_t* epoch_ptr(const Params& P) { uint32_t b; asm volatile("mov.u32 %0, %%ctaid.x;" : "=r"(b)); return scratch<uint32_t>(P, G_EPOCH + b * 4u); }

__device__ __forceinline__ int o_chunk(int s, int j) { const int hf = s >= 9, m = s - 2 - 7 * hf; return s < 2 ? 2 * j + s : 2 * (m == j ? 7 : m) + hf; }

__global__ void __cluster_dims__(2, 1, 1) __launch_bounds__(384, 1) fused_kernel(const __grid_constant__ Params P) {
  extern __shared__ __align__(1024) uint8_t smem_raw[];
  SP(0);
  const uint32_t sb = __shfl_sync(0xffffffffu, smem_u32(smem_raw), 0);
  const int warp = __shfl_sync(0xffffffffu, threadIdx.x >> 5, 0);
  const int lane = threadIdx.x & 31;
  if (warp >= 8 && elect_one()) {
    if (warp == 8) {
      prefetch_map(&P.map[M_XIN64]); prefetch_map(&P.map[M_WKV]);
#pragma unroll
      for (int i = 0; i < 4; i++) mbar_init(sb + BAR_FULL + 8 * i, 1);
      mbar_init(sb + BAR_XIN, 1); mbar_init(sb + BAR_XIN + 8, 1);
    } else if (warp == 9) {
#pragma unroll
      for (int i = 0; i < 8; i++) mbar_init(sb + BAR_EMPTY + 8 * i, 16);
    } else if (warp == 10) {
#pragma unroll
      for (int i = 0; i < 4; i++) { mbar_init(sb + BAR_FULL + 32 + 8 * i, 1); mbar_init(sb + BAR_SFULL + 8 * i, 4); }
    } else {
      prefetch_map(&P.map[M_XIN]); prefetch_map(&P.map[M_WQ]);
      mbar_init(sb + BAR_XFULL, 8); mbar_init(sb + BAR_CSE, 8);
      mbar_init(sb + BAR_SEMPTY, 1); mbar_init(sb + BAR_CSF, 1); mbar_init(sb + BAR_CSF + 8, 1);
    }
  }
  uint32_t role = blockIdx.x < 128 ? ((blockIdx.x >> 4) * 2 + (blockIdx.x & 1)) * 8 + ((blockIdx.x >> 1) & 7) : blockIdx.x;
  if (P.use_smid) { uint32_t smid; asm volatile("mov.u32 %0, %%smid;" : "=r"(smid)); role = role_of_sm(smid); }
  const bool spare = role >= 128;
  const int g = role >> 3, j = role & 7;
  SP(1);
  if (warp >= 8) {
    if (warp == 11) asm volatile("st.shared.u32 [%0], %1;" :: "r"(sb + SM_ROLE), "r"(role) : "memory");
    asm volatile("fence.mbarrier_init.release.cluster;\nfence.release.sync_restrict::shared::cta.cluster;" ::: "memory");
    fence_async_smem();
    __syncwarp();
  }
  SP(2);
  asm volatile("barrier.cluster.arrive.relaxed.aligned;" ::: "memory");
  if (warp == 8 && !spare) {
    if (elect_one()) {
#pragma unroll 1
      for (int s = 0; s < 2; s++) {
        const uint32_t xb = sb + BAR_XIN + 8 * s, fb = sb + BAR_FULL + 8 * s;
        mbar_expect_tx(xb, PAGE); mbar_expect_tx(fb, 2 * PAGE);
#pragma unroll
        for (int h = 0; h < 2; h++) tma_ld3(sb + SM_STAGE + h * PAGE + s * 8192, &P.map[M_XIN64], xb, s * 64, g & 1, (g >> 1) * 128 + h * 64);
#pragma unroll
        for (int h = 0; h < 2; h++) tma_ld3(sb + (2 * s + h) * PAGE, &P.map[M_WKV], fb, 0, s * 64, 16 + 16 * h + 2 * j);
      }
#pragma unroll 1
      for (int s = 0; s < 2; s++) {
        const uint32_t fb = sb + BAR_FULL + 16 + 8 * s;
        mbar_expect_tx(fb, PAGE);
        tma_ld3(sb + (4 + s) * PAGE, &P.map[M_WKV], fb, 0, s * 64, 2 * j);
      }
      spin_check((sb & 1023) << 22);
    }
    __syncwarp();
  }
  SP(3);
  asm volatile("barrier.cluster.wait.acquire.aligned;" ::: "memory");
  SP(4);
  uint32_t rank; asm("mov.u32 %0, %%cluster_ctarank;" : "=r"(rank));
  auto shared_b = [&]() {
    uint32_t peer;
    asm volatile("ld.shared::cluster.u32 %0, [%1];" : "=r"(peer) : "r"(mapa(sb + SM_ROLE, rank ^ 1)) : "memory");
    return !spare && peer < 128 && (peer & 7) == (uint32_t)j;
  };

  if (warp >= 8) {
    asm volatile("setmaxnreg.dec.sync.aligned.u32 40;");
    if (warp == 8) {
      if (elect_one()) {
        Prod p; p.sb = sb; p.n = 0; p.tail = 0; p.ready = 0; p.addr = 0;
        { const bool mc = shared_b(); p.rank = rank; p.flip = !mc; p.mask = mc ? 3 : 1 << rank; }
        uint32_t fb;
        if (spare) {
          p.pat = 0x55555000u;
#pragma unroll 1
          for (int r = 0; r < 7; r++) {
            const int ch = ((r < 2 ? r : r == 2 ? 6 : r - 1) * 4 + j) * 2;
#pragma unroll 1
            for (int k = 0; k < 16; k++) { const uint32_t a = p.acquire<2>(fb); p.load_wide(P, 1, a, fb, k, ch); }
          }
        } else {
          p.flag = scratch<uint32_t>(P, g * G_BLOCK + G_FLAGS - 128);
          SP(5);
#pragma unroll 1
          for (int hl = 0; hl < 4; hl++) {
            const int ffn = hl & 1;
            const CUtensorMap* xmap = &P.map[ffn ? M_XA_LD : hl ? M_OUT_LD : M_XIN];
            const int xpar = ffn ? g : g & 1, xrow = ffn ? 0 : (g >> 1) * 128;
            if (hl) {
              p.pat = ffn ? Pat<3>::v : Pat<7>::v; p.addr = 0;
#pragma unroll 1
              for (int s = 0; s < 2; s++) { const uint32_t a = p.acquire<2>(fb); p.load_wide(P, ffn, a, fb, 2 * j + s, 2 * j); }
#pragma unroll 1
              for (int s = 0; s < 2; s++) { const uint32_t a = p.acquire<1>(fb); p.load_narrow(P, ffn, a, fb, 2 * j + s, j); }
            } else { p.pat = (Pat<0>::v >> 8) | 0x55000000u; p.addr = 6 * PAGE; p.n = 4; }
            if (hl == 0) SP(6);
            uint32_t fb0 = 0;
#pragma unroll 1
            for (int m = 0; m < 14; m++) {
              const int hf = m >= 7, mm = m - 7 * hf, jj = mm == j ? 7 : mm;
              int k = 2 * jj + hf;
              if (hl == 0) {
                const int pr = (m >> 1) + 1;
                k = 2 * (j && pr == 2 ? j : pr == j ? 2 : pr) + (m & 1);
              }
              const uint32_t a = p.acquire<3>(fb);
              p.load_wide(P, ffn, a + PAGE, fb, k, 2 * j);
              if (hl) {
                if (m == 0) { fb0 = fb; continue; }
                if (m == 1) {
                  const int j0 = j ? 0 : 7;
                  p.flag += 32; p.ready = 0; p.need((1u << j0) | (1u << j));
                  tma_ld3(a - 3 * PAGE, xmap, fb0, j0 * 128, xpar, xrow);
                }
                if (m == 7) p.next();
                p.need(m == 13 ? 0xffu : 1u << jj);
              }
              tma_ld3(a, xmap, fb, k * 64, xpar, xrow);
              if (m == 5) { if (hl) p.peek(); else p.base = ld_relaxed(epoch_ptr(P)) * 255; }
            }
            static_assert(Pat<1>::v == Pat<4>::v, "");
            p.pat = Pat<1>::v;
#pragma unroll 1
            for (int m = 0; m < 14; m++) {
              const int k = (m >> 1) == (hl ? j : 0) ? 14 + (m & 1) : m;
              const uint32_t a = p.acquire<2>(fb);
              p.load_narrow(P, ffn, a + PAGE, fb, k, j);
              tma_ld3(a, xmap, fb, k * 64, xpar, xrow);
            }
            if (!ffn) {
              p.pat = Pat<2>::v;
              { const uint32_t a = p.acquire<2>(fb); tma_ld3(a, xmap, fb, j * 128, xpar, xrow); tma_ld3(a + PAGE, xmap, fb, j * 128 + 64, xpar, xrow); }
#pragma unroll 1
              for (int s = 0; s < 16; s++) {
                const uint32_t a = p.acquire<1>(fb);
                p.load_b(a, 8192, &P.map[M_WO], 0, fb, o_chunk(s, j), 2 * j, 1);
              }
            } else {
              p.pat = Pat<5>::v; p.addr = 6 * PAGE;
#pragma unroll 1
              for (int s = 16; s < 48; s++) {
                const int pi = (s >> 1) & 7;
                const int k = (s < 32 ? pi : pi == 4 ? j : pi == j ? 4 : pi) * 2 + (s & 1);
                const uint32_t a = p.acquire<3>(fb);
                p.load_wide(P, 1, a + PAGE, fb, k, (s & 48) + 2 * j);
                tma_ld3(a, xmap, fb, k * 64, g, 0);
                if (s == 45) p.peek();
              }
              p.pat = Pat<6>::v;
#pragma unroll 1
              for (int q = 0; q < 4; q++) {
                p.next(); p.need(0xffu);
                const int k0 = q == 0 ? 0 : q == 1 ? 48 : q * 16 - 16, k1 = k0 + (q == 1 ? 8 : 16);
#pragma unroll 1
                for (int k = k0; k < k1; k++) {
                  const uint32_t a = p.acquire<2>(fb);
                  p.load_b(a + PAGE, 8192, &P.map[M_W2], 0, fb, k, 2 * j, 1);
                  tma_ld3(a, &P.map[M_H_LD], fb, k * 64, g, 0);
                  if (k == k1 - 4) p.peek();
                }
              }
            }
            TL(2, 1 + hl);
          }
        }
        p.finish();
      }
    } else if (!spare) {
      const uint32_t tag = ld_relaxed(epoch_ptr(P)) + 1;
      mbar_wait(sb + BAR_XIN + CS_START, 0);
      if (elect_one()) prefetch_l2(ptr_add(P.wqkv, (role * 3 + (warp - 9)) * 16384u), 16384);
#pragma unroll 1
      for (int r = 0; r < 2; r++) {
        const uint32_t u = role * 3 + (warp - 9) + r * 384;
        const uint32_t strip = u < 512 ? 64 + (u >> 2) : (u - 512) >> 2, part = u & 3;
        const uint32_t col = strip * 16 + (lane & 1) * 8;
        const uint4* wp = ptr_add((const uint4*)P.wqkv, (part * 256 + (lane >> 1)) * 6144u + col * 2);
        float s[8] = {0, 0, 0, 0, 0, 0, 0, 0};
        uint4 v[4];
#pragma unroll
        for (int i = 0; i < 4; i++) v[i] = __ldcg(wp + i * (16 * 6144 / 16));
#pragma unroll 1
        for (int b = 0; b < 4; b++) {
          wp += 64 * 6144 / 16;
#pragma unroll
          for (int i = 0; i < 4; i++) {
            s[0] += bf_lo(v[i].x); s[1] += bf_hi(v[i].x); s[2] += bf_lo(v[i].y); s[3] += bf_hi(v[i].y);
            s[4] += bf_lo(v[i].z); s[5] += bf_hi(v[i].z); s[6] += bf_lo(v[i].w); s[7] += bf_hi(v[i].w);
            if (b < 3) v[i] = __ldcg(wp + i * (16 * 6144 / 16));
          }
        }
#pragma unroll
        for (int e = 0; e < 4; e++) { const bool h = lane & 16; const float t = __shfl_xor_sync(0xffffffffu, h ? s[e] : s[e + 4], 16); s[e] = (h ? s[e + 4] : s[e]) + t; }
#pragma unroll
        for (int e = 0; e < 2; e++) { const bool h = lane & 8; const float t = __shfl_xor_sync(0xffffffffu, h ? s[e] : s[e + 2], 8); s[e] = (h ? s[e + 2] : s[e]) + t; }
        { const bool h = lane & 4; const float t = __shfl_xor_sync(0xffffffffu, h ? s[0] : s[1], 4); s[0] = (h ? s[1] : s[0]) + t; }
        s[0] += __shfl_xor_sync(0xffffffffu, s[0], 2);
        if (!(lane & 2)) st_relaxed(scratch<uint32_t>(P, G_CS + (col + (lane >> 2)) * 16 + part * 4), tagf(s[0], tag));
        __syncwarp();
      }
      if (warp == 11 && lane == 0) TL(2, 30);
      if (warp == 11) {
        if (elect_one()) {
          prefetch_l2(ptr_add(P.wo, role * 16384u), 16384);
          mbar_wait(sb + BAR_CSE, 0); mbar_wait(sb + BAR_CSE, 1); mbar_wait(sb + BAR_CSE, 0);
#pragma unroll 1
          for (int i = 0; i < 7; i++) { prefetch_l2(ptr_add(P.w2, (i * 128 + role) * 8192u), 8192); __nanosleep(500); }
        }
      } else if (warp == 9) {
        if (elect_one()) {
          prefetch_map(&P.map[M_XA_ST]); prefetch_map(&P.map[M_XA_LD]); prefetch_map(&P.map[M_OUT_LD]); prefetch_map(&P.map[M_WO]); prefetch_map(&P.map[M_W1 + rank]);
          prefetch_map(&P.map[M_H_ST]); prefetch_map(&P.map[M_H_LD]); prefetch_map(&P.map[M_W1H + rank]); prefetch_map(&P.map[M_W2]); prefetch_map(&P.map[M_OUT_ST]);
          uint32_t* fl = scratch<uint32_t>(P, g * G_BLOCK + G_FLAGS);
          int pe = 0;
#pragma unroll 1
          for (int e = 0; e < 2 * EV_N; e++) {
            const int q = e & 7;
            const bool is_h = q >= EV_H0 && q < EV_XB, last = e >= EV_N + EV_XB;
            const CUtensorMap* map = &P.map[q >= EV_XB ? M_OUT_ST : is_h ? M_H_ST : M_XA_ST];
            const int col = q == EV_H3 ? 3072 - 64 + j * 64 : (q == EV_H1 ? 1024 : q == EV_H2 ? 2048 : 0) + j * 128;
            const int row = q >= EV_XB ? (g >> 1) * 128 : 0, par = q >= EV_XB ? g & 1 : g;
#pragma unroll 1
            for (int hb = is_h ? q == EV_H3 : q & 1; hb <= (is_h ? 1 : q & 1); hb++) {
#pragma unroll
              for (int wg = 0; wg < 2; wg++) {
                mbar_wait(sb + BAR_SFULL + 16 * wg + 8 * (pe & 1), (pe >> 1) & 1);
                if (wg == 0) TL(3, 20 + e);
                tma_st3(map, sb + SM_STAGE + wg * PAGE + hb * 8192, col + hb * 64, par, row + wg * 64);
              }
              pe++;
            }
            bulk_commit();
            if (e != EV_N + EV_XB) bulk_wait<0>();
            TL(3, 40 + e);
            if (is_h || (q & 1)) mbar_arrive(sb + BAR_SEMPTY);
            if (!last) red_release(fl, 1u << j);
            TL(3, e);
            fl += 32;
          }
          *epoch_ptr(P) = tag;
        }
      } else if (warp == 10) {
        const uint32_t cspos = sb + SM_CS + ((lane & 16) + ((lane >> 1) & 3) * 4 + ((lane >> 3) & 1) * 2 + (lane & 1)) * 4;
#pragma unroll 1
        for (int it = 0; it < 8; it++) {
          const int t = it & 3;
          if (it) mbar_wait(sb + BAR_CSE, (it - 1) & 1);
#pragma unroll 1
          for (int b = 0; b < (t < 2 ? 3 : 2); b++) {
            uint32_t c0, c1;
            if (b < 2) { c0 = (t ? 2048 + t * 1024 + b * FF : 1024 + b * 1024) + j * 128; c1 = c0 + 64; }
            else if (t) { c0 = 6144 + j * 64; c1 = c0 + FF; }
            else { c0 = j * 128; c1 = c0 + 64; }
            const uint4* p0 = scratch<uint4>(P, G_CS + (c0 + lane) * 16u);
            const uint4* p1 = scratch<uint4>(P, G_CS + (c1 + lane) * 16u);
            uint4 v[4]; uint32_t spins = 0; bool ok;
            do {
              if (spins) __nanosleep(200);
              v[0] = ld_relaxed4(p0); v[1] = ld_relaxed4(p0 + 32); v[2] = ld_relaxed4(p1); v[3] = ld_relaxed4(p1 + 32);
              ok = tag_ok4(v[0], tag) && tag_ok4(v[1], tag) && tag_ok4(v[2], tag) && tag_ok4(v[3], tag);
              spin_check(++spins);
            } while (__any_sync(0xffffffffu, !ok));
#pragma unroll
            for (int m = 0; m < 4; m++) sts32f(cspos + b * 512 + m * 128, (untag(v[m].x) + untag(v[m].y)) + (untag(v[m].z) + untag(v[m].w)));
            if (b == 0) { __syncwarp(); if (lane == 0) mbar_arrive(sb + BAR_CSF); }
          }
          __syncwarp();
          if (lane == 0) { mbar_arrive(sb + BAR_CSF + 8); TL(2, 16 + it); }
          if (t == 3) {
            uint4* op = scratch<uint4>(P, g * G_BLOCK + G_O + ((it >> 2) * 16 + 2 * j) * 16384u + lane * 16u);
#pragma unroll 1
            for (int i = 0; i < 64; i++) { st_b128(op, 0, 0, 0, 0); op += 32; __nanosleep(60); }
            if (g >= 2) {
              op = scratch<uint4>(P, G_HALO + (((it >> 2) * 16 + g - 2) * 8 + j) * 4096u + lane * 16u);
#pragma unroll 1
              for (int i = 0; i < 8; i++) { st_b128(op, 0, 0, 0, 0); op += 32; }
            }
          }
        }
      }
    }
  } else {
    asm volatile("setmaxnreg.inc.sync.aligned.u32 232;");
    SP(5);
    const int wg = warp >> 2;
    const int quad = lane & 3, gr = lane >> 2;
    Cons c; c.sb = sb; c.n = 0; c.off = 0; c.prev = 0; c.lane = lane;
    c.ebar = mapa(sb + BAR_EMPTY - 64, shared_b() ? lane & 1 : rank);
    const uint32_t stage = sb + SM_STAGE + wg * PAGE;
    const uint32_t dstage = desc_lo(stage, 16);
    if (spare) {
      const uint32_t tag = ld_relaxed(epoch_ptr(P)) + 1;
      const int tid = threadIdx.x & 127;
#pragma unroll
      for (int i = 0; i < 4; i++) sts128(stage + (i * 128 + tid) * 16, 0x3f803f80u, 0x3f803f80u, 0x3f803f80u, 0x3f803f80u);
      fence_async_smem();
      bar_sync(2 + wg, 128);
      c.db0 = desc_lo(sb + wg * PAGE, 8192);
#pragma unroll 1
      for (int r = 0; r < 7; r++) {
        float acc[64];
#pragma unroll 1
        for (int k = 0; k < 16; k++) c.step_ab<128, 2>(acc, dstage, c.db0 + c.off, k);
        c.drain();
        acc_fence<64>(acc);
        {
          float v = 0;
#pragma unroll
          for (int i = 0; i < 32; i++) asm("{\n.reg .pred p;\nsetp.eq.u32 p, %2, %3;\nselp.f32 %0, %1, %0, p;\n}" : "+f"(v) : "f"(acc[4 * (i >> 1) + (i & 1)]), "r"(tid >> 2), "r"(i));
          st_b128(scratch<uint4>(P, G_CS + (uint32_t)(3 * DM + wg * FF + ((r < 2 ? r : r == 2 ? 6 : r - 1) * 4 + j) * 128 + (tid >> 3) * 8 + quad * 2 + (gr & 1)) * 16u),
                  tagf(v, tag), tag & 15u, tag & 15u, tag & 15u);
        }
        __syncwarp();
      }
      if (wg == 0) {
        const uint32_t* p = scratch<uint32_t>(P, (tid >> 3) * G_BLOCK + G_STATS + (tid & 7) * 8u);
        uint32_t spins = 0;
        while (__any_sync(0xffffffffu, (ld_relaxed(p) ^ tag) & 15u)) spin_check(++spins);
      }
      bar_sync(1, 256);
      if (threadIdx.x == 0) *epoch_ptr(P) = tag;
    } else {
    c.da0 = desc_lo(sb + wg * 8192, 16); c.db0 = desc_lo(sb, 8192);
    uint32_t sphase = 1, sfull = sb + BAR_SFULL + 16 * wg;
    const uint32_t maddr = stage + ((warp & 3) * 16 + (lane & 15)) * 128 + (((lane >> 4) ^ (lane & 7)) << 4);
    const uint32_t csaddr = sb + SM_CS + quad * 16;
    float mean[2] = {0, 0}, rstd[2] = {0, 0};
    SP(6);

    auto stage_wait = [&]() { mbar_wait_fast(sb + BAR_SEMPTY, sphase); sphase ^= 1; };
    auto stage_publish = [&]() { fence_async_smem(); __syncwarp(); if (lane == 0) mbar_arrive(sfull); sfull ^= 8; };
    auto cs_load = [&](uint32_t (&cs)[16], int grp) {
#pragma unroll
      for (int i = 0; i < 4; i++) lds128(csaddr + grp * 256 + i * 64, cs[4 * i], cs[4 * i + 1], cs[4 * i + 2], cs[4 * i + 3]);
    };
    auto cs_apply = [&](float* acc, uint32_t (&cs)[16]) {
      acc_fence<32>(acc);
#pragma unroll
      for (int b = 0; b < 8; b++) {
        acc[4 * b] -= mean[0] * __uint_as_float(cs[2 * b]); acc[4 * b + 1] -= mean[0] * __uint_as_float(cs[2 * b + 1]);
        acc[4 * b + 2] -= mean[1] * __uint_as_float(cs[2 * b]); acc[4 * b + 3] -= mean[1] * __uint_as_float(cs[2 * b + 1]);
      }
      acc_fence<32>(acc);
    };
    auto glu_pair = [&](float g0, float g1, float u0, float u1, int r) {
      const float nl = -LOG2E * rstd[r], r2 = rstd[r] * rstd[r];
      return pack_bf16(g0 * u0 * r2 * rcp(1.0f + ex2(g0 * nl)), g1 * u1 * r2 * rcp(1.0f + ex2(g1 * nl)));
    };
    auto glu_slice = [&](const uint32_t (&pk)[64], int i) {
      uint32_t hp[4];
#pragma unroll
      for (int e = 0; e < 4; e++) hp[e] = glu_pair(bf_lo(pk[4 * i + e]), bf_hi(pk[4 * i + e]), bf_lo(pk[32 + 4 * i + e]), bf_hi(pk[32 + 4 * i + e]), e & 1);
      stsm4((maddr ^ ((i & 3) << 5)) + (i >> 2) * 8192, hp[0], hp[1], hp[2], hp[3]);
    };
    auto glu_slice_acc = [&](float (&acc)[128], int i) {
      uint32_t hp[4];
      acc_fence<8>(acc + 8 * i);
#pragma unroll
      for (int e = 0; e < 4; e++) hp[e] = glu_pair(acc[8 * i + 2 * e], acc[8 * i + 2 * e + 1], acc[64 + 8 * i + 2 * e], acc[64 + 8 * i + 2 * e + 1], e & 1);
      stsm4((maddr ^ ((i & 3) << 5)) + (i >> 2) * 8192, hp[0], hp[1], hp[2], hp[3]);
    };
    auto stage_x = [&](float (&x)[64], int hf) {
#pragma unroll
      for (int i = 4 * hf; i < 4 * hf + 4; i++)
        stsm4((maddr ^ ((i & 3) << 5)) + hf * 8192, pack_bf16(x[8 * i], x[8 * i + 1]), pack_bf16(x[8 * i + 2], x[8 * i + 3]),
              pack_bf16(x[8 * i + 4], x[8 * i + 5]), pack_bf16(x[8 * i + 6], x[8 * i + 7]));
      stage_publish();
    };

    float acc[128];
    const uint32_t epoch = ld_relaxed(epoch_ptr(P));
    mbar_wait_fast(sb + BAR_XIN, 0);
    SP(7);
    c.step_own<256>(acc, dstage, 0);
    mbar_wait_fast(sb + BAR_XIN + 8, 0);
    SP(8);
#pragma unroll 1
    for (int hl = 0;; hl++) {
      int t = hl & 1;
      float acc2[64];
      {
        c.step_own<256>(acc, dstage + 512, 1);
#pragma unroll
        for (int s = 0; s < 2; s++) c.step_own<128>(acc2, dstage + s * 512, s);
        c.steps<256>(acc, 2);
        float piv[2], s1[2] = {0, 0}, s2[2] = {0, 0};
#pragma unroll
        for (int s = 0; s < 2; s++) {
          const uint32_t ra = maddr + ((hl || j == 0) ? s * 8192 : (c.off << 4) - (SM_STAGE + wg * 8192));
          c.step<256>(acc);
#pragma unroll
          for (int i = 0; i < 4; i++) {
            uint32_t v[4];
            ldsm4(ra ^ (i << 5), v[0], v[1], v[2], v[3]);
            if (s + i == 0) { piv[0] = bf_lo(v[0]); piv[1] = bf_lo(v[1]); }
#pragma unroll
            for (int e = 0; e < 4; e++) {
              const float a = bf_lo(v[e]) - piv[e & 1], b = bf_hi(v[e]) - piv[e & 1];
              s1[e & 1] += a + b; s2[e & 1] += a * a; s2[e & 1] += b * b;
            }
          }
        }
        c.step<256>(acc);
        uint32_t tag;
        asm volatile("add.u32 %0, %1, 1;" : "=r"(tag) : "r"(epoch));
#pragma unroll
        for (int r = 0; r < 2; r++) {
          const float mt = piv[r] + s1[r] * (1.0f / 32);
          float m = mt + __shfl_xor_sync(0xffffffffu, mt, 1); m += __shfl_xor_sync(0xffffffffu, m, 2); m *= 0.25f;
          float q = s2[r] - s1[r] * s1[r] * (1.0f / 32) + 32.0f * (mt - m) * (mt - m);
          q += __shfl_xor_sync(0xffffffffu, q, 1); q += __shfl_xor_sync(0xffffffffu, q, 2);
          if (quad == 0) st_relaxed2(scratch<uint2>(P, g * G_BLOCK + G_STATS + (hl * 128 + warp * 16 + r * 8 + gr) * 64u + j * 8), tagf(m, tag), tagf(q, tag));
        }
        c.steps<256>(acc, 2);
        const uint2* sp = scratch<uint2>(P, g * G_BLOCK + G_STATS + (hl * 128 + warp * 16 + gr) * 64u + quad * 16);
        uint4 a = ld_relaxed4(sp), b = ld_relaxed4(sp + 64);
        c.steps<256>(acc, 2);
        uint32_t spins = 0;
        while (__any_sync(0xffffffffu, !(tag_ok4(a, tag) && tag_ok4(b, tag)))) { a = ld_relaxed4(sp); b = ld_relaxed4(sp + 64); spin_check(++spins); }
#pragma unroll
        for (int r = 0; r < 2; r++) {
          const uint4 v = r ? b : a;
          const float m0 = untag(v.x), m1 = untag(v.z);
          float m = m0 + m1; m += __shfl_xor_sync(0xffffffffu, m, 1); m += __shfl_xor_sync(0xffffffffu, m, 2); m *= 0.125f;
          float q = untag(v.y) + untag(v.w) + 128.0f * ((m0 - m) * (m0 - m) + (m1 - m) * (m1 - m));
          q += __shfl_xor_sync(0xffffffffu, q, 1); q += __shfl_xor_sync(0xffffffffu, q, 2);
          mean[r] = m; rstd[r] = rsqrtf(fmaxf(q, 0.f) * (1.0f / DM) + LN_EPS);
        }
      }
#pragma unroll 1
      for (;;) {
      const int it = (hl >> 1) * 4 + t;
#pragma unroll
      for (int s = 0; s < 4; s++) {
        uint32_t cs[16];
        c.step<256>(acc);
        if (!(s & 1)) mbar_wait_fast(sb + BAR_CSF + 4 * s, t & 1);
        if (s >= 2 && t <= 1) { cs_load(cs, 2 + s); cs_apply(acc2 + 32 * (s - 2), cs); }
        cs_load(cs, s);
        c.drain();
        cs_apply(acc + 32 * s, cs);
      }
      c.step<256>(acc);
      if (lane == 0) mbar_arrive(sb + BAR_CSE);
      c.drain();
      acc_fence<128>(acc);
      TL(wg, 1 + it * 6);
      uint32_t pkB[64];
      if (t == 2) {
#pragma unroll
        for (int i = 0; i < 64; i++) pkB[i] = pack_bf16(acc[2 * i], acc[2 * i + 1]);
        c.step<256>(acc, 0);
        stage_wait();
        glu_slice(pkB, 0);
#pragma unroll
        for (int s = 1; s < 4; s++) { c.step<256>(acc); glu_slice(pkB, s); }
      } else if (t == 0) {
        uint32_t pkA[64];
        auto kv_pack = [&](int v, int r) {
#pragma unroll
          for (int i = 32 * v + r; i < 32 * v + 32; i += 2) { acc_fence<2>(acc + 2 * i); pkA[i] = pack_bf16(acc[2 * i] * rstd[r], acc[2 * i + 1] * rstd[r]); }
        };
        uint4* const xs = ptr_add((uint4*)smem_raw, SM_STAGE + lane * 16u);
        uint4* const hp = scratch<uint4>(P, G_HALO + (((hl >> 1) * 16 + g) * 8 + j) * 4096u + lane * 16u);
        {
          uint4* const dst = (warp == 7 && g < 14) ? hp : ptr_add(xs, warp * 4096u);
#pragma unroll
          for (int s = 0; s < 2; s++) {
            c.steps<128>(acc2, s ? 2 : 1 + wg);
            if (s == 0) stage_wait();
            kv_pack(s, 1);
#pragma unroll
            for (int i = 4 * s; i < 4 * s + 4; i++) { pkA[8 * i + 1] = pkt_head(pkA[8 * i + 1]); gen_store(dst + i * 32, pkA[8 * i + 1], pkA[8 * i + 3], pkA[8 * i + 5], pkA[8 * i + 7]); }
          }
        }
        __syncwarp();
        if (lane == 0) mbar_arrive(sb + BAR_XFULL);
#pragma unroll
        for (int s = 0; s < 2; s++) {
          c.steps<128>(acc2, 2);
#pragma unroll
          for (int i = 33 - s; i < 64; i += 2) pkA[i] = movm(pkA[i]);
          kv_pack(1 - s, 0);
        }
        uint32_t kvH[32];
        {
          const uint4* const src = (warp == 0 && g >= 2) ? hp - 2 * 8 * 256 : ptr_add(xs, (warp ? warp - 1 : 0) * 4096u);
          c.steps<128>(acc2, 2);
          mbar_wait_fast(sb + BAR_XFULL, hl >> 1);
#pragma unroll
          for (int i = 0; i < 8; i++) gen_load(src + i * 32, kvH + 4 * i);
          c.steps<128>(acc2, 3 - wg);
          uint32_t spins = 0;
          while (__any_sync(0xffffffffu, !(kvH[0] && kvH[4] && kvH[8] && kvH[12] && kvH[16] && kvH[20] && kvH[24] && kvH[28]))) {
#pragma unroll
            for (int i = 0; i < 8; i++) gen_load(src + i * 32, kvH + 4 * i);
            spin_check(++spins);
          }
        }
#pragma unroll
        for (int i = 16; i < 32; i++) kvH[i] = movm(kvH[i]);
        c.steps<128>(acc2, 2);
#pragma unroll 1
        for (int i = 0; i < 3; i++) mbar_wait_fast(sb + BAR_FULL + (((c.n + i) & 7) << 3), ((c.n + i) >> 3) & 1);
        c.drain();
        acc_fence<64>(acc2);
        TL(wg, 2 + it * 6);
        uint32_t q[32];
#pragma unroll
        for (int i = 0; i < 32; i++) q[i] = pack_bf16(acc2[2 * i], acc2[2 * i + 1]);
        const uint32_t zm = bar_sync_zero(1, 256);
        uint32_t ob[4][16];
        uint4* const omail = scratch<uint4>(P, g * G_BLOCK + G_O + (hl >> 1) * 262144u + warp * 2048u + lane * 16u);
        auto o_send = [&](uint32_t (&v)[16], int hf) {
          uint4* op = ptr_add(omail, (uint32_t)(2 * j + hf) * 16384u);
#pragma unroll
          for (int i = 0; i < 4; i++) st_b128(op + i * 32, v[4 * i], v[4 * i + 1], v[4 * i + 2], v[4 * i + 3]);
        };
        auto o_fetch = [&](uint32_t (&v)[16], int s) {
          const uint4* op = ptr_add(omail, (uint32_t)o_chunk(s, j) * 16384u);
#pragma unroll
          for (int i = 0; i < 4; i++) pkt_load(op + i * 32, v + 4 * i);
        };
        {
          const uint32_t ra = maddr - (SM_STAGE + wg * 8192) + (c.off << 4);
#pragma unroll
          for (int i = 0; i < 8; i++) { uint32_t* v = ob[2 + (i >> 2)] + 4 * (i & 3); ldsm4((ra ^ ((i & 3) << 5)) + (i >> 2) * PAGE, v[0], v[1], v[2], v[3]); }
          c.prev = 64 + ((c.n & 7) << 3);
          c.advance<2>();
          const float hv = (warp == 0 && g < 2) ? -INFINITY : 0.f;
          const float hinit[4] = {hv, hv, hv, hv};
          const bool c0 = (2 * quad <= gr), c1 = (2 * quad + 1 <= gr);
          const uint32_t lm = (c0 ? 0xffffu : 0u) | (c1 ? 0xffff0000u : 0u);
          const float sc[2] = {rstd[0] * (0.17677669529663687f * LOG2E), rstd[1] * (0.17677669529663687f * LOG2E)};
          float lg[4][4], mx[4][2];
#pragma unroll
          for (int h = 0; h < 4; h++) {
            const int b = h * 4;
            float sH[4], sL[4], sU[4];
            q[2 * b] |= zm;
            mma16816(sH, q[2 * b], q[2 * b + 1], q[2 * b + 2], q[2 * b + 3], kvH[b], kvH[b + 1], hinit);
            mma16816z(sL, q[2 * b], q[2 * b + 1], q[2 * b + 2], q[2 * b + 3], pkA[2 * b], pkA[2 * b + 2]);
            mma16816z(sU, q[2 * b], q[2 * b + 1], q[2 * b + 2], q[2 * b + 3], pkA[2 * b + 1], pkA[2 * b + 3]);
            mma16816(sH, q[2 * b + 4], q[2 * b + 5], q[2 * b + 6], q[2 * b + 7], kvH[b + 2], kvH[b + 3], sH);
            mma16816(sL, q[2 * b + 4], q[2 * b + 5], q[2 * b + 6], q[2 * b + 7], pkA[2 * b + 4], pkA[2 * b + 6], sL);
            mma16816(sU, q[2 * b + 4], q[2 * b + 5], q[2 * b + 6], q[2 * b + 7], pkA[2 * b + 5], pkA[2 * b + 7], sU);
            lg[h][0] = c0 ? sL[0] : sH[0]; lg[h][1] = c1 ? sL[1] : sH[1]; lg[h][2] = c0 ? sU[2] : sL[2]; lg[h][3] = c1 ? sU[3] : sL[3];
            mx[h][0] = fmaxf(lg[h][0], lg[h][1]); mx[h][1] = fmaxf(lg[h][2], lg[h][3]);
          }
#pragma unroll
          for (int o = 1; o < 4; o <<= 1) {
#pragma unroll
            for (int i = 0; i < 8; i++) mx[i >> 1][i & 1] = fmaxf(mx[i >> 1][i & 1], __shfl_xor_sync(0xffffffffu, mx[i >> 1][i & 1], o));
          }
          uint32_t z = zm;
#pragma unroll
          for (int hf = 0; hf < 2; hf++) {
#pragma unroll
            for (int hh = 0; hh < 2; hh++) {
              const int h = hf * 2 + hh, b = h * 4;
              const uint32_t pa = pack_bf16(ex2((lg[h][0] - mx[h][0]) * sc[0]), ex2((lg[h][1] - mx[h][0]) * sc[0]));
              const uint32_t pb = pack_bf16(ex2((lg[h][2] - mx[h][1]) * sc[1]), ex2((lg[h][3] - mx[h][1]) * sc[1]));
              float sum[4];
              mma1688z(sum, pa, pb, 0x3f803f80u);
              const uint32_t p0 = pa & ~lm, p1 = pa & z, p2 = pa & lm, p3 = pb & ~lm, p4 = pb & z, p5 = pb & lm;
              const float ra = rcp(sum[0]), rb = rcp(sum[2]);
#pragma unroll
              for (int d = 0; d < 4; d++) {
                float o[4];
                mma16816z(o, p0, p1, p2, p3, kvH[16 + b + d], pkA[32 + 2 * (b + d)]);
                mma1688(o, p4, p5, pkA[32 + 2 * (b + d) + 1], o);
                ob[hf][(hh * 4 + d) * 2] = pack_bf16(o[0] * ra, o[1] * ra); ob[hf][(hh * 4 + d) * 2 + 1] = pack_bf16(o[2] * rb, o[3] * rb);
              }
            }
#pragma unroll
            for (int i = 0; i < 4; i++) ob[hf][4 * i] = pkt_head(ob[hf][4 * i]);
            if (hf == 0) { o_send(ob[0], 0); z = late_zero(zm); }
          }
#pragma unroll
          for (int i = 0; i < 32; i++) { acc2[2 * i] = bf_lo(ob[2 + (i >> 4)][i & 15]); acc2[2 * i + 1] = bf_hi(ob[2 + (i >> 4)][i & 15]); }
          acc_fence<64>(acc2);
          bar_sync(1, 256 | ((ob[1][1] | ob[1][5] | ob[1][9] | ob[1][13] | ob[1][3] | ob[1][7] | ob[1][11] | ob[1][15]) & zm));
        }
        TL(wg, 3 + it * 6);
        c.issue_rs(acc2, ob[0]);
        if (EARLY_FETCH) { o_fetch(ob[2], 2); o_fetch(ob[3], 3); }
        c.issue_rs(acc2, ob[1]);
        if (!EARLY_FETCH) { o_fetch(ob[2], 2); o_fetch(ob[3], 3); }
        c.drain();
        o_send(ob[1], 1);
#pragma unroll 1
        for (int s0 = 2;; s0 += 4) {
#pragma unroll
          for (int bb = 0; bb < 2; bb++) {
            const int s = s0 + 2 * bb, b = 2 - 2 * bb;
            uint32_t spins = 0;
            const uint32_t z = late_zero(zm);
            c.wait_full();
            while (__any_sync(0xffffffffu, ob[b][0] == z || ob[b][4] == z || ob[b][8] == z || ob[b][12] == z || ob[b + 1][0] == z || ob[b + 1][4] == z || ob[b + 1][8] == z || ob[b + 1][12] == z)) {
              o_fetch(ob[b], s); o_fetch(ob[b + 1], s + 1);
              spin_check(++spins);
            }
            if (s0 < 14) { o_fetch(ob[b ^ 2], s + 2); o_fetch(ob[b ^ 3], s + 3); }
            c.issue_rs(acc2, ob[b]);
            c.wait_full();
            c.issue_rs(acc2, ob[b + 1]);
            c.drain();
            if (s0 == 14) goto wo_done;
          }
        }
      wo_done:
        break;
      } else {
        c.steps<128>(acc2, 1 + wg);
        stage_wait();
        glu_slice_acc(acc, 0);
#pragma unroll
        for (int s = 1; s < 8; s++) { c.steps<128>(acc2, (s & 1) || t == 3 ? 2 : 1); if (s == 4) stage_publish(); glu_slice_acc(acc, s); }
        c.step<128>(acc2);
        stage_publish();
        c.steps<128>(acc2, 1 - wg);
        if (t == 3) {
          c.steps<128>(acc2, 39);
          stage_wait();
          c.drain();
          break;
        }
        c.drain();
        TL(wg, 2 + it * 6);
        c.off = 6 << 10; asm volatile("" : "+r"(c.off));
        c.step<256>(acc, 0);
        acc_fence<64>(acc2);
#pragma unroll
        for (int i = 0; i < 16; i++) { pkB[16 + i] = pack_bf16(acc2[2 * i], acc2[2 * i + 1]); pkB[48 + i] = pack_bf16(acc2[32 + 2 * i], acc2[32 + 2 * i + 1]); }
        c.steps<256>(acc, 3);
        stage_wait();
      }
      t++;
#pragma unroll
        for (int s = 4; s < 8; s++) { c.step<256>(acc); if (s == 4 && t == 3) stage_publish(); glu_slice(pkB, s); }
#pragma unroll
        for (int s = 0; s < 2; s++) {
          const uint32_t ra = maddr - (SM_STAGE + wg * 8192) + (c.off << 4);
          c.step<256>(acc);
          if (s == 0) stage_publish();
#pragma unroll
          for (int i = 0; i < 4; i++) {
            uint32_t v[4];
            ldsm4(ra ^ (i << 5), v[0], v[1], v[2], v[3]);
#pragma unroll
            for (int e = 0; e < 4; e++) { acc2[32 * s + 8 * i + 2 * e] = bf_lo(v[e]); acc2[32 * s + 8 * i + 2 * e + 1] = bf_hi(v[e]); }
          }
          acc_fence<32>(acc2 + 32 * s);
        }
        c.step<256>(acc);
      }
      const int it = (hl >> 1) * 4 + t;
      acc_fence<64>(acc2);
      TL(wg, 4 + it * 6);
      stage_x(acc2, 0);
      if (hl == 3) { stage_x(acc2, 1); TL(wg, 5 + it * 6); TLG(63); break; }
      bar_sync(2 + wg, 128);
      TL(wg, 5 + it * 6);
      c.off = 0; asm volatile("" : "+r"(c.off));
      c.step_own<256>(acc, dstage, 0);
      acc_fence<32>(acc2 + 32);
      stage_x(acc2, 1);
      bar_sync(2 + wg, 128);
    }
    }
  }
}

typedef CUresult (*EncodeFn)(CUtensorMap*, CUtensorMapDataType, cuuint32_t, void*, const cuuint64_t*, const cuuint64_t*, const cuuint32_t*,
                             const cuuint32_t*, CUtensorMapInterleave, CUtensorMapSwizzle, CUtensorMapL2promotion, CUtensorMapFloatOOBfill);

void encode(EncodeFn fn, CUtensorMap* m, const void* ptr, int rank, const cuuint64_t* dims, const cuuint64_t* strides, const cuuint32_t* box) {
  cuuint32_t es[5] = {1, 1, 1, 1, 1};
  fn(m, CU_TENSOR_MAP_DATA_TYPE_BFLOAT16, rank, const_cast<void*>(ptr), dims, strides, box, es, CU_TENSOR_MAP_INTERLEAVE_NONE,
     CU_TENSOR_MAP_SWIZZLE_128B, CU_TENSOR_MAP_L2_PROMOTION_L2_128B, CU_TENSOR_MAP_FLOAT_OOB_FILL_NONE);
}

}

extern "C" void kernel_launch(void* const* d_in, const int* in_sizes, int n_in, void* d_out, int out_size) {
  const __nv_bfloat16* x = (const __nv_bfloat16*)d_in[0];
  const __nv_bfloat16* wqkv = (const __nv_bfloat16*)d_in[1];
  const __nv_bfloat16* wo = (const __nv_bfloat16*)d_in[2];
  const __nv_bfloat16* w1 = (const __nv_bfloat16*)d_in[4];
  const __nv_bfloat16* w3 = (const __nv_bfloat16*)d_in[5];
  const __nv_bfloat16* w2 = (const __nv_bfloat16*)d_in[6];

  void* fnp = nullptr; cudaDriverEntryPointQueryResult qr;
  cudaGetDriverEntryPoint("cuTensorMapEncodeTiled", &fnp, cudaEnableDefault, &qr);
  EncodeFn fn = (EncodeFn)fnp;
  void* sym;
  cudaGetSymbolAddress(&sym, g_scratch);
  uint8_t* scr = (uint8_t*)(((uintptr_t)sym + G_BLOCK - 1) / G_BLOCK * G_BLOCK);

  Params P = {};
  { cuuint64_t d[3] = {DM, 2, SEQ / 2}, s[2] = {DM * 2, DM * 4}; cuuint32_t b[3] = {64, 1, 128}, b2[3] = {64, 1, 64};
    encode(fn, &P.map[M_XIN], x, 3, d, s, b); encode(fn, &P.map[M_XIN64], x, 3, d, s, b2);
    encode(fn, &P.map[M_OUT_LD], d_out, 3, d, s, b); encode(fn, &P.map[M_OUT_ST], d_out, 3, d, s, b2); }
  { cuuint64_t d[3] = {DM, 16, 128}, s[2] = {G_BLOCK, DM * 2}; cuuint32_t b[3] = {64, 1, 128}, b2[3] = {64, 1, 64};
    encode(fn, &P.map[M_XA_LD], scr + G_XA, 3, d, s, b); encode(fn, &P.map[M_XA_ST], scr + G_XA, 3, d, s, b2); }
  { cuuint64_t d[3] = {FF, 16, 128}, s[2] = {G_BLOCK, FF * 2}; cuuint32_t b[3] = {64, 1, 128}, b2[3] = {64, 1, 64};
    encode(fn, &P.map[M_H_LD], scr + G_H, 3, d, s, b); encode(fn, &P.map[M_H_ST], scr + G_H, 3, d, s, b2); }
  { const cuuint32_t b2[3] = {64, 64, 2}, b1[3] = {64, 64, 1};
    { cuuint64_t d[3] = {64, DM, 48}, s[2] = {3 * DM * 2, 128}; encode(fn, &P.map[M_WKV], wqkv, 3, d, s, b2); encode(fn, &P.map[M_WQ], wqkv, 3, d, s, b1); }
    { cuuint64_t d[3] = {64, DM, 16}, s[2] = {DM * 2, 128}; encode(fn, &P.map[M_WO], wo, 3, d, s, b1); }
    { cuuint64_t d[3] = {64, FF, 16}, s[2] = {DM * 2, 128}; encode(fn, &P.map[M_W2], w2, 3, d, s, b1); }
    { cuuint64_t d[3] = {64, DM, FF / 64}, s[2] = {FF * 2, 128};
      encode(fn, &P.map[M_W1], w1, 3, d, s, b2); encode(fn, &P.map[M_W3], w3, 3, d, s, b2);
      encode(fn, &P.map[M_W1H], w1, 3, d, s, b1); encode(fn, &P.map[M_W3H], w3, 3, d, s, b1); }
  }
  P.scratch = scr; P.wqkv = wqkv; P.wo = wo; P.w2 = w2;
  int dev = 0, sms = 0;
  cudaGetDevice(&dev);
  cudaDeviceGetAttribute(&sms, cudaDevAttrMultiProcessorCount, dev);
  P.use_smid = (sms == 132);
  cudaFuncSetAttribute(fused_kernel, cudaFuncAttributeMaxDynamicSharedMemorySize, SM_ALLOC);
  fused_kernel<<<132, 384, SM_ALLOC>>>(P);
}
```

```cpp
#include <cuda_runtime.h>
#include <cuda_bf16.h>
#include <cuda.h>
#include <stdint.h>
#include <math.h>

namespace {

constexpr int SEQ = 2048, DM = 1024, FF = 3584;
constexpr float LN_EPS = 1e-5f;
constexpr float LOG2E = 1.4426950408889634f;

constexpr uint32_t G_BLOCK = 2u << 20;
constexpr uint32_t G_H = 0;
constexpr uint32_t G_XA = G_H + 128 * FF * 2;
constexpr uint32_t G_O = G_XA + 128 * DM * 2;
constexpr uint32_t G_STATS = G_O + 2 * 128 * DM * 2;
constexpr uint32_t G_FLAGS = G_STATS + 4 * 128 * 64;
static_assert(G_FLAGS + 2048 <= G_BLOCK, "");
constexpr uint32_t G_HALO = 16 * G_BLOCK;
constexpr uint32_t G_CS = G_HALO + 2 * 16 * 8 * 4096;
constexpr uint32_t G_EPOCH = G_CS + (3 * DM + 2 * FF) * 16;
__device__ __align__(1024) uint8_t g_scratch[18 * G_BLOCK];

enum { M_XIN, M_XIN64, M_XA_LD, M_XA_ST, M_H_LD, M_H_ST, M_OUT_LD, M_OUT_ST, M_WKV, M_WQ, M_WO, M_W1, M_W3, M_W1H, M_W3H, M_W2, M_COUNT };
struct alignas(64) Params {
  CUtensorMap map[M_COUNT];
  uint8_t* scratch;
  const __nv_bfloat16* x;
  const __nv_bfloat16* wqkv;
  const __nv_bfloat16* wo;
  const __nv_bfloat16* w2;
  int use_smid;
};

constexpr uint32_t PAGE = 16384, NPAGE = 12;
constexpr uint32_t SM_STAGE = NPAGE * PAGE;
constexpr uint32_t SM_BAR = SM_STAGE + 2 * PAGE;
constexpr uint32_t SM_CS = SM_BAR + 256;
constexpr uint32_t SM_TOTAL = SM_CS + 1536;
constexpr uint32_t SM_ALLOC = SM_TOTAL;
static_assert(SM_ALLOC <= 232448, "shared memory");
constexpr uint32_t BAR_FULL = SM_BAR, BAR_EMPTY = SM_BAR + 64, BAR_SFULL = SM_BAR + 128;
constexpr uint32_t BAR_XFULL = SM_BAR + 160, BAR_CSE = SM_BAR + 168;
constexpr uint32_t BAR_SEMPTY = SM_BAR + 176, BAR_CSF = SM_BAR + 184, BAR_XIN = SM_BAR + 200;
constexpr uint32_t BAR_TAG = SM_BAR + 216, SM_ROLE = SM_BAR + 224, SM_TAG = SM_BAR + 228, SM_SEEN = SM_BAR + 232;
enum { EV_XA, EV_XA2, EV_H0, EV_H3, EV_H1, EV_H2, EV_XB, EV_XB2, EV_N };

#define WO_HOLD 4
struct Sched { uint32_t pat[14]; uint32_t page0[14]; bool ok; };
constexpr int seg_steps(int seg) { return seg == 0 || seg == 3 ? 18 : seg == 1 || seg == 4 ? 14 : seg == 2 ? 9 : seg == 5 ? 32 : 56; }
constexpr int step_pages(int seg, int i) {
  return seg == 0 || seg == 3 ? (i < 2 ? 2 : i < 4 ? 1 : 3) : seg == 5 ? 3 : 2;
}
constexpr Sched make_sched() {
  Sched s = {};
  int owner[NPAGE] = {-1, -1, -1, -1, -1, -1, -1, -1, -1, -1, -1, -1};
  int n = 0, tail = 0, page = 0;
  s.ok = true;
  for (int sg = 0; sg < 14; sg++) {
    const int seg = sg % 7;
    if (seg == 5) page = (page + 2) / 3 * 3 % NPAGE;
    if (seg == 0 || seg == 3) page = (page + 5) / 6 * 6 % NPAGE;
    s.page0[sg] = page;
    for (int i = 0; i < seg_steps(seg); i++) {
      const int p = step_pages(seg, i);
      if (page + p > (int)NPAGE) { s.ok = false; return s; }
      int need = n - 8;
      for (int q = 0; q < p; q++) { if (owner[page + q] > need) need = owner[page + q]; owner[page + q] = n; }
      if (seg == 3 && i < 4 && need < n - i - WO_HOLD + (i > 2 ? 2 : i)) need = n - i - WO_HOLD + (i > 2 ? 2 : i);
      int nw = need + 1 - tail; if (nw < 0) nw = 0;
      tail += nw;
      if (i < 16) s.pat[sg] |= (uint32_t)nw << (2 * i); else if (nw != 1) s.ok = false;
      if (nw > 3) s.ok = false;
      page = (page + p) % NPAGE; n++;
    }
  }
  for (int sg = 0; sg < 7; sg++) if (s.page0[sg] != s.page0[sg + 7] || (sg && s.pat[sg] != s.pat[sg + 7])) s.ok = false;
  return s;
}
constexpr Sched SCHED = make_sched();
static_assert(SCHED.ok && SCHED.page0[0] == 0 && SCHED.page0[3] == 0 && SCHED.page0[5] == 6 && (SCHED.pat[0] & 0xfff) == 0, "ring schedule");
template <int SEG> struct Pat { static constexpr uint32_t v = SCHED.pat[SEG]; };

__device__ __forceinline__ uint32_t smem_u32(const void* p) { return (uint32_t)__cvta_generic_to_shared(p); }
__device__ __forceinline__ void mbar_init(uint32_t bar, uint32_t cnt) { asm volatile("mbarrier.init.shared::cta.b64 [%0], %1;" :: "r"(bar), "r"(cnt)); }
__device__ __forceinline__ void mbar_expect_tx(uint32_t bar, uint32_t bytes) { asm volatile("mbarrier.arrive.expect_tx.shared::cta.b64 _, [%0], %1;" :: "r"(bar), "r"(bytes) : "memory"); }
__device__ __forceinline__ void mbar_arrive(uint32_t bar) { asm volatile("mbarrier.arrive.shared::cta.b64 _, [%0];" :: "r"(bar) : "memory"); }
__device__ __forceinline__ void mbar_wait(uint32_t bar, uint32_t parity) {
  asm volatile("{\n.reg .pred p;\n.reg .u32 n;\nmov.u32 n, 0;\nLAB_WAIT:\n"
               "mbarrier.try_wait.parity.shared::cta.b64 p, [%0], %1;\n@p bra LAB_DONE;\n"
               "add.u32 n, n, 1;\nsetp.lt.u32 p, n, 4194304;\n@p bra LAB_WAIT;\ntrap;\nLAB_DONE:\n}" :: "r"(bar), "r"(parity) : "memory");
}
__device__ __forceinline__ void mbar_wait_fast(uint32_t bar, uint32_t parity) {
  asm volatile("{\n.reg .pred p;\nLAB_WAIT:\nmbarrier.try_wait.parity.shared::cta.b64 p, [%0], %1;\n@!p bra LAB_WAIT;\n}" :: "r"(bar), "r"(parity) : "memory");
}
__device__ __forceinline__ void spin_check(uint32_t n) { asm volatile("{\n.reg .pred p;\nsetp.ge.u32 p, %0, 4194304;\n@p st.volatile.global.u32 [%1], %0;\n}" :: "r"(n), "l"(0ull)); }
__device__ __forceinline__ void tma_ld3(uint32_t dst, const CUtensorMap* m, uint32_t bar, int c0, int c1, int c2) {
  asm volatile("cp.async.bulk.tensor.3d.shared::cluster.global.mbarrier::complete_tx::bytes [%0], [%1, {%3, %4, %5}], [%2];" :: "r"(dst), "l"(m), "r"(bar), "r"(c0), "r"(c1), "r"(c2) : "memory");
}
__device__ __forceinline__ void tma_ld3_mc(uint32_t dst, const CUtensorMap* m, uint32_t bar, int c0, int c1, int c2, uint16_t mask) {
  asm volatile("cp.async.bulk.tensor.3d.shared::cluster.global.mbarrier::complete_tx::bytes.multicast::cluster [%0], [%1, {%3, %4, %5}], [%2], %6;"
               :: "r"(dst), "l"(m), "r"(bar), "r"(c0), "r"(c1), "r"(c2), "h"(mask) : "memory");
}
__device__ __forceinline__ uint32_t mapa(uint32_t addr, uint32_t cta) { uint32_t r; asm("mapa.shared::cluster.u32 %0, %1, %2;" : "=r"(r) : "r"(addr), "r"(cta)); return r; }
__device__ __forceinline__ void mbar_arrive_cluster(uint32_t bar) { asm volatile("mbarrier.arrive.shared::cluster.b64 _, [%0];" :: "r"(bar) : "memory"); }
__device__ __forceinline__ void tma_st3(const CUtensorMap* m, uint32_t src, int c0, int c1, int c2) {
  asm volatile("cp.async.bulk.tensor.3d.global.shared::cta.bulk_group [%0, {%2, %3, %4}], [%1];" :: "l"(m), "r"(src), "r"(c0), "r"(c1), "r"(c2) : "memory");
}
__device__ __forceinline__ void bulk_commit() { asm volatile("cp.async.bulk.commit_group;" ::: "memory"); }
template <int N> __device__ __forceinline__ void bulk_wait() { asm volatile("cp.async.bulk.wait_group %0;" :: "n"(N) : "memory"); }
__device__ __forceinline__ void fence_async_smem() { asm volatile("fence.proxy.async.shared::cta;" ::: "memory"); }
__device__ __forceinline__ void fence_async_global() { asm volatile("fence.proxy.async.global;" ::: "memory"); }
__device__ __forceinline__ bool elect_one() { uint32_t p; asm volatile("{\n.reg .pred P;\nelect.sync _|P, 0xffffffff;\nselp.u32 %0, 1, 0, P;\n}" : "=r"(p)); return p; }
__device__ __forceinline__ void prefetch_map(const CUtensorMap* m) { asm volatile("prefetch.tensormap [%0];" :: "l"(m) : "memory"); }
__device__ __forceinline__ void prefetch_l2(const void* p, uint32_t bytes) { asm volatile("cp.async.bulk.prefetch.L2.global [%0], %1;" :: "l"(p), "r"(bytes) : "memory"); }
__device__ __forceinline__ void wgmma_fence() { asm volatile("wgmma.fence.sync.aligned;" ::: "memory"); }
__device__ __forceinline__ void wgmma_commit() { asm volatile("wgmma.commit_group.sync.aligned;" ::: "memory"); }
template <int N> __device__ __forceinline__ void wgmma_wait() { asm volatile("wgmma.wait_group.sync.aligned %0;" :: "n"(N) : "memory"); }
__device__ __forceinline__ uint32_t desc_lo(uint32_t addr, uint32_t lbo) { return ((addr & 0x3FFFF) >> 4) | ((lbo >> 4) << 16); }
__device__ __forceinline__ uint64_t desc64(uint32_t lo) { uint64_t r; asm("mov.b64 %0, {%1, %2};" : "=l"(r) : "r"(lo), "r"(0x40000040u)); return r; }
__device__ __forceinline__ void bar_sync(int id, int n) { asm volatile("bar.sync %0, %1;" :: "r"(id), "r"(n) : "memory"); }
__device__ __forceinline__ uint32_t pack_bf16(float lo, float hi) { uint32_t r; asm("cvt.rn.bf16x2.f32 %0, %1, %2;" : "=r"(r) : "f"(hi), "f"(lo)); return r; }
__device__ __forceinline__ float bf_lo(uint32_t v) { return __uint_as_float(v << 16); }
__device__ __forceinline__ float bf_hi(uint32_t v) { return __uint_as_float(v & 0xffff0000u); }
__device__ __forceinline__ float ex2(float x) { float r; asm("ex2.approx.ftz.f32 %0, %1;" : "=f"(r) : "f"(x)); return r; }
__device__ __forceinline__ float rcp(float x) { float r; asm("rcp.approx.ftz.f32 %0, %1;" : "=f"(r) : "f"(x)); return r; }
__device__ __forceinline__ void stsm4(uint32_t a, uint32_t r0, uint32_t r1, uint32_t r2, uint32_t r3) {
  asm volatile("stmatrix.sync.aligned.m8n8.x4.shared.b16 [%0], {%1, %2, %3, %4};" :: "r"(a), "r"(r0), "r"(r1), "r"(r2), "r"(r3) : "memory");
}
__device__ __forceinline__ void ldsm4(uint32_t a, uint32_t& r0, uint32_t& r1, uint32_t& r2, uint32_t& r3) {
  asm volatile("ldmatrix.sync.aligned.m8n8.x4.shared.b16 {%0, %1, %2, %3}, [%4];" : "=r"(r0), "=r"(r1), "=r"(r2), "=r"(r3) : "r"(a) : "memory");
}
__device__ __forceinline__ uint32_t movm(uint32_t v) { uint32_t r; asm volatile("movmatrix.sync.aligned.m8n8.trans.b16 %0, %1;" : "=r"(r) : "r"(v)); return r; }
__device__ __forceinline__ void sts128(uint32_t a, uint32_t r0, uint32_t r1, uint32_t r2, uint32_t r3) {
  asm volatile("st.shared.v4.b32 [%0], {%1, %2, %3, %4};" :: "r"(a), "r"(r0), "r"(r1), "r"(r2), "r"(r3) : "memory");
}
__device__ __forceinline__ void lds128(uint32_t a, uint32_t& r0, uint32_t& r1, uint32_t& r2, uint32_t& r3) {
  asm volatile("ld.shared.v4.b32 {%0, %1, %2, %3}, [%4];" : "=r"(r0), "=r"(r1), "=r"(r2), "=r"(r3) : "r"(a) : "memory");
}
__device__ __forceinline__ void sts32f(uint32_t a, float v) { asm volatile("st.shared.f32 [%0], %1;" :: "r"(a), "f"(v) : "memory"); }
__device__ __forceinline__ void mma16816(float (&d)[4], uint32_t a0, uint32_t a1, uint32_t a2, uint32_t a3, uint32_t b0, uint32_t b1, const float (&c)[4]) {
  asm("mma.sync.aligned.m16n8k16.row.col.f32.bf16.bf16.f32 {%0, %1, %2, %3}, {%4, %5, %6, %7}, {%8, %9}, {%10, %11, %12, %13};"
      : "=f"(d[0]), "=f"(d[1]), "=f"(d[2]), "=f"(d[3]) : "r"(a0), "r"(a1), "r"(a2), "r"(a3), "r"(b0), "r"(b1), "f"(c[0]), "f"(c[1]), "f"(c[2]), "f"(c[3]));
}
__device__ __forceinline__ void mma1688(float (&d)[4], uint32_t a0, uint32_t a1, uint32_t b0, const float (&c)[4]) {
  asm("mma.sync.aligned.m16n8k8.row.col.f32.bf16.bf16.f32 {%0, %1, %2, %3}, {%4, %5}, {%6}, {%7, %8, %9, %10};"
      : "=f"(d[0]), "=f"(d[1]), "=f"(d[2]), "=f"(d[3]) : "r"(a0), "r"(a1), "r"(b0), "f"(c[0]), "f"(c[1]), "f"(c[2]), "f"(c[3]));
}
__device__ __forceinline__ void mma16816z(float (&d)[4], uint32_t a0, uint32_t a1, uint32_t a2, uint32_t a3, uint32_t b0, uint32_t b1) {
  asm("mma.sync.aligned.m16n8k16.row.col.f32.bf16.bf16.f32 {%0, %1, %2, %3}, {%4, %5, %6, %7}, {%8, %9}, {0f00000000, 0f00000000, 0f00000000, 0f00000000};"
      : "=f"(d[0]), "=f"(d[1]), "=f"(d[2]), "=f"(d[3]) : "r"(a0), "r"(a1), "r"(a2), "r"(a3), "r"(b0), "r"(b1));
}
__device__ __forceinline__ void mma1688z(float (&d)[4], uint32_t a0, uint32_t a1, uint32_t b0) {
  asm("mma.sync.aligned.m16n8k8.row.col.f32.bf16.bf16.f32 {%0, %1, %2, %3}, {%4, %5}, {%6}, {0f00000000, 0f00000000, 0f00000000, 0f00000000};"
      : "=f"(d[0]), "=f"(d[1]), "=f"(d[2]), "=f"(d[3]) : "r"(a0), "r"(a1), "r"(b0));
}
__device__ __forceinline__ uint32_t bar_sync_zero(int id, int n) {
  uint32_t r;
  asm volatile("{\n.reg .pred p;\nsetp.eq.u32 p, %1, 0;\nbarrier.cta.red.popc.aligned.u32 %0, %1, %2, p;\n}" : "=r"(r) : "r"(id), "r"(n) : "memory");
  return r;
}
__device__ __forceinline__ uint32_t late_zero(uint32_t zm) { uint32_t c; asm volatile("mov.u32 %0, %%clock;" : "=r"(c) :: "memory"); return c & zm; }
#define WO_ORDER 1
#define EARLY_PF 1
#define CS_START 8
__device__ __forceinline__ void st_b128(uint4* p, uint32_t a, uint32_t b, uint32_t c, uint32_t d) {
  asm volatile("{\n.reg .b128 t;\n.reg .b64 lo, hi;\nmov.b64 lo, {%0, %1};\nmov.b64 hi, {%2, %3};\nmov.b128 t, {lo, hi};\nst.relaxed.gpu.global.b128 [%4], t;\n}"
               :: "r"(a), "r"(b), "r"(c), "r"(d), "l"(p) : "memory");
}
__device__ __forceinline__ uint32_t pkt_head(uint32_t a) { return a ? a : 0x8000u; }
__device__ __forceinline__ void gen_store(uint4* p, uint32_t a, uint32_t b, uint32_t c, uint32_t d) {
  asm volatile("{\n.reg .b128 t;\n.reg .b64 lo, hi;\nmov.b64 lo, {%0, %1};\nmov.b64 hi, {%2, %3};\nmov.b128 t, {lo, hi};\nst.relaxed.gpu.b128 [%4], t;\n}"
               :: "r"(a), "r"(b), "r"(c), "r"(d), "l"(p) : "memory");
}
__device__ __forceinline__ void gen_load(const uint4* p, uint32_t* v) {
  asm volatile("{\n.reg .b128 t;\n.reg .b64 lo, hi;\nld.relaxed.gpu.b128 t, [%4];\nmov.b128 {lo, hi}, t;\nmov.b64 {%0, %1}, lo;\nmov.b64 {%2, %3}, hi;\n}"
               : "=r"(v[0]), "=r"(v[1]), "=r"(v[2]), "=r"(v[3]) : "l"(p) : "memory");
}
__device__ __forceinline__ void pkt_load(const uint4* p, uint32_t* v) {
  asm volatile("{\n.reg .b128 t;\n.reg .b64 lo, hi;\nld.relaxed.gpu.global.b128 t, [%4];\nmov.b128 {lo, hi}, t;\nmov.b64 {%0, %1}, lo;\nmov.b64 {%2, %3}, hi;\n}"
               : "=r"(v[0]), "=r"(v[1]), "=r"(v[2]), "=r"(v[3]) : "l"(p) : "memory");
}
__device__ __forceinline__ uint32_t ld_relaxed(const uint32_t* p) { uint32_t v; asm volatile("ld.relaxed.gpu.global.u32 %0, [%1];" : "=r"(v) : "l"(p) : "memory"); return v; }
__device__ __forceinline__ uint4 ld_relaxed4(const void* p) { uint4 v; asm volatile("ld.relaxed.gpu.global.v4.u32 {%0, %1, %2, %3}, [%4];" : "=r"(v.x), "=r"(v.y), "=r"(v.z), "=r"(v.w) : "l"(p) : "memory"); return v; }
__device__ __forceinline__ void st_relaxed(uint32_t* p, uint32_t v) { asm volatile("st.relaxed.gpu.global.u32 [%0], %1;" :: "l"(p), "r"(v) : "memory"); }
__device__ __forceinline__ void st_relaxed2(void* p, uint32_t a, uint32_t b) { asm volatile("st.relaxed.gpu.global.v2.u32 [%0], {%1, %2};" :: "l"(p), "r"(a), "r"(b) : "memory"); }
__device__ __forceinline__ void red_release(uint32_t* p, uint32_t v) { asm volatile("red.release.gpu.global.add.u32 [%0], %1;" :: "l"(p), "r"(v) : "memory"); }
__device__ __forceinline__ uint32_t tagf(float v, uint32_t tag) { return (__float_as_uint(v) & ~15u) | (tag & 15u); }
__device__ __forceinline__ bool tag_ok4(const uint4& v, uint32_t tag) { return (((v.x ^ tag) | (v.y ^ tag) | (v.z ^ tag) | (v.w ^ tag)) & 15u) == 0; }
__device__ __forceinline__ float untag(uint32_t v) { return __uint_as_float(v & ~15u); }
template <typename T> __device__ __forceinline__ T* ptr_add(T* p, uint32_t bytes) {
  uint64_t r;
  asm("{\n.reg .u32 lo, hi;\nmov.b64 {lo, hi}, %1;\nadd.cc.u32 lo, lo, %2;\naddc.u32 hi, hi, 0;\nmov.b64 %0, {lo, hi};\n}" : "=l"(r) : "l"(p), "r"(bytes));
  return (T*)r;
}
#define TL(who, slot) do {} while (0)
#define TLC(slot) do {} while (0)
#define ST(who, n) do {} while (0)
#define AP(i) do {} while (0)
#define SP(v) do {} while (0)
#define TLG(slot) do {} while (0)
#define STA() do {} while (0)
#define STB(n) do {} while (0)

__device__ __forceinline__ void wgmma_n128(float (&d)[64], uint64_t da, uint64_t db, int scale_d) {
  asm volatile("{\n.reg .pred p;\nsetp.ne.b32 p, %66, 0;\n"
    "wgmma.mma_async.sync.aligned.m64n128k16.f32.bf16.bf16 "
    "{%0, %1, %2, %3, %4, %5, %6, %7, %8, %9, %10, %11, %12, %13, %14, %15, "
    "%16, %17, %18, %19, %20, %21, %22, %23, %24, %25, %26, %27, %28, %29, %30, %31, "
    "%32, %33, %34, %35, %36, %37, %38, %39, %40, %41, %42, %43, %44, %45, %46, %47, "
    "%48, %49, %50, %51, %52, %53, %54, %55, %56, %57, %58, %59, %60, %61, %62, %63}, "
    "%64, %65, p, 1, 1, 0, 1;\n}\n"
    : "+f"(d[0]), "+f"(d[1]), "+f"(d[2]), "+f"(d[3]), "+f"(d[4]), "+f"(d[5]), "+f"(d[6]), "+f"(d[7]),
      "+f"(d[8]), "+f"(d[9]), "+f"(d[10]), "+f"(d[11]), "+f"(d[12]), "+f"(d[13]), "+f"(d[14]), "+f"(d[15]),
      "+f"(d[16]), "+f"(d[17]), "+f"(d[18]), "+f"(d[19]), "+f"(d[20]), "+f"(d[21]), "+f"(d[22]), "+f"(d[23]),
      "+f"(d[24]), "+f"(d[25]), "+f"(d[26]), "+f"(d[27]), "+f"(d[28]), "+f"(d[29]), "+f"(d[30]), "+f"(d[31]),
      "+f"(d[32]), "+f"(d[33]), "+f"(d[34]), "+f"(d[35]), "+f"(d[36]), "+f"(d[37]), "+f"(d[38]), "+f"(d[39]),
      "+f"(d[40]), "+f"(d[41]), "+f"(d[42]), "+f"(d[43]), "+f"(d[44]), "+f"(d[45]), "+f"(d[46]), "+f"(d[47]),
      "+f"(d[48]), "+f"(d[49]), "+f"(d[50]), "+f"(d[51]), "+f"(d[52]), "+f"(d[53]), "+f"(d[54]), "+f"(d[55]),
      "+f"(d[56]), "+f"(d[57]), "+f"(d[58]), "+f"(d[59]), "+f"(d[60]), "+f"(d[61]), "+f"(d[62]), "+f"(d[63])
    : "l"(da), "l"(db), "r"(scale_d));
}
__device__ __forceinline__ void wgmma_n256(float (&d)[128], uint64_t da, uint64_t db, int scale_d) {
  asm volatile("{\n.reg .pred p;\nsetp.ne.b32 p, %130, 0;\n"
    "wgmma.mma_async.sync.aligned.m64n256k16.f32.bf16.bf16 "
    "{%0, %1, %2, %3, %4, %5, %6, %7, %8, %9, %10, %11, %12, %13, %14, %15, "
    "%16, %17, %18, %19, %20, %21, %22, %23, %24, %25, %26, %27, %28, %29, %30, %31, "
    "%32, %33, %34, %35, %36, %37, %38, %39, %40, %41, %42, %43, %44, %45, %46, %47, "
    "%48, %49, %50, %51, %52, %53, %54, %55, %56, %57, %58, %59, %60, %61, %62, %63, "
    "%64, %65, %66, %67, %68, %69, %70, %71, %72, %73, %74, %75, %76, %77, %78, %79, "
    "%80, %81, %82, %83, %84, %85, %86, %87, %88, %89, %90, %91, %92, %93, %94, %95, "
    "%96, %97, %98, %99, %100, %101, %102, %103, %104, %105, %106, %107, %108, %109, %110, %111, "
    "%112, %113, %114, %115, %116, %117, %118, %119, %120, %121, %122, %123, %124, %125, %126, %127}, "
    "%128, %129, p, 1, 1, 0, 1;\n}\n"
    : "+f"(d[0]), "+f"(d[1]), "+f"(d[2]), "+f"(d[3]), "+f"(d[4]), "+f"(d[5]), "+f"(d[6]), "+f"(d[7]),
      "+f"(d[8]), "+f"(d[9]), "+f"(d[10]), "+f"(d[11]), "+f"(d[12]), "+f"(d[13]), "+f"(d[14]), "+f"(d[15]),
      "+f"(d[16]), "+f"(d[17]), "+f"(d[18]), "+f"(d[19]), "+f"(d[20]), "+f"(d[21]), "+f"(d[22]), "+f"(d[23]),
      "+f"(d[24]), "+f"(d[25]), "+f"(d[26]), "+f"(d[27]), "+f"(d[28]), "+f"(d[29]), "+f"(d[30]), "+f"(d[31]),
      "+f"(d[32]), "+f"(d[33]), "+f"(d[34]), "+f"(d[35]), "+f"(d[36]), "+f"(d[37]), "+f"(d[38]), "+f"(d[39]),
      "+f"(d[40]), "+f"(d[41]), "+f"(d[42]), "+f"(d[43]), "+f"(d[44]), "+f"(d[45]), "+f"(d[46]), "+f"(d[47]),
      "+f"(d[48]), "+f"(d[49]), "+f"(d[50]), "+f"(d[51]), "+f"(d[52]), "+f"(d[53]), "+f"(d[54]), "+f"(d[55]),
      "+f"(d[56]), "+f"(d[57]), "+f"(d[58]), "+f"(d[59]), "+f"(d[60]), "+f"(d[61]), "+f"(d[62]), "+f"(d[63]),
      "+f"(d[64]), "+f"(d[65]), "+f"(d[66]), "+f"(d[67]), "+f"(d[68]), "+f"(d[69]), "+f"(d[70]), "+f"(d[71]),
      "+f"(d[72]), "+f"(d[73]), "+f"(d[74]), "+f"(d[75]), "+f"(d[76]), "+f"(d[77]), "+f"(d[78]), "+f"(d[79]),
      "+f"(d[80]), "+f"(d[81]), "+f"(d[82]), "+f"(d[83]), "+f"(d[84]), "+f"(d[85]), "+f"(d[86]), "+f"(d[87]),
      "+f"(d[88]), "+f"(d[89]), "+f"(d[90]), "+f"(d[91]), "+f"(d[92]), "+f"(d[93]), "+f"(d[94]), "+f"(d[95]),
      "+f"(d[96]), "+f"(d[97]), "+f"(d[98]), "+f"(d[99]), "+f"(d[100]), "+f"(d[101]), "+f"(d[102]), "+f"(d[103]),
      "+f"(d[104]), "+f"(d[105]), "+f"(d[106]), "+f"(d[107]), "+f"(d[108]), "+f"(d[109]), "+f"(d[110]), "+f"(d[111]),
      "+f"(d[112]), "+f"(d[113]), "+f"(d[114]), "+f"(d[115]), "+f"(d[116]), "+f"(d[117]), "+f"(d[118]), "+f"(d[119]),
      "+f"(d[120]), "+f"(d[121]), "+f"(d[122]), "+f"(d[123]), "+f"(d[124]), "+f"(d[125]), "+f"(d[126]), "+f"(d[127])
    : "l"(da), "l"(db), "r"(scale_d));
}
__device__ __forceinline__ void wgmma_rs_n128(float (&d)[64], const uint32_t* a, uint64_t db, int scale_d) {
  asm volatile("{\n.reg .pred p;\nsetp.ne.b32 p, %69, 0;\n"
    "wgmma.mma_async.sync.aligned.m64n128k16.f32.bf16.bf16 "
    "{%0, %1, %2, %3, %4, %5, %6, %7, %8, %9, %10, %11, %12, %13, %14, %15, "
    "%16, %17, %18, %19, %20, %21, %22, %23, %24, %25, %26, %27, %28, %29, %30, %31, "
    "%32, %33, %34, %35, %36, %37, %38, %39, %40, %41, %42, %43, %44, %45, %46, %47, "
    "%48, %49, %50, %51, %52, %53, %54, %55, %56, %57, %58, %59, %60, %61, %62, %63}, "
    "{%64, %65, %66, %67}, %68, p, 1, 1, 1;\n}\n"
    : "+f"(d[0]), "+f"(d[1]), "+f"(d[2]), "+f"(d[3]), "+f"(d[4]), "+f"(d[5]), "+f"(d[6]), "+f"(d[7]),
      "+f"(d[8]), "+f"(d[9]), "+f"(d[10]), "+f"(d[11]), "+f"(d[12]), "+f"(d[13]), "+f"(d[14]), "+f"(d[15]),
      "+f"(d[16]), "+f"(d[17]), "+f"(d[18]), "+f"(d[19]), "+f"(d[20]), "+f"(d[21]), "+f"(d[22]), "+f"(d[23]),
      "+f"(d[24]), "+f"(d[25]), "+f"(d[26]), "+f"(d[27]), "+f"(d[28]), "+f"(d[29]), "+f"(d[30]), "+f"(d[31]),
      "+f"(d[32]), "+f"(d[33]), "+f"(d[34]), "+f"(d[35]), "+f"(d[36]), "+f"(d[37]), "+f"(d[38]), "+f"(d[39]),
      "+f"(d[40]), "+f"(d[41]), "+f"(d[42]), "+f"(d[43]), "+f"(d[44]), "+f"(d[45]), "+f"(d[46]), "+f"(d[47]),
      "+f"(d[48]), "+f"(d[49]), "+f"(d[50]), "+f"(d[51]), "+f"(d[52]), "+f"(d[53]), "+f"(d[54]), "+f"(d[55]),
      "+f"(d[56]), "+f"(d[57]), "+f"(d[58]), "+f"(d[59]), "+f"(d[60]), "+f"(d[61]), "+f"(d[62]), "+f"(d[63])
    : "r"(a[0]), "r"(a[1]), "r"(a[2]), "r"(a[3]), "l"(db), "r"(scale_d));
}

template <int BN> __device__ __forceinline__ void wgmma(float (&d)[BN / 2], uint64_t a, uint64_t b, int s) {
  if constexpr (BN == 128) wgmma_n128(d, a, b, s);
  else wgmma_n256(d, a, b, s);
}

template <int N> __device__ __forceinline__ void acc_fence(float* a) {
#pragma unroll
  for (int i = 0; i < N; i++) asm volatile("" : "+f"(a[i]) :: "memory");
}

#define SELECT8(a, f) do { \
  if ((a) & 4) { if ((a) & 2) { if ((a) & 1) f(7); else f(6); } else { if ((a) & 1) f(5); else f(4); } } \
  else { if ((a) & 2) { if ((a) & 1) f(3); else f(2); } else { if ((a) & 1) f(1); else f(0); } } } while (0)
__device__ __forceinline__ uint32_t lane_now() { uint32_t l; asm volatile("mov.u32 %0, %%laneid;" : "=r"(l)); return l; }

struct Prod {
  uint32_t sb, n, tail, addr, pat, ready;
  uint32_t rank, flip; uint16_t mask;
  __device__ __forceinline__ void load_b(uint32_t dst, uint32_t half, const CUtensorMap* m, uint32_t mstep, uint32_t fb, int k, int ch, int cstep) {
    uint32_t h = rank;
    do { tma_ld3_mc(dst + h * half, ptr_add(m, h * mstep), fb, 0, k * 64, ch + h * cstep, mask); h ^= flip; } while (h != rank);
  }
  __device__ __forceinline__ void load_wide(const Params& P, int ffn, uint32_t dst, uint32_t fb, int k, int ch) {
    load_b(dst, PAGE, &P.map[ffn ? M_W1 : M_WKV], ffn ? 128 : 0, fb, k, ffn ? ch : ch + 16, ffn ? 0 : 16);
  }
  __device__ __forceinline__ void load_narrow(const Params& P, int ffn, uint32_t dst, uint32_t fb, int k, int j) {
    load_b(dst, 8192, &P.map[ffn ? M_W1H : M_WQ], ffn ? 128 : 0, fb, k, ffn ? 48 + j : 2 * j, ffn ? 0 : 1);
  }
  __device__ __forceinline__ void finish() {
#pragma unroll 1
    for (; tail < n; tail++) mbar_wait(sb + BAR_EMPTY + ((tail & 7) << 3), (tail >> 3) & 1);
  }
  template <int PAGES> __device__ __forceinline__ uint32_t acquire(uint32_t& fb) {
    uint32_t nw = pat & 3; pat = (pat >> 2) | 0x40000000u;
#pragma unroll 1
    for (; nw; nw--) { mbar_wait(sb + BAR_EMPTY + ((tail & 7) << 3), (tail >> 3) & 1); tail++; }
    ST(4, n);
    fb = sb + BAR_FULL + ((n & 7) << 3);
    mbar_expect_tx(fb, PAGES * PAGE);
    const uint32_t a = sb + addr;
    addr += PAGES * PAGE; if (addr >= NPAGE * PAGE) addr = 0;
    n++;
    return a;
  }
  const uint32_t* flag; uint32_t base, seen;
  __device__ __forceinline__ void acquire_fence() { asm volatile("fence.acquire.gpu;" ::: "memory"); fence_async_global(); }
  __device__ __forceinline__ void next() {
    uint32_t v, spins = 0;
    seen++;
    do { asm volatile("ld.acquire.cta.shared.u32 %0, [%1];" : "=r"(v) : "r"(sb + SM_SEEN) : "memory"); spin_check(++spins >> 4); } while (v < seen);
    fence_async_global();
  }
  __device__ __forceinline__ void need(uint32_t mask) {
    if ((ready & mask) != mask) {
      uint32_t spins = 0;
      do { ready = ld_relaxed(flag) - base; spin_check(++spins); } while ((ready & mask) != mask);
      acquire_fence();
    }
    ST(5, n - 1);
  }
};

struct Cons {
  uint32_t sb, n, off, prev;
  uint32_t ebar;
  uint32_t da0, db0;
  int lane;
  template <int PAGES> __device__ __forceinline__ void advance() {
    n++; off += PAGES << 10; if (off >= (NPAGE << 10)) off = 0;
    asm volatile("" : "+r"(n), "+r"(off));
  }
  template <int BN, int PAGES> __device__ __forceinline__ void step_ab(float (&acc)[BN / 2], uint32_t da, uint32_t db, int accumulate) {
    STA();
    mbar_wait_fast(sb + BAR_FULL + ((n & 7) << 3), (n >> 3) & 1);
    STB(n);
    const uint64_t da64 = desc64(da), db64 = desc64(db);
    wgmma_fence();
#pragma unroll
    for (int k = 0; k < 4; k++) wgmma<BN>(acc, da64 + 2 * k, db64 + 128 * k, k ? 1 : accumulate);
    wgmma_commit();
    wgmma_wait<1>();
    if (prev && lane < 2) mbar_arrive_cluster(ebar + prev);
    prev = 64 + ((n & 7) << 3);
    advance<PAGES>();
  }
  template <int BN> __device__ __forceinline__ void step(float (&acc)[BN / 2], int accumulate = 1) { step_ab<BN, BN / 128 + 1>(acc, da0 + off, db0 + 1024 + off, accumulate); }
  template <int BN> __device__ __forceinline__ void step_own(float (&acc)[BN / 2], uint32_t da, int accumulate) { step_ab<BN, BN / 128>(acc, da, db0 + off, accumulate); }
  __device__ __forceinline__ void wait_full(uint32_t i) { mbar_wait_fast(sb + BAR_FULL + (((n + i) & 7) << 3), ((n + i) >> 3) & 1); }
  __device__ __forceinline__ void issue_rs2(float (&acc)[64], uint32_t (&a0)[16], uint32_t (&a1)[16]) {
    STA(); STB(n);
    const uint64_t db64 = desc64(db0 + off);
    wgmma_fence();
#pragma unroll
    for (int k = 0; k < 4; k++) wgmma_rs_n128(acc, a0 + 4 * k, db64 + 128 * k, 1);
#pragma unroll
    for (int k = 0; k < 4; k++) wgmma_rs_n128(acc, a1 + 4 * k, db64 + 1024 + 128 * k, 1);
    wgmma_commit();
    prev = 64 + ((n & 7) << 3);
    advance<2>();
  }
  template <int BN> __device__ __forceinline__ void steps(float (&acc)[BN / 2], int cnt) {
#pragma unroll 1
    do { step<BN>(acc); } while (--cnt > 0);
  }
  __device__ __forceinline__ void drain() {
    wgmma_wait<0>();
    if (lane < 2) mbar_arrive_cluster(ebar + prev);
    prev = 0;
  }
};

#define MAPPING 2
__device__ __forceinline__ uint32_t role_of_sm(uint32_t smid) {
  const uint32_t t = smid >> 1;
  uint32_t q, i;
  if (t < 32) { q = t & 7; i = t >> 3; }
  else if (t < 60) { const uint32_t u = t - 32, d = (u * 37) >> 8; q = 1 + u - d * 7; i = 4 + d; }
  else if (t < 62) return 128 + smid - 120;
  else { q = 0; i = t - 58; }
  return (q * 2 + (smid & 1)) * 8 + i;
}

template <typename T> __device__ __forceinline__ T* scratch(const Params& P, uint32_t off) { return (T*)ptr_add(P.scratch, off); }
__device__ __forceinline__ uint32_t* epoch_ptr(const Params& P) { uint32_t b; asm volatile("mov.u32 %0, %%ctaid.x;" : "=r"(b)); return scratch<uint32_t>(P, G_EPOCH + b * 4u); }

__device__ __forceinline__ int o_chunk(int s, int j) { const int hf = s >= 9, m = s - 2 - 7 * hf; return s < 2 ? 2 * j + s : 2 * (m == j ? 7 : m) + hf; }

__global__ void __cluster_dims__(2, 1, 1) __launch_bounds__(384, 1) fused_kernel(const __grid_constant__ Params P) {
  extern __shared__ __align__(1024) uint8_t smem_raw[];
  SP(0);
  const uint32_t sb = __shfl_sync(0xffffffffu, smem_u32(smem_raw), 0);
  const int warp = __shfl_sync(0xffffffffu, threadIdx.x >> 5, 0);
  const int lane = threadIdx.x & 31;
  if (warp == 7 && elect_one()) { prefetch_map(&P.map[M_XIN64]); prefetch_map(&P.map[M_WKV]); prefetch_map(&P.map[M_XIN]); }
  uint32_t role = blockIdx.x < 128 ? ((blockIdx.x >> 4) * 2 + (blockIdx.x & 1)) * 8 + ((blockIdx.x >> 1) & 7) : blockIdx.x;
  if (P.use_smid) { uint32_t smid; asm volatile("mov.u32 %0, %%smid;" : "=r"(smid)); role = role_of_sm(smid); }
  const bool spare = role >= 128;
  const int g = role >> 3, j = role & 7;
  uint32_t rank; asm("mov.u32 %0, %%cluster_ctarank;" : "=r"(rank));
  auto shared_b = [&]() {
    uint32_t peer;
    asm volatile("ld.shared::cluster.u32 %0, [%1];" : "=r"(peer) : "r"(mapa(sb + SM_ROLE, rank ^ 1)) : "memory");
    return !spare && peer < 128 && (peer & 7) == (uint32_t)j;
  };
  SP(1);

  if (warp >= 8) {
    asm volatile("setmaxnreg.dec.sync.aligned.u32 40;");
    if (elect_one()) {
      if (warp == 8) {
#pragma unroll
        for (int i = 0; i < 6; i++) mbar_init(sb + BAR_FULL + 8 * i, 1);
        mbar_init(sb + BAR_XIN, 1); mbar_init(sb + BAR_XIN + 8, 1);
      } else if (warp == 9) {
#pragma unroll
        for (int i = 0; i < 8; i++) mbar_init(sb + BAR_EMPTY + 8 * i, 16);
      } else if (warp == 10) {
#pragma unroll
        for (int i = 0; i < 4; i++) mbar_init(sb + BAR_SFULL + 8 * i, 4);
        mbar_init(sb + BAR_FULL + 48, 1); mbar_init(sb + BAR_FULL + 56, 1);
      } else {
        sts128(sb + SM_ROLE, role, 0, 0, 0);
        mbar_init(sb + BAR_TAG, 1); mbar_init(sb + BAR_XFULL, 8); mbar_init(sb + BAR_CSE, 8);
        mbar_init(sb + BAR_SEMPTY, 1); mbar_init(sb + BAR_CSF, 1); mbar_init(sb + BAR_CSF + 8, 2);
      }
      asm volatile("fence.mbarrier_init.release.cluster;\nfence.release.sync_restrict::shared::cta.cluster;" ::: "memory");
      fence_async_smem();
    }
    __syncwarp();
    SP(2);
    asm volatile("barrier.cluster.arrive.relaxed.aligned;" ::: "memory");
    if (warp == 8 && !spare) {
      if (elect_one()) {
        const int par = g & 1, row = (g >> 1) * 128;
#pragma unroll 1
        for (int s = 0; s < 2; s++) {
          const uint32_t xb = sb + BAR_XIN + 8 * s, fb = sb + BAR_FULL + 8 * s;
          mbar_expect_tx(xb, PAGE); mbar_expect_tx(fb, 2 * PAGE);
#pragma unroll
          for (int h = 0; h < 2; h++) tma_ld3(sb + SM_STAGE + h * PAGE + s * 8192, &P.map[M_XIN64], xb, s * 64, par, row + h * 64);
#pragma unroll
          for (int h = 0; h < 2; h++) tma_ld3(sb + (2 * s + h) * PAGE, &P.map[M_WKV], fb, 0, s * 64, 16 + 16 * h + 2 * j);
        }
#pragma unroll 1
        for (int s = 0; s < 2; s++) {
          const uint32_t fb = sb + BAR_FULL + 16 + 8 * s;
          mbar_expect_tx(fb, PAGE);
          tma_ld3(sb + (4 + s) * PAGE, &P.map[M_WKV], fb, 0, s * 64, 2 * j);
        }
#pragma unroll 1
        for (int s = 0; s < 2; s++) {
          const uint32_t fb = sb + BAR_FULL + 32 + 8 * s, a = sb + (6 + 3 * s) * PAGE;
          const int k = (j == 1 ? 4 : 2) + s;
          mbar_expect_tx(fb, 3 * PAGE);
          tma_ld3(a, &P.map[M_XIN], fb, k * 64, par, row);
#pragma unroll
          for (int h = 0; h < 2; h++) tma_ld3(a + PAGE + h * PAGE, &P.map[M_WKV], fb, 0, k * 64, 16 + 16 * h + 2 * j);
        }
        spin_check((sb & 1023) << 22);
      }
      __syncwarp();
    }
    SP(3);
    asm volatile("barrier.cluster.wait.acquire.aligned;" ::: "memory");
    SP(4);
    if (warp == 8) {
      if (elect_one()) {
        Prod p; p.sb = sb; p.n = 0; p.tail = 0; p.ready = 0; p.addr = 0;
        { const bool mc = shared_b(); p.rank = rank; p.flip = !mc; p.mask = mc ? 3 : 1 << rank; }
        uint32_t fb;
        if (spare) {
          p.pat = 0x55555000u;
#pragma unroll 1
          for (int r = -1; r < 7; r++) {
            const int ch = r < 0 ? 4 * j : ((r < 2 ? r : r == 2 ? 6 : r - 1) * 4 + j) * 2;
#pragma unroll 1
            for (int k = 0; k < 16; k++) { const uint32_t a = p.acquire<2>(fb); p.load_b(a, PAGE, &P.map[r < 0 ? M_WKV : M_W1], r < 0 ? 0 : 128, fb, k, ch, r < 0 ? 2 : 0); }
          }
        } else {
          p.seen = 0;
          SP(5);
#pragma unroll 1
          for (int hl = 0; hl < 4; hl++) {
            const int ffn = hl & 1;
            const CUtensorMap* xmap = &P.map[ffn ? M_XA_LD : hl ? M_OUT_LD : M_XIN];
            const int xpar = ffn ? g : g & 1, xrow = ffn ? 0 : (g >> 1) * 128;
            if (hl) {
              p.pat = ffn ? Pat<3>::v : Pat<7>::v; p.addr = 0;
#pragma unroll 1
              for (int s = 0; s < 2; s++) { const uint32_t a = p.acquire<2>(fb); p.load_wide(P, ffn, a, fb, 2 * j + s, 2 * j); }
#pragma unroll 1
              for (int s = 0; s < 2; s++) { const uint32_t a = p.acquire<1>(fb); p.load_narrow(P, ffn, a, fb, 2 * j + s, j); }
            } else { p.pat = (Pat<0>::v >> 12) | 0x55500000u; p.addr = 0; p.n = 6; }
            if (hl == 0) SP(6);
            uint32_t fb0 = 0;
#pragma unroll 1
            for (int m = hl ? 0 : 2; m < 14; m++) {
              const int hf = m >= 7, mm = m - 7 * hf, jj = mm == j ? 7 : mm;
              int k = 2 * jj + hf;
              if (hl == 0) {
                const int pr = (m >> 1) + 1;
                k = 2 * (j && pr == 2 ? j : pr == j ? 2 : pr) + (m & 1);
              }
              const uint32_t a = p.acquire<3>(fb);
              p.load_wide(P, ffn, a + PAGE, fb, k, 2 * j);
              if (hl) {
                if (m == 0) { fb0 = fb; continue; }
                if (m == 1) {
                  const int j0 = j ? 0 : 7;
                  p.flag = scratch<uint32_t>(P, g * G_BLOCK + G_FLAGS + (ffn ? (hl >> 1) * EV_N + EV_XA : EV_XB) * 128);
                  p.ready = 0; p.need((1u << j0) | (1u << j));
                  tma_ld3(a - 3 * PAGE, xmap, fb0, j0 * 128, xpar, xrow);
                }
                if (m < 7) p.need(1u << jj); else if (m == 7) p.next();
              }
              tma_ld3(a, xmap, fb, k * 64, xpar, xrow);
            }
            if (hl == 0) { mbar_wait(sb + BAR_TAG, 0); asm volatile("ld.shared.u32 %0, [%1];" : "=r"(p.base) : "r"(sb + SM_TAG) : "memory"); p.base = (p.base - 1) * 255; }
            static_assert(Pat<1>::v == Pat<4>::v, "");
            p.pat = Pat<1>::v;
#pragma unroll 1
            for (int m = 0; m < 14; m++) {
              const int k = (m >> 1) == (hl ? j : 0) ? 14 + (m & 1) : m;
              const uint32_t a = p.acquire<2>(fb);
              p.load_narrow(P, ffn, a + PAGE, fb, k, j);
              tma_ld3(a, xmap, fb, k * 64, xpar, xrow);
            }
            if (!ffn) {
              p.pat = Pat<2>::v;
              uint32_t a = p.acquire<2>(fb);
              tma_ld3(a, xmap, fb, j * 128, xpar, xrow); tma_ld3(a + PAGE, xmap, fb, j * 128 + 64, xpar, xrow);
#pragma unroll 1
              for (int s = 0; s < 16; s++) {
                if (!(s & 1)) a = p.acquire<2>(fb); else a += PAGE;
                p.load_b(a, 8192, &P.map[M_WO], 0, fb, o_chunk(s, j), 2 * j, 1);
              }
            } else {
              p.pat = Pat<5>::v; p.addr = 6 * PAGE;
#pragma unroll 1
              for (int s = 16; s < 48; s++) {
                const int pi = (s >> 1) & 7;
                const int k = (s < 32 ? pi : pi == 4 ? j : pi == j ? 4 : pi) * 2 + (s & 1);
                const uint32_t a = p.acquire<3>(fb);
                p.load_wide(P, 1, a + PAGE, fb, k, (s & 48) + 2 * j);
                tma_ld3(a, xmap, fb, k * 64, g, 0);
              }
              p.pat = Pat<6>::v;
#pragma unroll 1
              for (int q = 0; q < 4; q++) {
                p.next();
                const int k0 = q == 0 ? 0 : q == 1 ? 48 : q * 16 - 16, k1 = k0 + (q == 1 ? 8 : 16);
#pragma unroll 1
                for (int k = k0; k < k1; k++) {
                  const uint32_t a = p.acquire<2>(fb);
                  p.load_b(a + PAGE, 8192, &P.map[M_W2], 0, fb, k, 2 * j, 1);
                  tma_ld3(a, &P.map[M_H_LD], fb, k * 64, g, 0);
                }
              }
            }
            TL(2, 1 + hl);
          }
        }
        p.finish();
      }
    } else if (!spare) {
      mbar_wait(sb + BAR_XIN + CS_START, 0);
      if (elect_one()) prefetch_l2(ptr_add(P.wqkv, (role * 3 + (warp - 9)) * 16384u), 16384);
      const uint32_t tag = ld_relaxed(epoch_ptr(P)) + 1;
      if (warp == 10 && lane == 0) { asm volatile("st.shared.u32 [%0], %1;" :: "r"(sb + SM_TAG), "r"(tag) : "memory"); mbar_arrive(sb + BAR_TAG); }
      {
        const uint32_t part = warp - 9, col = DM + role * 16 + (lane & 1) * 8;
        const int cnt = part ? 21 : 22;
        const uint4* wp = ptr_add((const uint4*)P.wqkv, ((part ? 16 + part * 336 : 0) + (lane >> 1)) * 6144u + col * 2);
        float s[8] = {0, 0, 0, 0, 0, 0, 0, 0};
        uint4 v[4];
#pragma unroll
        for (int i = 0; i < 4; i++) v[i] = __ldcg(wp + i * (16 * 6144 / 16));
#pragma unroll 1
        for (int b = 4; b < 28; b += 4) {
          wp += 64 * 6144 / 16;
#pragma unroll
          for (int i = 0; i < 4; i++) {
            s[0] += bf_lo(v[i].x); s[1] += bf_hi(v[i].x); s[2] += bf_lo(v[i].y); s[3] += bf_hi(v[i].y);
            s[4] += bf_lo(v[i].z); s[5] += bf_hi(v[i].z); s[6] += bf_lo(v[i].w); s[7] += bf_hi(v[i].w);
            v[i] = make_uint4(0, 0, 0, 0);
            if (b + i < cnt) v[i] = __ldcg(wp + i * (16 * 6144 / 16));
          }
        }
#pragma unroll
        for (int e = 0; e < 4; e++) { const bool h = lane & 16; const float t = __shfl_xor_sync(0xffffffffu, h ? s[e] : s[e + 4], 16); s[e] = (h ? s[e + 4] : s[e]) + t; }
#pragma unroll
        for (int e = 0; e < 2; e++) { const bool h = lane & 8; const float t = __shfl_xor_sync(0xffffffffu, h ? s[e] : s[e + 2], 8); s[e] = (h ? s[e + 2] : s[e]) + t; }
        { const bool h = lane & 4; const float t = __shfl_xor_sync(0xffffffffu, h ? s[0] : s[1], 4); s[0] = (h ? s[1] : s[0]) + t; }
        s[0] += __shfl_xor_sync(0xffffffffu, s[0], 2);
        if (!(lane & 2) || part == 0) st_relaxed(scratch<uint32_t>(P, G_CS + (col + (lane >> 2)) * 16 + ((lane & 2) ? 3 : part) * 4), tagf((lane & 2) ? 0.f : s[0], tag));
        __syncwarp();
      }
      if (warp == 11 && lane == 0) TL(2, 30);
      {
        const uint32_t cspos = sb + SM_CS + ((lane & 16) + ((lane >> 1) & 3) * 4 + ((lane >> 3) & 1) * 2 + (lane & 1)) * 4;
#pragma unroll 1
        for (int it = 0; it < (warp == 10 ? 8 : 1); it++) {
          const int t = it & 3;
          if (it) mbar_wait(sb + BAR_CSE, (it - 1) & 1);
          if (t == 1) mbar_wait(sb + BAR_SEMPTY, 0);
#pragma unroll 1
          for (int b = it ? 0 : warp - 9; b < (it == 0 ? warp - 8 : t < 2 ? 3 : 2); b++) {
            uint32_t c0, c1;
            if (b < 2) { c0 = (t ? 2048 + t * 1024 + b * FF : 1024 + b * 1024) + j * 128; c1 = c0 + 64; }
            else if (t) { c0 = 6144 + j * 64; c1 = c0 + FF; }
            else { c0 = j * 128; c1 = c0 + 64; }
            const uint4* p0 = scratch<uint4>(P, G_CS + (c0 + lane) * 16u);
            const uint4* p1 = scratch<uint4>(P, G_CS + (c1 + lane) * 16u);
            uint4 v[4]; uint32_t spins = 0; bool ok;
            do {
              if (spins) __nanosleep(200);
              v[0] = ld_relaxed4(p0); v[1] = ld_relaxed4(p0 + 32); v[2] = ld_relaxed4(p1); v[3] = ld_relaxed4(p1 + 32);
              ok = tag_ok4(v[0], tag) && tag_ok4(v[1], tag) && tag_ok4(v[2], tag) && tag_ok4(v[3], tag);
              spin_check(++spins);
            } while (__any_sync(0xffffffffu, !ok));
#pragma unroll
            for (int m = 0; m < 4; m++) sts32f(cspos + b * 512 + m * 128, (untag(v[m].x) + untag(v[m].y)) + (untag(v[m].z) + untag(v[m].w)));
            __syncwarp();
            if (lane == 0) mbar_arrive(sb + BAR_CSF + (b ? 8 : 0));
          }
          if (lane == 0) { if (t >= 2) mbar_arrive(sb + BAR_CSF + 8); TL(2, 16 + it + (warp == 11 ? 8 : warp == 9 ? 9 : 0)); }
          if (t == 3) {
            uint4* op = scratch<uint4>(P, g * G_BLOCK + G_O + ((it >> 2) * 16 + 2 * j) * 16384u + lane * 16u);
#pragma unroll 1
            for (int i = 0; i < 64; i++) { st_b128(op, 0, 0, 0, 0); op += 32; __nanosleep(60); }
            if (g >= 2) {
              op = scratch<uint4>(P, G_HALO + (((it >> 2) * 16 + g - 2) * 8 + j) * 4096u + lane * 16u);
#pragma unroll 1
              for (int i = 0; i < 8; i++) { st_b128(op, 0, 0, 0, 0); op += 32; }
            }
          }
        }
      }
      if (warp == 11) {
        if (elect_one()) {
          prefetch_l2(ptr_add(P.wo, role * 16384u), 16384);
          const uint32_t* fl = scratch<uint32_t>(P, g * G_BLOCK + G_FLAGS);
          uint32_t seen = 0;
#pragma unroll 1
          for (int e = EV_XA2; e < EV_N + EV_XB; e++) {
            if (e == EV_XB || e == EV_N + EV_XA) continue;
            uint32_t spins = 0, m;
            while ((m = ld_relaxed(ptr_add(fl, e * 128u)) - (tag - 1) * 255) != 255) { __nanosleep(m ? 50 : 500); spin_check(++spins); }
            asm volatile("fence.acquire.gpu;\nst.release.cta.shared.u32 [%0], %1;" :: "r"(sb + SM_SEEN), "r"(++seen) : "memory");
            if (e == EV_H3) {
#pragma unroll 1
              for (int i = 0; i < 7; i++) { prefetch_l2(ptr_add(P.w2, (i * 128 + role) * 8192u), 8192); __nanosleep(500); }
            }
          }
        }
      } else if (warp == 9) {
        if (elect_one()) {
          prefetch_map(&P.map[M_WQ]); prefetch_map(&P.map[M_XA_ST]); prefetch_map(&P.map[M_XA_LD]); prefetch_map(&P.map[M_OUT_LD]); prefetch_map(&P.map[M_WO]); prefetch_map(&P.map[M_W1 + rank]);
          prefetch_map(&P.map[M_H_ST]); prefetch_map(&P.map[M_H_LD]); prefetch_map(&P.map[M_W1H + rank]); prefetch_map(&P.map[M_W2]); prefetch_map(&P.map[M_OUT_ST]);
          uint32_t* fl = scratch<uint32_t>(P, g * G_BLOCK + G_FLAGS);
          int pe = 0;
#pragma unroll 1
          for (int e = 0; e < 2 * EV_N; e++) {
            const int q = e & 7;
            const bool is_h = q >= EV_H0 && q < EV_XB, last = e >= EV_N + EV_XB;
            const CUtensorMap* map = &P.map[q >= EV_XB ? M_OUT_ST : is_h ? M_H_ST : M_XA_ST];
            const int col = q == EV_H3 ? 3072 - 64 + j * 64 : (q == EV_H1 ? 1024 : q == EV_H2 ? 2048 : 0) + j * 128;
            const int row = q >= EV_XB ? (g >> 1) * 128 : 0, par = q >= EV_XB ? g & 1 : g;
#pragma unroll 1
            for (int hb = is_h ? q == EV_H3 : q & 1; hb <= (is_h ? 1 : q & 1); hb++) {
#pragma unroll
              for (int wg = 0; wg < 2; wg++) {
                mbar_wait(sb + BAR_SFULL + 16 * wg + 8 * (pe & 1), (pe >> 1) & 1);
                if (wg == 0) TL(3, 20 + e);
                tma_st3(map, sb + SM_STAGE + wg * PAGE + hb * 8192, col + hb * 64, par, row + wg * 64);
              }
              pe++;
            }
            bulk_commit();
            if (e != EV_N + EV_XB) bulk_wait<0>();
            TL(3, 40 + e);
            if (is_h || (q & 1)) mbar_arrive(sb + BAR_SEMPTY);
            if (!last) red_release(fl, 1u << j);
            TL(3, e);
            fl += 32;
          }
          *epoch_ptr(P) = tag;
        }
      }
    }
  } else {
    if (EARLY_PF && !spare) {
      if (warp == 0) asm volatile("prefetch.global.L2 [%0];" :: "l"(ptr_add(P.x, (2 * ((g >> 1) * 128 + j * 16 + (lane >> 1)) + (g & 1)) * 2048u + (lane & 1) * 128u)));
      else if (warp < 3 && (warp == 1 || lane < 16)) asm volatile("prefetch.global.L2 [%0];" :: "l"(ptr_add(P.wqkv, role * 6144u + (warp - 1) * 4096u + lane * 128u)));
      __syncwarp();
    }
    asm volatile("barrier.cluster.arrive.relaxed.aligned;" ::: "memory");
    asm volatile("setmaxnreg.inc.sync.aligned.u32 232;");
    SP(4);
    asm volatile("barrier.cluster.wait.acquire.aligned;" ::: "memory");
    SP(5);
    const int wg = warp >> 2;
    const int quad = lane & 3, gr = lane >> 2;
    Cons c; c.sb = sb; c.n = 0; c.off = 0; c.prev = 0; c.lane = lane;
    c.ebar = mapa(sb + BAR_EMPTY - 64, shared_b() ? lane & 1 : rank);
    const uint32_t stage = sb + SM_STAGE + wg * PAGE;
    const uint32_t dstage = desc_lo(stage, 16);
    if (spare) {
      const uint32_t tag = ld_relaxed(epoch_ptr(P)) + 1;
      const int tid = threadIdx.x & 127;
#pragma unroll
      for (int i = 0; i < 4; i++) sts128(stage + (i * 128 + tid) * 16, 0x3f803f80u, 0x3f803f80u, 0x3f803f80u, 0x3f803f80u);
      fence_async_smem();
      bar_sync(2 + wg, 128);
      c.db0 = desc_lo(sb + wg * PAGE, 8192);
#pragma unroll 1
      for (int r = -1; r < 7; r++) {
        float acc[64];
#pragma unroll 1
        for (int k = 0; k < 16; k++) c.step_ab<128, 2>(acc, dstage, c.db0 + c.off, k);
        c.drain();
        acc_fence<64>(acc);
        {
          float v = 0;
#pragma unroll
          for (int i = 0; i < 32; i++) asm("{\n.reg .pred p;\nsetp.eq.u32 p, %2, %3;\nselp.f32 %0, %1, %0, p;\n}" : "+f"(v) : "f"(acc[4 * (i >> 1) + (i & 1)]), "r"(tid >> 2), "r"(i));
          st_b128(scratch<uint4>(P, G_CS + (uint32_t)((r < 0 ? j * 256 + wg * 128 : 3 * DM + wg * FF + ((r < 2 ? r : r == 2 ? 6 : r - 1) * 4 + j) * 128) + (tid >> 3) * 8 + quad * 2 + (gr & 1)) * 16u),
                  tagf(v, tag), tag & 15u, tag & 15u, tag & 15u);
        }
        __syncwarp();
      }
      if (wg == 0) {
        const uint32_t* p = scratch<uint32_t>(P, (tid >> 3) * G_BLOCK + G_STATS + (tid & 7) * 8u);
        uint32_t spins = 0;
        while (__any_sync(0xffffffffu, (ld_relaxed(p) ^ tag) & 15u)) spin_check(++spins);
      }
      bar_sync(1, 256);
      if (threadIdx.x == 0) *epoch_ptr(P) = tag;
    } else {
    c.da0 = desc_lo(sb + wg * 8192, 16); c.db0 = desc_lo(sb, 8192);
    uint32_t sphase = 1, sfull = sb + BAR_SFULL + 16 * wg;
    const uint32_t maddr = stage + ((warp & 3) * 16 + (lane & 15)) * 128 + (((lane >> 4) ^ (lane & 7)) << 4);
    const uint32_t csaddr = sb + SM_CS + quad * 16;
    float st[8] = {0, 0, 0, 0, 0, 0, 0, 0};
    float* const mean = st; float* const rstd = st + 2;
    SP(6);

    auto stage_wait = [&]() { mbar_wait_fast(sb + BAR_SEMPTY, sphase); sphase ^= 1; };
    auto stage_publish = [&]() { fence_async_smem(); __syncwarp(); if (lane == 0) mbar_arrive(sfull); sfull ^= 8; };
    auto cs_load = [&](uint32_t (&cs)[16], int grp) {
#pragma unroll
      for (int i = 0; i < 4; i++) lds128(csaddr + grp * 256 + i * 64, cs[4 * i], cs[4 * i + 1], cs[4 * i + 2], cs[4 * i + 3]);
    };
    auto cs_apply = [&](float* acc, uint32_t (&cs)[16]) {
      acc_fence<32>(acc);
#pragma unroll
      for (int b = 0; b < 8; b++) {
        acc[4 * b] -= mean[0] * __uint_as_float(cs[2 * b]); acc[4 * b + 1] -= mean[0] * __uint_as_float(cs[2 * b + 1]);
        acc[4 * b + 2] -= mean[1] * __uint_as_float(cs[2 * b]); acc[4 * b + 3] -= mean[1] * __uint_as_float(cs[2 * b + 1]);
      }
      acc_fence<32>(acc);
    };
    auto glu_pair = [&](float g0, float g1, float u0, float u1, int r) {
      const float nl = -LOG2E * rstd[r], r2 = rstd[r] * rstd[r];
      return pack_bf16(g0 * u0 * r2 * rcp(1.0f + ex2(g0 * nl)), g1 * u1 * r2 * rcp(1.0f + ex2(g1 * nl)));
    };
    auto glu_slice = [&](uint32_t (&pk)[64], int i) {
      uint32_t hp[4];
#pragma unroll
      for (int e = 0; e < 4; e++) {
        asm volatile("" : "+r"(pk[4 * i + e]), "+r"(pk[32 + 4 * i + e]));
        const uint32_t pg = pk[4 * i + e], pu = pk[32 + 4 * i + e];
        hp[e] = glu_pair(bf_lo(pg), bf_hi(pg), bf_lo(pu), bf_hi(pu), e & 1);
      }
      stsm4((maddr ^ ((i & 3) << 5)) + (i >> 2) * 8192, hp[0], hp[1], hp[2], hp[3]);
    };
    auto glu_slice_acc = [&](float (&acc)[128], int i) {
      uint32_t hp[4];
      acc_fence<8>(acc + 8 * i);
#pragma unroll
      for (int e = 0; e < 4; e++) hp[e] = glu_pair(acc[8 * i + 2 * e], acc[8 * i + 2 * e + 1], acc[64 + 8 * i + 2 * e], acc[64 + 8 * i + 2 * e + 1], e & 1);
      stsm4((maddr ^ ((i & 3) << 5)) + (i >> 2) * 8192, hp[0], hp[1], hp[2], hp[3]);
    };
    auto stage_x = [&](float (&x)[64], int hf) {
#pragma unroll
      for (int i = 4 * hf; i < 4 * hf + 4; i++)
        stsm4((maddr ^ ((i & 3) << 5)) + hf * 8192, pack_bf16(x[8 * i], x[8 * i + 1]), pack_bf16(x[8 * i + 2], x[8 * i + 3]),
              pack_bf16(x[8 * i + 4], x[8 * i + 5]), pack_bf16(x[8 * i + 6], x[8 * i + 7]));
      stage_publish();
    };

    float acc[128];
    mbar_wait_fast(sb + BAR_XIN, 0);
    SP(7);
    c.step_own<256>(acc, dstage, 0);
    mbar_wait_fast(sb + BAR_XIN + 8, 0);
    SP(8);
#pragma unroll 1
    for (int hl = 0;; hl++) {
      int t = hl & 1;
      float acc2[64];
      c.step_own<256>(acc, dstage + 512, 1);
#pragma unroll
      for (int s = 0; s < 2; s++) c.step_own<128>(acc2, dstage + s * 512, s);
#pragma unroll 1
      for (int s = 2; s < 11; s++) {
        const uint32_t apage = (c.off << 4) - (SM_STAGE + wg * 8192);
        c.step<256>(acc);
        int act = s;
        asm volatile("" : "+r"(act));
        auto get_tag = [&]() { uint32_t tag; asm volatile("ld.shared.u32 %0, [%1];" : "=r"(tag) : "r"(sb + SM_TAG) : "memory"); return tag; };
        auto stat_ptr = [&]() { return scratch<uint2>(P, g * G_BLOCK + G_STATS + (hl * 128 + warp * 16 + (lane_now() >> 2)) * 64u); };
        auto stat_get = [&]() {
          const uint2* sp = ptr_add(stat_ptr(), (lane_now() & 3) * 16);
          const uint4 a = ld_relaxed4(sp), b = ld_relaxed4(sp + 64);
          st[0] = __uint_as_float(a.x); st[1] = __uint_as_float(a.y); st[2] = __uint_as_float(a.z); st[3] = __uint_as_float(a.w);
          st[4] = __uint_as_float(b.x); st[5] = __uint_as_float(b.y); st[6] = __uint_as_float(b.z); st[7] = __uint_as_float(b.w);
        };
        switch (act) {
          case 4: case 5: {
            const uint32_t ra = maddr + ((hl || j == 0) ? (s & 1) * 8192 : apage);
#pragma unroll
            for (int i = 0; i < 4; i++) {
              uint32_t v[4];
              ldsm4(ra ^ (i << 5), v[0], v[1], v[2], v[3]);
              if (i == 0 && s == 4) { st[0] = bf_lo(v[0]); st[1] = bf_lo(v[1]); st[2] = st[3] = st[4] = st[5] = 0; }
#pragma unroll
              for (int e = 0; e < 4; e++) {
                const float a = bf_lo(v[e]) - st[e & 1], b = bf_hi(v[e]) - st[e & 1];
                st[2 + (e & 1)] += a + b; st[4 + (e & 1)] += a * a; st[4 + (e & 1)] += b * b;
              }
            }
          } break;
          case 6: {
            mbar_wait_fast(sb + BAR_TAG, 0);
            const uint32_t tag = get_tag();
#pragma unroll
            for (int r = 0; r < 2; r++) {
              const float mt = st[r] + st[2 + r] * (1.0f / 32);
              float m = mt + __shfl_xor_sync(0xffffffffu, mt, 1); m += __shfl_xor_sync(0xffffffffu, m, 2); m *= 0.25f;
              float q = st[4 + r] - st[2 + r] * st[2 + r] * (1.0f / 32) + 32.0f * (mt - m) * (mt - m);
              q += __shfl_xor_sync(0xffffffffu, q, 1); q += __shfl_xor_sync(0xffffffffu, q, 2);
              if (quad == 0) st_relaxed2(ptr_add(stat_ptr(), r * 512 + j * 8), tagf(m, tag), tagf(q, tag));
            }
          } break;
          case 8: stat_get(); break;
          case 10: {
            const uint32_t tag = get_tag();
            uint32_t spins = 0;
            for (;;) {
              uint32_t bad = 0;
#pragma unroll
              for (int i = 0; i < 8; i++) bad |= __float_as_uint(st[i]) ^ tag;
              if (!__any_sync(0xffffffffu, bad & 15u)) break;
              stat_get(); spin_check(++spins);
            }
            float mr[4];
#pragma unroll
            for (int r = 0; r < 2; r++) {
              const float m0 = untag(__float_as_uint(st[4 * r])), m1 = untag(__float_as_uint(st[4 * r + 2]));
              float m = m0 + m1; m += __shfl_xor_sync(0xffffffffu, m, 1); m += __shfl_xor_sync(0xffffffffu, m, 2); m *= 0.125f;
              float q = untag(__float_as_uint(st[4 * r + 1])) + untag(__float_as_uint(st[4 * r + 3])) + 128.0f * ((m0 - m) * (m0 - m) + (m1 - m) * (m1 - m));
              q += __shfl_xor_sync(0xffffffffu, q, 1); q += __shfl_xor_sync(0xffffffffu, q, 2);
              mr[r] = m; mr[2 + r] = rsqrtf(fmaxf(q, 0.f) * (1.0f / DM) + LN_EPS);
            }
            st[0] = mr[0]; st[1] = mr[1]; st[2] = mr[2]; st[3] = mr[3];
          } break;
          default: break;
        }
      }
#pragma unroll 1
      for (;;) {
      const int it = (hl >> 1) * 4 + t;
#pragma unroll
      for (int s = 0; s < 4; s++) {
        uint32_t cs[16];
        c.step<256>(acc);
        if (!(s & 1)) mbar_wait_fast(sb + BAR_CSF + 4 * s, t & 1);
        if (s >= 2 && t <= 1) { cs_load(cs, 2 + s); cs_apply(acc2 + 32 * (s - 2), cs); }
        cs_load(cs, s);
        c.drain();
        cs_apply(acc + 32 * s, cs);
      }
      c.step<256>(acc);
      if (lane == 0) mbar_arrive(sb + BAR_CSE);
      c.drain();
      acc_fence<128>(acc);
      TLC(1 + it * 6);
      uint32_t pkB[64];
      if (t == 2) {
#pragma unroll
        for (int i = 0; i < 64; i++) pkB[i] = pack_bf16(acc[2 * i], acc[2 * i + 1]);
      } else if (t == 0) {
        uint32_t pkA[64];
        auto kv_pack = [&](int v, int r) {
#pragma unroll
          for (int i = 32 * v + r; i < 32 * v + 32; i += 2) { acc_fence<2>(acc + 2 * i); pkA[i] = pack_bf16(acc[2 * i] * rstd[r], acc[2 * i + 1] * rstd[r]); }
        };
        const uint32_t l16 = lane_now() * 16u;
        uint4* const xs = ptr_add((uint4*)smem_raw, SM_STAGE + l16);
        uint4* const hp = scratch<uint4>(P, G_HALO + (((hl >> 1) * 16 + g) * 8 + j) * 4096u + l16);
        {
          uint4* const dst = (warp == 7 && g < 14) ? hp : ptr_add(xs, warp * 4096u);
#pragma unroll
          for (int s = 0; s < 2; s++) {
            c.steps<128>(acc2, s ? 2 : 1 + wg);
            if (s == 0) stage_wait();
            kv_pack(s, 1);
#pragma unroll
            for (int i = 4 * s; i < 4 * s + 4; i++) { pkA[8 * i + 1] = pkt_head(pkA[8 * i + 1]); gen_store(dst + i * 32, pkA[8 * i + 1], pkA[8 * i + 3], pkA[8 * i + 5], pkA[8 * i + 7]); }
          }
        }
        __syncwarp();
        if (lane == 0) mbar_arrive(sb + BAR_XFULL);
#pragma unroll
        for (int s = 0; s < 2; s++) {
          c.steps<128>(acc2, 2);
#pragma unroll
          for (int i = 33 - s; i < 64; i += 2) pkA[i] = movm(pkA[i]);
          kv_pack(1 - s, 0);
        }
        uint32_t kvH[32];
        {
          const uint4* const src = (warp == 0 && g >= 2) ? hp - 2 * 8 * 256 : ptr_add(xs, (warp ? warp - 1 : 0) * 4096u);
          c.steps<128>(acc2, 2);
          mbar_wait_fast(sb + BAR_XFULL, hl >> 1);
#pragma unroll
          for (int i = 0; i < 8; i++) gen_load(src + i * 32, kvH + 4 * i);
          c.steps<128>(acc2, 3 - wg);
          uint32_t spins = 0;
          while (__any_sync(0xffffffffu, !(kvH[0] && kvH[4] && kvH[8] && kvH[12] && kvH[16] && kvH[20] && kvH[24] && kvH[28]))) {
#pragma unroll
            for (int i = 0; i < 8; i++) gen_load(src + i * 32, kvH + 4 * i);
            spin_check(++spins);
          }
        }
#pragma unroll
        for (int i = 16; i < 32; i++) kvH[i] = movm(kvH[i]);
        c.steps<128>(acc2, 2);
        AP(0);
#pragma unroll 1
        for (int i = 0; i < 2; i++) c.wait_full(i);
        AP(1);
        c.drain();
        AP(2);
        acc_fence<64>(acc2);
        TLC(2 + it * 6);
        uint32_t q[32];
#pragma unroll
        for (int i = 0; i < 32; i++) q[i] = pack_bf16(acc2[2 * i], acc2[2 * i + 1]);
        const uint32_t zm = bar_sync_zero(1, 256);
        AP(3);
        uint32_t ob[4][16];
        uint4* const omail = scratch<uint4>(P, g * G_BLOCK + G_O + (hl >> 1) * 262144u + warp * 2048u + l16);
        auto o_fetch = [&](uint32_t (&v0)[16], uint32_t (&v1)[16], const uint4* p0, const uint4* p1) {
#pragma unroll
          for (int i = 0; i < 4; i++) pkt_load(p0 + i * 32, v0 + 4 * i);
#pragma unroll
          for (int i = 0; i < 4; i++) pkt_load(p1 + i * 32, v1 + 4 * i);
        };
        {
          const uint32_t ra = maddr - (SM_STAGE + wg * 8192) + (c.off << 4);
#pragma unroll
          for (int i = 0; i < 8; i++) { uint32_t* v = ob[2 + (i >> 2)] + 4 * (i & 3); ldsm4((ra ^ ((i & 3) << 5)) + (i >> 2) * PAGE, v[0], v[1], v[2], v[3]); }
          const uint32_t rbar = 64 + ((c.n & 7) << 3);
          c.advance<2>();
          const float hv = (warp == 0 && g < 2) ? -INFINITY : 0.f;
          const float hinit[4] = {hv, hv, hv, hv};
          const bool c0 = (2 * quad <= gr), c1 = (2 * quad + 1 <= gr);
          const uint32_t lm = (c0 ? 0xffffu : 0u) | (c1 ? 0xffff0000u : 0u);
          const float sc[2] = {rstd[0] * (0.17677669529663687f * LOG2E), rstd[1] * (0.17677669529663687f * LOG2E)};
          float lg[4][4], mx[4][2];
#pragma unroll
          for (int h = 0; h < 4; h++) {
            const int b = h * 4;
            float sH[4], sL[4], sU[4];
            q[2 * b] |= zm;
            mma16816(sH, q[2 * b], q[2 * b + 1], q[2 * b + 2], q[2 * b + 3], kvH[b], kvH[b + 1], hinit);
            mma16816z(sL, q[2 * b], q[2 * b + 1], q[2 * b + 2], q[2 * b + 3], pkA[2 * b], pkA[2 * b + 2]);
            mma16816z(sU, q[2 * b], q[2 * b + 1], q[2 * b + 2], q[2 * b + 3], pkA[2 * b + 1], pkA[2 * b + 3]);
            mma16816(sH, q[2 * b + 4], q[2 * b + 5], q[2 * b + 6], q[2 * b + 7], kvH[b + 2], kvH[b + 3], sH);
            mma16816(sL, q[2 * b + 4], q[2 * b + 5], q[2 * b + 6], q[2 * b + 7], pkA[2 * b + 4], pkA[2 * b + 6], sL);
            mma16816(sU, q[2 * b + 4], q[2 * b + 5], q[2 * b + 6], q[2 * b + 7], pkA[2 * b + 5], pkA[2 * b + 7], sU);
            lg[h][0] = c0 ? sL[0] : sH[0]; lg[h][1] = c1 ? sL[1] : sH[1]; lg[h][2] = c0 ? sU[2] : sL[2]; lg[h][3] = c1 ? sU[3] : sL[3];
            mx[h][0] = fmaxf(lg[h][0], lg[h][1]); mx[h][1] = fmaxf(lg[h][2], lg[h][3]);
          }
#pragma unroll
          for (int o = 1; o < 4; o <<= 1) {
#pragma unroll
            for (int i = 0; i < 8; i++) mx[i >> 1][i & 1] = fmaxf(mx[i >> 1][i & 1], __shfl_xor_sync(0xffffffffu, mx[i >> 1][i & 1], o));
          }
          AP(4);
          uint32_t z = zm;
#pragma unroll
          for (int hf = 0; hf < 2; hf++) {
#pragma unroll
            for (int hh = 0; hh < 2; hh++) {
              const int h = hf * 2 + hh, b = h * 4;
              const uint32_t pa = pack_bf16(ex2((lg[h][0] - mx[h][0]) * sc[0]), ex2((lg[h][1] - mx[h][0]) * sc[0]));
              const uint32_t pb = pack_bf16(ex2((lg[h][2] - mx[h][1]) * sc[1]), ex2((lg[h][3] - mx[h][1]) * sc[1]));
              float sum[4];
              mma1688z(sum, pa, pb, 0x3f803f80u);
              const uint32_t p0 = pa & ~lm, p1 = pa & z, p2 = pa & lm, p3 = pb & ~lm, p4 = pb & z, p5 = pb & lm;
              const float ra = rcp(sum[0]), rb = rcp(sum[2]);
#pragma unroll
              for (int d = 0; d < 4; d++) {
                float o[4];
                mma16816z(o, p0, p1, p2, p3, kvH[16 + b + d], pkA[32 + 2 * (b + d)]);
                mma1688(o, p4, p5, pkA[32 + 2 * (b + d) + 1], o);
                ob[hf][(hh * 4 + d) * 2] = pack_bf16(o[0] * ra, o[1] * ra); ob[hf][(hh * 4 + d) * 2 + 1] = pack_bf16(o[2] * rb, o[3] * rb);
              }
            }
#pragma unroll
            for (int i = 0; i < 4; i++) ob[hf][4 * i] = pkt_head(ob[hf][4 * i]);
            if (hf == 0) {
              AP(5);
              uint4* op = ptr_add(omail, j * 32768u);
#pragma unroll
              for (int i = 0; i < 4; i++) st_b128(op + i * 32, ob[0][4 * i], ob[0][4 * i + 1], ob[0][4 * i + 2], ob[0][4 * i + 3]);
              z = late_zero(zm);
              AP(6);
            }
          }
#pragma unroll
          for (int i = 0; i < 32; i++) { acc2[2 * i] = bf_lo(ob[2 + (i >> 4)][i & 15]); acc2[2 * i + 1] = bf_hi(ob[2 + (i >> 4)][i & 15]); }
          acc_fence<64>(acc2);
          if (lane < 2) mbar_arrive_cluster(c.ebar + rbar);
#pragma unroll
          for (int i = 0; i < 4; i++) sts128(stage + (warp & 3) * 2048 + i * 512 + l16, ob[1][4 * i], ob[1][4 * i + 1], ob[1][4 * i + 2], ob[1][4 * i + 3]);
          AP(7);
          bar_sync(1, 256);
        }
        TLC(3 + it * 6);
        AP(8);
        uint64_t todo;
        { const uint32_t o7 = 0x6543210u | (7u << (4 * j) & 0xfffffffu); todo = (uint64_t)(o7 * 2) | (uint64_t)(o7 * 2 + 0x1111111u) << 28; }
        const uint4* p0 = ptr_add(omail, ((uint32_t)todo & 15u) << 14);
        const uint4* p1 = ptr_add(omail, ((uint32_t)todo & 240u) << 10);
#pragma unroll 1
        for (int s0 = 0; s0 < 16; s0 += 4) {
#pragma unroll
          for (int b = 0; b < 4; b += 2) {
            const bool more = b == 0 || s0 < 12;
            uint32_t (&y0)[16] = ob[b ^ 2], (&y1)[16] = ob[b ^ 3];
            if (WO_ORDER == 1 && b == 0 && s0 == 0) y0[0] = 0;
            else if (more) o_fetch(y0, y1, p0, p1);
            c.issue_rs2(acc2, ob[b], ob[b + 1]);
            if (more) {
              const uint32_t z = late_zero(zm);
              c.wait_full(0);
              if (s0 + b == 0) AP(9);
              uint32_t spins = 0;
              while (__builtin_expect(__any_sync(0xffffffffu, (y0[0] == z || y0[4] == z || y0[8] == z || y0[12] == z) | (y1[0] == z || y1[4] == z || y1[8] == z || y1[12] == z)), 0)) {
                o_fetch(y0, y1, p0, p1);
                spin_check(++spins);
              }
              if (b == 0 && s0 == 0) {
                fence_async_smem();
                __syncwarp();
                if (elect_one()) {
                  asm volatile("cp.async.bulk.global.shared::cta.bulk_group [%0], [%1], 2048;"
                               :: "l"(scratch<uint4>(P, g * G_BLOCK + G_O + (hl >> 1) * 262144u + (2 * j + 1) * 16384u + warp * 2048u)), "r"(stage + (warp & 3) * 2048) : "memory");
                  bulk_commit();
                }
              }
              todo >>= 8;
              p0 = ptr_add(omail, ((uint32_t)todo & 15u) << 14); p1 = ptr_add(omail, ((uint32_t)todo & 240u) << 10);
              asm volatile("" : "+l"(p0), "+l"(p1));
            } else { if (elect_one()) bulk_wait<0>(); __syncwarp(); }
            c.drain();
            if (s0 + b == 0) AP(11);
            if (s0 + b == 2) AP(12);
            if (s0 + b == 4) AP(13);
            if (s0 + b == 14) AP(14);
          }
        }
        break;
      } else {
        c.steps<128>(acc2, 1 + wg);
        stage_wait();
        glu_slice_acc(acc, 0);
#pragma unroll
        for (int s = 1; s < 8; s++) { c.steps<128>(acc2, (s & 1) || t == 3 ? 2 : 1); if (s == 4) stage_publish(); glu_slice_acc(acc, s); }
        c.steps<128>(acc2, 2 - wg);
        stage_publish();
        if (t == 3) c.steps<128>(acc2, 39);
        if (t == 3) stage_wait();
        c.drain();
        acc_fence<64>(acc2);
        if (t == 3) break;
        TLC(2 + it * 6);
        c.off = 6 << 10; asm volatile("" : "+r"(c.off));
        c.step<256>(acc, 0);
        acc_fence<64>(acc2);
#pragma unroll
        for (int i = 0; i < 16; i++) {
          pkB[16 + i] = pack_bf16(acc2[2 * i], acc2[2 * i + 1]); pkB[48 + i] = pack_bf16(acc2[32 + 2 * i], acc2[32 + 2 * i + 1]);
          pkB[i] = 0; pkB[32 + i] = 0;
        }
      }
      t++;
#pragma unroll 1
      for (int s = 3 - t; s < 8; s++) {
        c.step<256>(acc, s);
        int act = (t == 3 || s >= 4) ? s : 8;
        asm volatile("" : "+r"(act));
        if (act < 8) {
          if (!(act & 3)) { if (act && t == 3) stage_publish(); else stage_wait(); }
          auto f = [&](int i) { glu_slice(pkB, i); };
          SELECT8(act, f);
        }
      }
#pragma unroll
      for (int s = 0; s < 2; s++) {
        const uint32_t ra = maddr - (SM_STAGE + wg * 8192) + (c.off << 4);
        c.step<256>(acc);
        if (s == 0) stage_publish();
#pragma unroll
        for (int i = 0; i < 4; i++) {
          uint32_t v[4];
          ldsm4(ra ^ (i << 5), v[0], v[1], v[2], v[3]);
#pragma unroll
          for (int e = 0; e < 4; e++) { acc2[32 * s + 8 * i + 2 * e] = bf_lo(v[e]); acc2[32 * s + 8 * i + 2 * e + 1] = bf_hi(v[e]); }
        }
        acc_fence<32>(acc2 + 32 * s);
      }
      c.step<256>(acc);
      }
      const int it = (hl >> 1) * 4 + t;
      acc_fence<64>(acc2);
      TLC(4 + it * 6);
      stage_x(acc2, 0);
      if (hl == 3) { stage_x(acc2, 1); TLC(5 + it * 6); TLG(63); break; }
      bar_sync(2 + wg, 128);
      TLC(5 + it * 6);
      c.off = 0; asm volatile("" : "+r"(c.off));
      c.step_own<256>(acc, dstage, 0);
      acc_fence<32>(acc2 + 32);
      stage_x(acc2, 1);
      bar_sync(2 + wg, 128);
    }
    }
  }
}

typedef CUresult (*EncodeFn)(CUtensorMap*, CUtensorMapDataType, cuuint32_t, void*, const cuuint64_t*, const cuuint64_t*, const cuuint32_t*,
                             const cuuint32_t*, CUtensorMapInterleave, CUtensorMapSwizzle, CUtensorMapL2promotion, CUtensorMapFloatOOBfill);

void encode(EncodeFn fn, CUtensorMap* m, const void* ptr, int rank, const cuuint64_t* dims, const cuuint64_t* strides, const cuuint32_t* box) {
  cuuint32_t es[5] = {1, 1, 1, 1, 1};
  fn(m, CU_TENSOR_MAP_DATA_TYPE_BFLOAT16, rank, const_cast<void*>(ptr), dims, strides, box, es, CU_TENSOR_MAP_INTERLEAVE_NONE,
     CU_TENSOR_MAP_SWIZZLE_128B, CU_TENSOR_MAP_L2_PROMOTION_L2_128B, CU_TENSOR_MAP_FLOAT_OOB_FILL_NONE);
}

}

extern "C" void kernel_launch(void* const* d_in, const int* in_sizes, int n_in, void* d_out, int out_size) {
  const __nv_bfloat16* x = (const __nv_bfloat16*)d_in[0];
  const __nv_bfloat16* wqkv = (const __nv_bfloat16*)d_in[1];
  const __nv_bfloat16* wo = (const __nv_bfloat16*)d_in[2];
  const __nv_bfloat16* w1 = (const __nv_bfloat16*)d_in[4];
  const __nv_bfloat16* w3 = (const __nv_bfloat16*)d_in[5];
  const __nv_bfloat16* w2 = (const __nv_bfloat16*)d_in[6];

  void* fnp = nullptr; cudaDriverEntryPointQueryResult qr;
  cudaGetDriverEntryPoint("cuTensorMapEncodeTiled", &fnp, cudaEnableDefault, &qr);
  EncodeFn fn = (EncodeFn)fnp;
  void* sym;
  cudaGetSymbolAddress(&sym, g_scratch);
  uint8_t* scr = (uint8_t*)(((uintptr_t)sym + G_BLOCK - 1) / G_BLOCK * G_BLOCK);

  Params P = {};
  { cuuint64_t d[3] = {DM, 2, SEQ / 2}, s[2] = {DM * 2, DM * 4}; cuuint32_t b[3] = {64, 1, 128}, b2[3] = {64, 1, 64};
    encode(fn, &P.map[M_XIN], x, 3, d, s, b); encode(fn, &P.map[M_XIN64], x, 3, d, s, b2);
    encode(fn, &P.map[M_OUT_LD], d_out, 3, d, s, b); encode(fn, &P.map[M_OUT_ST], d_out, 3, d, s, b2); }
  { cuuint64_t d[3] = {DM, 16, 128}, s[2] = {G_BLOCK, DM * 2}; cuuint32_t b[3] = {64, 1, 128}, b2[3] = {64, 1, 64};
    encode(fn, &P.map[M_XA_LD], scr + G_XA, 3, d, s, b); encode(fn, &P.map[M_XA_ST], scr + G_XA, 3, d, s, b2); }
  { cuuint64_t d[3] = {FF, 16, 128}, s[2] = {G_BLOCK, FF * 2}; cuuint32_t b[3] = {64, 1, 128}, b2[3] = {64, 1, 64};
    encode(fn, &P.map[M_H_LD], scr + G_H, 3, d, s, b); encode(fn, &P.map[M_H_ST], scr + G_H, 3, d, s, b2); }
  { const cuuint32_t b2[3] = {64, 64, 2}, b1[3] = {64, 64, 1};
    { cuuint64_t d[3] = {64, DM, 48}, s[2] = {3 * DM * 2, 128}; encode(fn, &P.map[M_WKV], wqkv, 3, d, s, b2); encode(fn, &P.map[M_WQ], wqkv, 3, d, s, b1); }
    { cuuint64_t d[3] = {64, DM, 16}, s[2] = {DM * 2, 128}; encode(fn, &P.map[M_WO], wo, 3, d, s, b1); }
    { cuuint64_t d[3] = {64, FF, 16}, s[2] = {DM * 2, 128}; encode(fn, &P.map[M_W2], w2, 3, d, s, b1); }
    { cuuint64_t d[3] = {64, DM, FF / 64}, s[2] = {FF * 2, 128};
      encode(fn, &P.map[M_W1], w1, 3, d, s, b2); encode(fn, &P.map[M_W3], w3, 3, d, s, b2);
      encode(fn, &P.map[M_W1H], w1, 3, d, s, b1); encode(fn, &P.map[M_W3H], w3, 3, d, s, b1); }
  }
  P.scratch = scr; P.x = x; P.wqkv = wqkv; P.wo = wo; P.w2 = w2;
  int dev = 0, sms = 0;
  cudaGetDevice(&dev);
  cudaDeviceGetAttribute(&sms, cudaDevAttrMultiProcessorCount, dev);
  P.use_smid = (sms == 132);
  cudaFuncSetAttribute(fused_kernel, cudaFuncAttributeMaxDynamicSharedMemorySize, SM_ALLOC);
  fused_kernel<<<132, 384, SM_ALLOC>>>(P);
}
```

```cpp
#include <cuda_runtime.h>
#include <cuda_bf16.h>
#include <cuda.h>
#include <stdint.h>
#include <math.h>

namespace {

constexpr int SEQ = 2048, DM = 1024, FF = 3584;
constexpr float LN_EPS = 1e-5f;
constexpr float LOG2E = 1.4426950408889634f;

constexpr uint32_t G_BLOCK = 2u << 20;
constexpr uint32_t G_H = 0;
constexpr uint32_t G_XA = G_H + 128 * FF * 2;
constexpr uint32_t G_O = G_XA + 128 * DM * 2;
constexpr uint32_t G_STATS = G_O + 128 * DM * 2;
constexpr uint32_t G_FLAGS = G_STATS + 4 * 128 * 64;
static_assert(G_FLAGS + 4096 <= G_BLOCK, "");
constexpr uint32_t G_HALO = 16 * G_BLOCK;
constexpr uint32_t G_CS = G_HALO + 2 * 16 * 8 * 4096;
constexpr uint32_t G_EPOCH = G_CS + (3 * DM + 2 * FF) * 16;
__device__ __align__(1024) uint8_t g_scratch[18 * G_BLOCK];

enum { M_XIN, M_XIN64, M_XA_LD, M_XA_ST, M_H_LD, M_H_ST, M_OUT_LD, M_OUT_ST, M_WKV, M_WQ, M_WO, M_W1, M_W3, M_W1H, M_W3H, M_W2, M_COUNT };
struct alignas(64) Params {
  CUtensorMap map[M_COUNT];
  uint8_t* scratch;
  const __nv_bfloat16* x;
  const __nv_bfloat16* wqkv;
  const __nv_bfloat16* wo;
  const __nv_bfloat16* w2;
  int use_smid;
};

constexpr uint32_t PAGE = 16384, NPAGE = 12;
constexpr uint32_t SM_STAGE = NPAGE * PAGE;
constexpr uint32_t SM_BAR = SM_STAGE + 2 * PAGE;
constexpr uint32_t SM_CS = SM_BAR + 256;
constexpr uint32_t SM_TOTAL = SM_CS + 1536;
constexpr uint32_t SM_ALLOC = SM_TOTAL;
static_assert(SM_ALLOC <= 232448, "shared memory");
constexpr uint32_t BAR_FULL = SM_BAR, BAR_EMPTY = SM_BAR + 64, BAR_SFULL = SM_BAR + 128;
constexpr uint32_t BAR_XFULL = SM_BAR + 160, BAR_CSE = SM_BAR + 168;
constexpr uint32_t BAR_SEMPTY = SM_BAR + 176, BAR_CSF = SM_BAR + 184, BAR_XIN = SM_BAR + 200;
constexpr uint32_t BAR_CLR = SM_BAR + 240, BAR_TAG = SM_BAR + 216, SM_ROLE = SM_BAR + 224, SM_TAG = SM_BAR + 228, SM_SEEN = SM_BAR + 232;
enum { EV_XA, EV_XA2, EV_H0, EV_H3, EV_H1, EV_H2, EV_XB, EV_XB2, EV_N };

#define WO_HOLD 4
struct Sched { uint32_t pat[14]; uint32_t page0[14]; bool ok; };
constexpr int seg_steps(int seg) { return seg == 0 || seg == 3 ? 18 : seg == 1 || seg == 4 ? 14 : seg == 2 ? 9 : seg == 5 ? 32 : 56; }
constexpr int step_pages(int seg, int i) {
  return seg == 0 || seg == 3 ? (i < 2 ? 2 : i < 4 ? 1 : 3) : seg == 5 ? 3 : 2;
}
constexpr Sched make_sched() {
  Sched s = {};
  int owner[NPAGE] = {-1, -1, -1, -1, -1, -1, -1, -1, -1, -1, -1, -1};
  int n = 0, tail = 0, page = 0;
  s.ok = true;
  for (int sg = 0; sg < 14; sg++) {
    const int seg = sg % 7;
    if (seg == 5) page = (page + 2) / 3 * 3 % NPAGE;
    if (seg == 0 || seg == 3) page = (page + 5) / 6 * 6 % NPAGE;
    s.page0[sg] = page;
    for (int i = 0; i < seg_steps(seg); i++) {
      const int p = step_pages(seg, i);
      if (page + p > (int)NPAGE) { s.ok = false; return s; }
      int need = n - 8;
      for (int q = 0; q < p; q++) { if (owner[page + q] > need) need = owner[page + q]; owner[page + q] = n; }
      if (seg == 3 && i < 4 && need < n - i - WO_HOLD + (i > 2 ? 2 : i)) need = n - i - WO_HOLD + (i > 2 ? 2 : i);
      int nw = need + 1 - tail; if (nw < 0) nw = 0;
      tail += nw;
      if (i < 16) s.pat[sg] |= (uint32_t)nw << (2 * i); else if (nw != 1) s.ok = false;
      if (nw > 3) s.ok = false;
      page = (page + p) % NPAGE; n++;
    }
  }
  for (int sg = 0; sg < 7; sg++) if (s.page0[sg] != s.page0[sg + 7] || (sg && s.pat[sg] != s.pat[sg + 7])) s.ok = false;
  return s;
}
constexpr Sched SCHED = make_sched();
static_assert(SCHED.ok && SCHED.page0[0] == 0 && SCHED.page0[3] == 0 && SCHED.page0[5] == 6 && (SCHED.pat[0] & 0xfff) == 0, "ring schedule");
template <int SEG> struct Pat { static constexpr uint32_t v = SCHED.pat[SEG]; };

__device__ __forceinline__ uint32_t smem_u32(const void* p) { return (uint32_t)__cvta_generic_to_shared(p); }
__device__ __forceinline__ void mbar_init(uint32_t bar, uint32_t cnt) { asm volatile("mbarrier.init.shared::cta.b64 [%0], %1;" :: "r"(bar), "r"(cnt)); }
__device__ __forceinline__ void mbar_expect_tx(uint32_t bar, uint32_t bytes) { asm volatile("mbarrier.arrive.expect_tx.shared::cta.b64 _, [%0], %1;" :: "r"(bar), "r"(bytes) : "memory"); }
__device__ __forceinline__ void mbar_arrive(uint32_t bar) { asm volatile("mbarrier.arrive.shared::cta.b64 _, [%0];" :: "r"(bar) : "memory"); }
__device__ __forceinline__ void mbar_wait(uint32_t bar, uint32_t parity) {
  asm volatile("{\n.reg .pred p;\n.reg .u32 n;\nmov.u32 n, 0;\nLAB_WAIT:\n"
               "mbarrier.try_wait.parity.shared::cta.b64 p, [%0], %1;\n@p bra LAB_DONE;\n"
               "add.u32 n, n, 1;\nsetp.lt.u32 p, n, 4194304;\n@p bra LAB_WAIT;\ntrap;\nLAB_DONE:\n}" :: "r"(bar), "r"(parity) : "memory");
}
__device__ __forceinline__ void mbar_wait_fast(uint32_t bar, uint32_t parity) {
  asm volatile("{\n.reg .pred p;\nLAB_WAIT:\nmbarrier.try_wait.parity.shared::cta.b64 p, [%0], %1;\n@!p bra LAB_WAIT;\n}" :: "r"(bar), "r"(parity) : "memory");
}
__device__ __forceinline__ void spin_check(uint32_t n) { asm volatile("{\n.reg .pred p;\nsetp.ge.u32 p, %0, 4194304;\n@p st.volatile.global.u32 [%1], %0;\n}" :: "r"(n), "l"(0ull)); }
__device__ __forceinline__ void tma_ld3(uint32_t dst, const CUtensorMap* m, uint32_t bar, int c0, int c1, int c2) {
  asm volatile("cp.async.bulk.tensor.3d.shared::cluster.global.mbarrier::complete_tx::bytes [%0], [%1, {%3, %4, %5}], [%2];" :: "r"(dst), "l"(m), "r"(bar), "r"(c0), "r"(c1), "r"(c2) : "memory");
}
__device__ __forceinline__ void tma_ld3_mc(uint32_t dst, const CUtensorMap* m, uint32_t bar, int c0, int c1, int c2, uint16_t mask) {
  asm volatile("cp.async.bulk.tensor.3d.shared::cluster.global.mbarrier::complete_tx::bytes.multicast::cluster [%0], [%1, {%3, %4, %5}], [%2], %6;"
               :: "r"(dst), "l"(m), "r"(bar), "r"(c0), "r"(c1), "r"(c2), "h"(mask) : "memory");
}
__device__ __forceinline__ uint32_t mapa(uint32_t addr, uint32_t cta) { uint32_t r; asm("mapa.shared::cluster.u32 %0, %1, %2;" : "=r"(r) : "r"(addr), "r"(cta)); return r; }
__device__ __forceinline__ void mbar_arrive_cluster(uint32_t bar) { asm volatile("mbarrier.arrive.shared::cluster.b64 _, [%0];" :: "r"(bar) : "memory"); }
__device__ __forceinline__ void tma_st3(const CUtensorMap* m, uint32_t src, int c0, int c1, int c2) {
  asm volatile("cp.async.bulk.tensor.3d.global.shared::cta.bulk_group [%0, {%2, %3, %4}], [%1];" :: "l"(m), "r"(src), "r"(c0), "r"(c1), "r"(c2) : "memory");
}
__device__ __forceinline__ void bulk_commit() { asm volatile("cp.async.bulk.commit_group;" ::: "memory"); }
template <int N> __device__ __forceinline__ void bulk_wait() { asm volatile("cp.async.bulk.wait_group %0;" :: "n"(N) : "memory"); }
__device__ __forceinline__ void fence_async_smem() { asm volatile("fence.proxy.async.shared::cta;" ::: "memory"); }
__device__ __forceinline__ void fence_async_global() { asm volatile("fence.proxy.async.global;" ::: "memory"); }
__device__ __forceinline__ bool elect_one() { uint32_t p; asm volatile("{\n.reg .pred P;\nelect.sync _|P, 0xffffffff;\nselp.u32 %0, 1, 0, P;\n}" : "=r"(p)); return p; }
__device__ __forceinline__ void prefetch_map(const CUtensorMap* m) { asm volatile("prefetch.tensormap [%0];" :: "l"(m) : "memory"); }
__device__ __forceinline__ void prefetch_l2(const void* p, uint32_t bytes) { asm volatile("cp.async.bulk.prefetch.L2.global [%0], %1;" :: "l"(p), "r"(bytes) : "memory"); }
__device__ __forceinline__ void wgmma_fence() { asm volatile("wgmma.fence.sync.aligned;" ::: "memory"); }
__device__ __forceinline__ void wgmma_commit() { asm volatile("wgmma.commit_group.sync.aligned;" ::: "memory"); }
template <int N> __device__ __forceinline__ void wgmma_wait() { asm volatile("wgmma.wait_group.sync.aligned %0;" :: "n"(N) : "memory"); }
__device__ __forceinline__ uint32_t desc_lo(uint32_t addr, uint32_t lbo) { return ((addr & 0x3FFFF) >> 4) | ((lbo >> 4) << 16); }
__device__ __forceinline__ uint64_t desc64(uint32_t lo) { uint64_t r; asm("mov.b64 %0, {%1, %2};" : "=l"(r) : "r"(lo), "r"(0x40000040u)); return r; }
__device__ __forceinline__ void bar_sync(int id, int n) { asm volatile("bar.sync %0, %1;" :: "r"(id), "r"(n) : "memory"); }
__device__ __forceinline__ uint32_t pack_bf16(float lo, float hi) { uint32_t r; asm("cvt.rn.bf16x2.f32 %0, %1, %2;" : "=r"(r) : "f"(hi), "f"(lo)); return r; }
__device__ __forceinline__ float bf_lo(uint32_t v) { return __uint_as_float(v << 16); }
__device__ __forceinline__ float bf_hi(uint32_t v) { return __uint_as_float(v & 0xffff0000u); }
__device__ __forceinline__ float ex2(float x) { float r; asm("ex2.approx.ftz.f32 %0, %1;" : "=f"(r) : "f"(x)); return r; }
__device__ __forceinline__ float rcp(float x) { float r; asm("rcp.approx.ftz.f32 %0, %1;" : "=f"(r) : "f"(x)); return r; }
__device__ __forceinline__ void stsm4(uint32_t a, uint32_t r0, uint32_t r1, uint32_t r2, uint32_t r3) {
  asm volatile("stmatrix.sync.aligned.m8n8.x4.shared.b16 [%0], {%1, %2, %3, %4};" :: "r"(a), "r"(r0), "r"(r1), "r"(r2), "r"(r3) : "memory");
}
__device__ __forceinline__ void ldsm4(uint32_t a, uint32_t& r0, uint32_t& r1, uint32_t& r2, uint32_t& r3) {
  asm volatile("ldmatrix.sync.aligned.m8n8.x4.shared.b16 {%0, %1, %2, %3}, [%4];" : "=r"(r0), "=r"(r1), "=r"(r2), "=r"(r3) : "r"(a) : "memory");
}
__device__ __forceinline__ uint32_t movm(uint32_t v) { uint32_t r; asm volatile("movmatrix.sync.aligned.m8n8.trans.b16 %0, %1;" : "=r"(r) : "r"(v)); return r; }
__device__ __forceinline__ void sts128(uint32_t a, uint32_t r0, uint32_t r1, uint32_t r2, uint32_t r3) {
  asm volatile("st.shared.v4.b32 [%0], {%1, %2, %3, %4};" :: "r"(a), "r"(r0), "r"(r1), "r"(r2), "r"(r3) : "memory");
}
__device__ __forceinline__ void lds128(uint32_t a, uint32_t& r0, uint32_t& r1, uint32_t& r2, uint32_t& r3) {
  asm volatile("ld.shared.v4.b32 {%0, %1, %2, %3}, [%4];" : "=r"(r0), "=r"(r1), "=r"(r2), "=r"(r3) : "r"(a) : "memory");
}
__device__ __forceinline__ void sts32f(uint32_t a, float v) { asm volatile("st.shared.f32 [%0], %1;" :: "r"(a), "f"(v) : "memory"); }
__device__ __forceinline__ void mma16816(float (&d)[4], uint32_t a0, uint32_t a1, uint32_t a2, uint32_t a3, uint32_t b0, uint32_t b1, const float (&c)[4]) {
  asm("mma.sync.aligned.m16n8k16.row.col.f32.bf16.bf16.f32 {%0, %1, %2, %3}, {%4, %5, %6, %7}, {%8, %9}, {%10, %11, %12, %13};"
      : "=f"(d[0]), "=f"(d[1]), "=f"(d[2]), "=f"(d[3]) : "r"(a0), "r"(a1), "r"(a2), "r"(a3), "r"(b0), "r"(b1), "f"(c[0]), "f"(c[1]), "f"(c[2]), "f"(c[3]));
}
__device__ __forceinline__ void mma1688(float (&d)[4], uint32_t a0, uint32_t a1, uint32_t b0, const float (&c)[4]) {
  asm("mma.sync.aligned.m16n8k8.row.col.f32.bf16.bf16.f32 {%0, %1, %2, %3}, {%4, %5}, {%6}, {%7, %8, %9, %10};"
      : "=f"(d[0]), "=f"(d[1]), "=f"(d[2]), "=f"(d[3]) : "r"(a0), "r"(a1), "r"(b0), "f"(c[0]), "f"(c[1]), "f"(c[2]), "f"(c[3]));
}
__device__ __forceinline__ void mma16816z(float (&d)[4], uint32_t a0, uint32_t a1, uint32_t a2, uint32_t a3, uint32_t b0, uint32_t b1) {
  asm("mma.sync.aligned.m16n8k16.row.col.f32.bf16.bf16.f32 {%0, %1, %2, %3}, {%4, %5, %6, %7}, {%8, %9}, {0f00000000, 0f00000000, 0f00000000, 0f00000000};"
      : "=f"(d[0]), "=f"(d[1]), "=f"(d[2]), "=f"(d[3]) : "r"(a0), "r"(a1), "r"(a2), "r"(a3), "r"(b0), "r"(b1));
}
__device__ __forceinline__ void mma1688z(float (&d)[4], uint32_t a0, uint32_t a1, uint32_t b0) {
  asm("mma.sync.aligned.m16n8k8.row.col.f32.bf16.bf16.f32 {%0, %1, %2, %3}, {%4, %5}, {%6}, {0f00000000, 0f00000000, 0f00000000, 0f00000000};"
      : "=f"(d[0]), "=f"(d[1]), "=f"(d[2]), "=f"(d[3]) : "r"(a0), "r"(a1), "r"(b0));
}
__device__ __forceinline__ uint32_t bar_sync_zero(int id, int n) {
  uint32_t r;
  asm volatile("{\n.reg .pred p;\nsetp.eq.u32 p, %1, 0;\nbarrier.cta.red.popc.aligned.u32 %0, %1, %2, p;\n}" : "=r"(r) : "r"(id), "r"(n) : "memory");
  return r;
}
__device__ __forceinline__ uint32_t late_zero(uint32_t zm) { uint32_t c; asm volatile("mov.u32 %0, %%clock;" : "=r"(c) :: "memory"); return c & zm; }
#define CLR_NS 10
#define WO_ORDER 1
#define EARLY_PF 1
#define CS_START 8
__device__ __forceinline__ void st_b128(uint4* p, uint32_t a, uint32_t b, uint32_t c, uint32_t d) {
  asm volatile("{\n.reg .b128 t;\n.reg .b64 lo, hi;\nmov.b64 lo, {%0, %1};\nmov.b64 hi, {%2, %3};\nmov.b128 t, {lo, hi};\nst.relaxed.gpu.global.b128 [%4], t;\n}"
               :: "r"(a), "r"(b), "r"(c), "r"(d), "l"(p) : "memory");
}
__device__ __forceinline__ uint32_t pkt_head(uint32_t a) { return a ? a : 0x8000u; }
__device__ __forceinline__ void gen_store(uint4* p, uint32_t a, uint32_t b, uint32_t c, uint32_t d) {
  asm volatile("{\n.reg .b128 t;\n.reg .b64 lo, hi;\nmov.b64 lo, {%0, %1};\nmov.b64 hi, {%2, %3};\nmov.b128 t, {lo, hi};\nst.relaxed.gpu.b128 [%4], t;\n}"
               :: "r"(a), "r"(b), "r"(c), "r"(d), "l"(p) : "memory");
}
__device__ __forceinline__ void gen_load(const uint4* p, uint32_t* v) {
  asm volatile("{\n.reg .b128 t;\n.reg .b64 lo, hi;\nld.relaxed.gpu.b128 t, [%4];\nmov.b128 {lo, hi}, t;\nmov.b64 {%0, %1}, lo;\nmov.b64 {%2, %3}, hi;\n}"
               : "=r"(v[0]), "=r"(v[1]), "=r"(v[2]), "=r"(v[3]) : "l"(p) : "memory");
}
__device__ __forceinline__ void pkt_load(const uint4* p, uint32_t* v) {
  asm volatile("{\n.reg .b128 t;\n.reg .b64 lo, hi;\nld.relaxed.gpu.global.b128 t, [%4];\nmov.b128 {lo, hi}, t;\nmov.b64 {%0, %1}, lo;\nmov.b64 {%2, %3}, hi;\n}"
               : "=r"(v[0]), "=r"(v[1]), "=r"(v[2]), "=r"(v[3]) : "l"(p) : "memory");
}
__device__ __forceinline__ uint32_t ld_relaxed(const uint32_t* p) { uint32_t v; asm volatile("ld.relaxed.gpu.global.u32 %0, [%1];" : "=r"(v) : "l"(p) : "memory"); return v; }
__device__ __forceinline__ uint4 ld_relaxed4(const void* p) { uint4 v; asm volatile("ld.relaxed.gpu.global.v4.u32 {%0, %1, %2, %3}, [%4];" : "=r"(v.x), "=r"(v.y), "=r"(v.z), "=r"(v.w) : "l"(p) : "memory"); return v; }
__device__ __forceinline__ void st_relaxed(uint32_t* p, uint32_t v) { asm volatile("st.relaxed.gpu.global.u32 [%0], %1;" :: "l"(p), "r"(v) : "memory"); }
__device__ __forceinline__ void st_relaxed2(void* p, uint32_t a, uint32_t b) { asm volatile("st.relaxed.gpu.global.v2.u32 [%0], {%1, %2};" :: "l"(p), "r"(a), "r"(b) : "memory"); }
__device__ __forceinline__ void red_release(uint32_t* p, uint32_t v) { asm volatile("red.release.gpu.global.add.u32 [%0], %1;" :: "l"(p), "r"(v) : "memory"); }
__device__ __forceinline__ uint32_t tagf(float v, uint32_t tag) { return (__float_as_uint(v) & ~15u) | (tag & 15u); }
__device__ __forceinline__ bool tag_ok4(const uint4& v, uint32_t tag) { return (((v.x ^ tag) | (v.y ^ tag) | (v.z ^ tag) | (v.w ^ tag)) & 15u) == 0; }
__device__ __forceinline__ float untag(uint32_t v) { return __uint_as_float(v & ~15u); }
template <typename T> __device__ __forceinline__ T* ptr_add(T* p, uint32_t bytes) {
  uint64_t r;
  asm("{\n.reg .u32 lo, hi;\nmov.b64 {lo, hi}, %1;\nadd.cc.u32 lo, lo, %2;\naddc.u32 hi, hi, 0;\nmov.b64 %0, {lo, hi};\n}" : "=l"(r) : "l"(p), "r"(bytes));
  return (T*)r;
}
#define TL(who, slot) do {} while (0)
#define TLC(slot) do {} while (0)
#define ST(who, n) do {} while (0)
#define AP(i) do {} while (0)
#define SP(v) do {} while (0)
#define TLG(slot) do {} while (0)
#define STA() do {} while (0)
#define STB(n) do {} while (0)

__device__ __forceinline__ void wgmma_n128(float (&d)[64], uint64_t da, uint64_t db, int scale_d) {
  asm volatile("{\n.reg .pred p;\nsetp.ne.b32 p, %66, 0;\n"
    "wgmma.mma_async.sync.aligned.m64n128k16.f32.bf16.bf16 "
    "{%0, %1, %2, %3, %4, %5, %6, %7, %8, %9, %10, %11, %12, %13, %14, %15, "
    "%16, %17, %18, %19, %20, %21, %22, %23, %24, %25, %26, %27, %28, %29, %30, %31, "
    "%32, %33, %34, %35, %36, %37, %38, %39, %40, %41, %42, %43, %44, %45, %46, %47, "
    "%48, %49, %50, %51, %52, %53, %54, %55, %56, %57, %58, %59, %60, %61, %62, %63}, "
    "%64, %65, p, 1, 1, 0, 1;\n}\n"
    : "+f"(d[0]), "+f"(d[1]), "+f"(d[2]), "+f"(d[3]), "+f"(d[4]), "+f"(d[5]), "+f"(d[6]), "+f"(d[7]),
      "+f"(d[8]), "+f"(d[9]), "+f"(d[10]), "+f"(d[11]), "+f"(d[12]), "+f"(d[13]), "+f"(d[14]), "+f"(d[15]),
      "+f"(d[16]), "+f"(d[17]), "+f"(d[18]), "+f"(d[19]), "+f"(d[20]), "+f"(d[21]), "+f"(d[22]), "+f"(d[23]),
      "+f"(d[24]), "+f"(d[25]), "+f"(d[26]), "+f"(d[27]), "+f"(d[28]), "+f"(d[29]), "+f"(d[30]), "+f"(d[31]),
      "+f"(d[32]), "+f"(d[33]), "+f"(d[34]), "+f"(d[35]), "+f"(d[36]), "+f"(d[37]), "+f"(d[38]), "+f"(d[39]),
      "+f"(d[40]), "+f"(d[41]), "+f"(d[42]), "+f"(d[43]), "+f"(d[44]), "+f"(d[45]), "+f"(d[46]), "+f"(d[47]),
      "+f"(d[48]), "+f"(d[49]), "+f"(d[50]), "+f"(d[51]), "+f"(d[52]), "+f"(d[53]), "+f"(d[54]), "+f"(d[55]),
      "+f"(d[56]), "+f"(d[57]), "+f"(d[58]), "+f"(d[59]), "+f"(d[60]), "+f"(d[61]), "+f"(d[62]), "+f"(d[63])
    : "l"(da), "l"(db), "r"(scale_d));
}
__device__ __forceinline__ void wgmma_n256(float (&d)[128], uint64_t da, uint64_t db, int scale_d) {
  asm volatile("{\n.reg .pred p;\nsetp.ne.b32 p, %130, 0;\n"
    "wgmma.mma_async.sync.aligned.m64n256k16.f32.bf16.bf16 "
    "{%0, %1, %2, %3, %4, %5, %6, %7, %8, %9, %10, %11, %12, %13, %14, %15, "
    "%16, %17, %18, %19, %20, %21, %22, %23, %24, %25, %26, %27, %28, %29, %30, %31, "
    "%32, %33, %34, %35, %36, %37, %38, %39, %40, %41, %42, %43, %44, %45, %46, %47, "
    "%48, %49, %50, %51, %52, %53, %54, %55, %56, %57, %58, %59, %60, %61, %62, %63, "
    "%64, %65, %66, %67, %68, %69, %70, %71, %72, %73, %74, %75, %76, %77, %78, %79, "
    "%80, %81, %82, %83, %84, %85, %86, %87, %88, %89, %90, %91, %92, %93, %94, %95, "
    "%96, %97, %98, %99, %100, %101, %102, %103, %104, %105, %106, %107, %108, %109, %110, %111, "
    "%112, %113, %114, %115, %116, %117, %118, %119, %120, %121, %122, %123, %124, %125, %126, %127}, "
    "%128, %129, p, 1, 1, 0, 1;\n}\n"
    : "+f"(d[0]), "+f"(d[1]), "+f"(d[2]), "+f"(d[3]), "+f"(d[4]), "+f"(d[5]), "+f"(d[6]), "+f"(d[7]),
      "+f"(d[8]), "+f"(d[9]), "+f"(d[10]), "+f"(d[11]), "+f"(d[12]), "+f"(d[13]), "+f"(d[14]), "+f"(d[15]),
      "+f"(d[16]), "+f"(d[17]), "+f"(d[18]), "+f"(d[19]), "+f"(d[20]), "+f"(d[21]), "+f"(d[22]), "+f"(d[23]),
      "+f"(d[24]), "+f"(d[25]), "+f"(d[26]), "+f"(d[27]), "+f"(d[28]), "+f"(d[29]), "+f"(d[30]), "+f"(d[31]),
      "+f"(d[32]), "+f"(d[33]), "+f"(d[34]), "+f"(d[35]), "+f"(d[36]), "+f"(d[37]), "+f"(d[38]), "+f"(d[39]),
      "+f"(d[40]), "+f"(d[41]), "+f"(d[42]), "+f"(d[43]), "+f"(d[44]), "+f"(d[45]), "+f"(d[46]), "+f"(d[47]),
      "+f"(d[48]), "+f"(d[49]), "+f"(d[50]), "+f"(d[51]), "+f"(d[52]), "+f"(d[53]), "+f"(d[54]), "+f"(d[55]),
      "+f"(d[56]), "+f"(d[57]), "+f"(d[58]), "+f"(d[59]), "+f"(d[60]), "+f"(d[61]), "+f"(d[62]), "+f"(d[63]),
      "+f"(d[64]), "+f"(d[65]), "+f"(d[66]), "+f"(d[67]), "+f"(d[68]), "+f"(d[69]), "+f"(d[70]), "+f"(d[71]),
      "+f"(d[72]), "+f"(d[73]), "+f"(d[74]), "+f"(d[75]), "+f"(d[76]), "+f"(d[77]), "+f"(d[78]), "+f"(d[79]),
      "+f"(d[80]), "+f"(d[81]), "+f"(d[82]), "+f"(d[83]), "+f"(d[84]), "+f"(d[85]), "+f"(d[86]), "+f"(d[87]),
      "+f"(d[88]), "+f"(d[89]), "+f"(d[90]), "+f"(d[91]), "+f"(d[92]), "+f"(d[93]), "+f"(d[94]), "+f"(d[95]),
      "+f"(d[96]), "+f"(d[97]), "+f"(d[98]), "+f"(d[99]), "+f"(d[100]), "+f"(d[101]), "+f"(d[102]), "+f"(d[103]),
      "+f"(d[104]), "+f"(d[105]), "+f"(d[106]), "+f"(d[107]), "+f"(d[108]), "+f"(d[109]), "+f"(d[110]), "+f"(d[111]),
      "+f"(d[112]), "+f"(d[113]), "+f"(d[114]), "+f"(d[115]), "+f"(d[116]), "+f"(d[117]), "+f"(d[118]), "+f"(d[119]),
      "+f"(d[120]), "+f"(d[121]), "+f"(d[122]), "+f"(d[123]), "+f"(d[124]), "+f"(d[125]), "+f"(d[126]), "+f"(d[127])
    : "l"(da), "l"(db), "r"(scale_d));
}
__device__ __forceinline__ void wgmma_rs_n128(float (&d)[64], const uint32_t* a, uint64_t db, int scale_d) {
  asm volatile("{\n.reg .pred p;\nsetp.ne.b32 p, %69, 0;\n"
    "wgmma.mma_async.sync.aligned.m64n128k16.f32.bf16.bf16 "
    "{%0, %1, %2, %3, %4, %5, %6, %7, %8, %9, %10, %11, %12, %13, %14, %15, "
    "%16, %17, %18, %19, %20, %21, %22, %23, %24, %25, %26, %27, %28, %29, %30, %31, "
    "%32, %33, %34, %35, %36, %37, %38, %39, %40, %41, %42, %43, %44, %45, %46, %47, "
    "%48, %49, %50, %51, %52, %53, %54, %55, %56, %57, %58, %59, %60, %61, %62, %63}, "
    "{%64, %65, %66, %67}, %68, p, 1, 1, 1;\n}\n"
    : "+f"(d[0]), "+f"(d[1]), "+f"(d[2]), "+f"(d[3]), "+f"(d[4]), "+f"(d[5]), "+f"(d[6]), "+f"(d[7]),
      "+f"(d[8]), "+f"(d[9]), "+f"(d[10]), "+f"(d[11]), "+f"(d[12]), "+f"(d[13]), "+f"(d[14]), "+f"(d[15]),
      "+f"(d[16]), "+f"(d[17]), "+f"(d[18]), "+f"(d[19]), "+f"(d[20]), "+f"(d[21]), "+f"(d[22]), "+f"(d[23]),
      "+f"(d[24]), "+f"(d[25]), "+f"(d[26]), "+f"(d[27]), "+f"(d[28]), "+f"(d[29]), "+f"(d[30]), "+f"(d[31]),
      "+f"(d[32]), "+f"(d[33]), "+f"(d[34]), "+f"(d[35]), "+f"(d[36]), "+f"(d[37]), "+f"(d[38]), "+f"(d[39]),
      "+f"(d[40]), "+f"(d[41]), "+f"(d[42]), "+f"(d[43]), "+f"(d[44]), "+f"(d[45]), "+f"(d[46]), "+f"(d[47]),
      "+f"(d[48]), "+f"(d[49]), "+f"(d[50]), "+f"(d[51]), "+f"(d[52]), "+f"(d[53]), "+f"(d[54]), "+f"(d[55]),
      "+f"(d[56]), "+f"(d[57]), "+f"(d[58]), "+f"(d[59]), "+f"(d[60]), "+f"(d[61]), "+f"(d[62]), "+f"(d[63])
    : "r"(a[0]), "r"(a[1]), "r"(a[2]), "r"(a[3]), "l"(db), "r"(scale_d));
}

template <int BN> __device__ __forceinline__ void wgmma(float (&d)[BN / 2], uint64_t a, uint64_t b, int s) {
  if constexpr (BN == 128) wgmma_n128(d, a, b, s);
  else wgmma_n256(d, a, b, s);
}

template <int N> __device__ __forceinline__ void acc_fence(float* a) {
#pragma unroll
  for (int i = 0; i < N; i++) asm volatile("" : "+f"(a[i]) :: "memory");
}

#define SELECT8(a, f) do { \
  if ((a) & 4) { if ((a) & 2) { if ((a) & 1) f(7); else f(6); } else { if ((a) & 1) f(5); else f(4); } } \
  else { if ((a) & 2) { if ((a) & 1) f(3); else f(2); } else { if ((a) & 1) f(1); else f(0); } } } while (0)
__device__ __forceinline__ uint32_t lane_now() { uint32_t l; asm volatile("mov.u32 %0, %%laneid;" : "=r"(l)); return l; }

struct Prod {
  uint32_t sb, n, tail, addr, pat, ready;
  uint32_t rank, flip; uint16_t mask;
  __device__ __forceinline__ void load_b(uint32_t dst, uint32_t half, const CUtensorMap* m, uint32_t mstep, uint32_t fb, int k, int ch, int cstep) {
    uint32_t h = rank;
    do { tma_ld3_mc(dst + h * half, ptr_add(m, h * mstep), fb, 0, k * 64, ch + h * cstep, mask); h ^= flip; } while (h != rank);
  }
  __device__ __forceinline__ void load_wide(const Params& P, int ffn, uint32_t dst, uint32_t fb, int k, int ch) {
    load_b(dst, PAGE, &P.map[ffn ? M_W1 : M_WKV], ffn ? 128 : 0, fb, k, ffn ? ch : ch + 16, ffn ? 0 : 16);
  }
  __device__ __forceinline__ void load_narrow(const Params& P, int ffn, uint32_t dst, uint32_t fb, int k, int j) {
    load_b(dst, 8192, &P.map[ffn ? M_W1H : M_WQ], ffn ? 128 : 0, fb, k, ffn ? 48 + j : 2 * j, ffn ? 0 : 1);
  }
  __device__ __forceinline__ void finish() {
#pragma unroll 1
    for (; tail < n; tail++) mbar_wait(sb + BAR_EMPTY + ((tail & 7) << 3), (tail >> 3) & 1);
  }
  template <int PAGES> __device__ __forceinline__ uint32_t acquire(uint32_t& fb) {
    uint32_t nw = pat & 3; pat = (pat >> 2) | 0x40000000u;
#pragma unroll 1
    for (; nw; nw--) { mbar_wait(sb + BAR_EMPTY + ((tail & 7) << 3), (tail >> 3) & 1); tail++; }
    ST(4, n);
    fb = sb + BAR_FULL + ((n & 7) << 3);
    mbar_expect_tx(fb, PAGES * PAGE);
    const uint32_t a = sb + addr;
    addr += PAGES * PAGE; if (addr >= NPAGE * PAGE) addr = 0;
    n++;
    return a;
  }
  const uint32_t* flag; uint32_t base, seen;
  __device__ __forceinline__ void acquire_fence() { asm volatile("fence.acquire.gpu;" ::: "memory"); fence_async_global(); }
  __device__ __forceinline__ void next() {
    uint32_t v, spins = 0;
    seen++;
    do { asm volatile("ld.acquire.cta.shared.u32 %0, [%1];" : "=r"(v) : "r"(sb + SM_SEEN) : "memory"); spin_check(++spins >> 4); } while (v < seen);
    fence_async_global();
  }
  __device__ __forceinline__ void need(uint32_t mask) {
    if ((ready & mask) != mask) {
      uint32_t spins = 0;
      do { ready = ld_relaxed(flag) - base; spin_check(++spins); } while ((ready & mask) != mask);
      acquire_fence();
    }
    ST(5, n - 1);
  }
};

struct Cons {
  uint32_t sb, n, off, prev;
  uint32_t ebar;
  uint32_t da0, db0;
  int lane;
  template <int PAGES> __device__ __forceinline__ void advance() {
    n++; off += PAGES << 10; if (off >= (NPAGE << 10)) off = 0;
    asm volatile("" : "+r"(n), "+r"(off));
  }
  template <int BN, int PAGES> __device__ __forceinline__ void step_ab(float (&acc)[BN / 2], uint32_t da, uint32_t db, int accumulate) {
    STA();
    mbar_wait_fast(sb + BAR_FULL + ((n & 7) << 3), (n >> 3) & 1);
    STB(n);
    const uint64_t da64 = desc64(da), db64 = desc64(db);
    wgmma_fence();
#pragma unroll
    for (int k = 0; k < 4; k++) wgmma<BN>(acc, da64 + 2 * k, db64 + 128 * k, k ? 1 : accumulate);
    wgmma_commit();
    wgmma_wait<1>();
    if (prev && lane < 2) mbar_arrive_cluster(ebar + prev);
    prev = 64 + ((n & 7) << 3);
    advance<PAGES>();
  }
  template <int BN> __device__ __forceinline__ void step(float (&acc)[BN / 2], int accumulate = 1) { step_ab<BN, BN / 128 + 1>(acc, da0 + off, db0 + 1024 + off, accumulate); }
  template <int BN> __device__ __forceinline__ void step_own(float (&acc)[BN / 2], uint32_t da, int accumulate) { step_ab<BN, BN / 128>(acc, da, db0 + off, accumulate); }
  __device__ __forceinline__ void wait_full(uint32_t i) { mbar_wait_fast(sb + BAR_FULL + (((n + i) & 7) << 3), ((n + i) >> 3) & 1); }
  __device__ __forceinline__ void issue_rs2(float (&acc)[64], uint32_t (&a0)[16], uint32_t (&a1)[16]) {
    STA(); STB(n);
    const uint64_t db64 = desc64(db0 + off);
    wgmma_fence();
#pragma unroll
    for (int k = 0; k < 4; k++) wgmma_rs_n128(acc, a0 + 4 * k, db64 + 128 * k, 1);
#pragma unroll
    for (int k = 0; k < 4; k++) wgmma_rs_n128(acc, a1 + 4 * k, db64 + 1024 + 128 * k, 1);
    wgmma_commit();
    prev = 64 + ((n & 7) << 3);
    advance<2>();
  }
  template <int BN> __device__ __forceinline__ void steps(float (&acc)[BN / 2], int cnt) {
#pragma unroll 1
    do { step<BN>(acc); } while (--cnt > 0);
  }
  __device__ __forceinline__ void drain() {
    wgmma_wait<0>();
    if (lane < 2) mbar_arrive_cluster(ebar + prev);
    prev = 0;
  }
};

#define MAPPING 2
__device__ __forceinline__ uint32_t role_of_sm(uint32_t smid) {
  const uint32_t t = smid >> 1;
  uint32_t q, i;
  if (t < 32) { q = t & 7; i = t >> 3; }
  else if (t < 60) { const uint32_t u = t - 32, d = (u * 37) >> 8; q = 1 + u - d * 7; i = 4 + d; }
  else if (t < 62) return 128 + smid - 120;
  else { q = 0; i = t - 58; }
  return (q * 2 + (smid & 1)) * 8 + i;
}

template <typename T> __device__ __forceinline__ T* scratch(const Params& P, uint32_t off) { return (T*)ptr_add(P.scratch, off); }
__device__ __forceinline__ uint32_t* epoch_ptr(const Params& P) { uint32_t b; asm volatile("mov.u32 %0, %%ctaid.x;" : "=r"(b)); return scratch<uint32_t>(P, G_EPOCH + b * 4u); }

__device__ __forceinline__ int o_chunk(int s, int j) { const int hf = s >= 9, m = s - 2 - 7 * hf; return s < 2 ? 2 * j + s : 2 * (m == j ? 7 : m) + hf; }

__global__ void __cluster_dims__(2, 1, 1) __launch_bounds__(384, 1) fused_kernel(const __grid_constant__ Params P) {
  extern __shared__ __align__(1024) uint8_t smem_raw[];
  SP(0);
  const uint32_t sb = __shfl_sync(0xffffffffu, smem_u32(smem_raw), 0);
  const int warp = __shfl_sync(0xffffffffu, threadIdx.x >> 5, 0);
  const int lane = threadIdx.x & 31;
  if (warp == 7 && elect_one()) { prefetch_map(&P.map[M_XIN64]); prefetch_map(&P.map[M_WKV]); prefetch_map(&P.map[M_XIN]); }
  uint32_t role = blockIdx.x < 128 ? ((blockIdx.x >> 4) * 2 + (blockIdx.x & 1)) * 8 + ((blockIdx.x >> 1) & 7) : blockIdx.x;
  if (P.use_smid) { uint32_t smid; asm volatile("mov.u32 %0, %%smid;" : "=r"(smid)); role = role_of_sm(smid); }
  const bool spare = role >= 128;
  const int g = role >> 3, j = role & 7;
  uint32_t rank; asm("mov.u32 %0, %%cluster_ctarank;" : "=r"(rank));
  auto shared_b = [&]() {
    uint32_t peer;
    asm volatile("ld.shared::cluster.u32 %0, [%1];" : "=r"(peer) : "r"(mapa(sb + SM_ROLE, rank ^ 1)) : "memory");
    return !spare && peer < 128 && (peer & 7) == (uint32_t)j;
  };
  SP(1);

  if (warp >= 8) {
    asm volatile("setmaxnreg.dec.sync.aligned.u32 40;");
    if (elect_one()) {
      if (warp == 8) {
#pragma unroll
        for (int i = 0; i < 6; i++) mbar_init(sb + BAR_FULL + 8 * i, 1);
        mbar_init(sb + BAR_XIN, 1); mbar_init(sb + BAR_XIN + 8, 1);
      } else if (warp == 9) {
#pragma unroll
        for (int i = 0; i < 8; i++) mbar_init(sb + BAR_EMPTY + 8 * i, 16);
      } else if (warp == 10) {
#pragma unroll
        for (int i = 0; i < 4; i++) mbar_init(sb + BAR_SFULL + 8 * i, 4);
        mbar_init(sb + BAR_CLR, 1); mbar_init(sb + BAR_FULL + 48, 1); mbar_init(sb + BAR_FULL + 56, 1);
      } else {
        sts128(sb + SM_ROLE, role, 0, 0, 0);
        mbar_init(sb + BAR_TAG, 1); mbar_init(sb + BAR_XFULL, 8); mbar_init(sb + BAR_CSE, 8);
        mbar_init(sb + BAR_SEMPTY, 1); mbar_init(sb + BAR_CSF, 1); mbar_init(sb + BAR_CSF + 8, 2);
      }
      asm volatile("fence.mbarrier_init.release.cluster;\nfence.release.sync_restrict::shared::cta.cluster;" ::: "memory");
      fence_async_smem();
    }
    __syncwarp();
    SP(2);
    asm volatile("barrier.cluster.arrive.relaxed.aligned;" ::: "memory");
    if (warp == 8 && !spare) {
      if (elect_one()) {
        const int par = g & 1, row = (g >> 1) * 128;
#pragma unroll 1
        for (int s = 0; s < 2; s++) {
          const uint32_t xb = sb + BAR_XIN + 8 * s, fb = sb + BAR_FULL + 8 * s;
          mbar_expect_tx(xb, PAGE); mbar_expect_tx(fb, 2 * PAGE);
#pragma unroll
          for (int h = 0; h < 2; h++) tma_ld3(sb + SM_STAGE + h * PAGE + s * 8192, &P.map[M_XIN64], xb, s * 64, par, row + h * 64);
#pragma unroll
          for (int h = 0; h < 2; h++) tma_ld3(sb + (2 * s + h) * PAGE, &P.map[M_WKV], fb, 0, s * 64, 16 + 16 * h + 2 * j);
        }
#pragma unroll 1
        for (int s = 0; s < 2; s++) {
          const uint32_t fb = sb + BAR_FULL + 16 + 8 * s;
          mbar_expect_tx(fb, PAGE);
          tma_ld3(sb + (4 + s) * PAGE, &P.map[M_WKV], fb, 0, s * 64, 2 * j);
        }
#pragma unroll 1
        for (int s = 0; s < 2; s++) {
          const uint32_t fb = sb + BAR_FULL + 32 + 8 * s, a = sb + (6 + 3 * s) * PAGE;
          const int k = (j == 1 ? 4 : 2) + s;
          mbar_expect_tx(fb, 3 * PAGE);
          tma_ld3(a, &P.map[M_XIN], fb, k * 64, par, row);
#pragma unroll
          for (int h = 0; h < 2; h++) tma_ld3(a + PAGE + h * PAGE, &P.map[M_WKV], fb, 0, k * 64, 16 + 16 * h + 2 * j);
        }
        spin_check((sb & 1023) << 22);
      }
      __syncwarp();
    }
    SP(3);
    asm volatile("barrier.cluster.wait.acquire.aligned;" ::: "memory");
    SP(4);
    if (warp == 8) {
      if (elect_one()) {
        Prod p; p.sb = sb; p.n = 0; p.tail = 0; p.ready = 0; p.addr = 0;
        { const bool mc = shared_b(); p.rank = rank; p.flip = !mc; p.mask = mc ? 3 : 1 << rank; }
        uint32_t fb;
        if (spare) {
          p.pat = 0x55555000u;
#pragma unroll 1
          for (int r = -1; r < 7; r++) {
            const int ch = r < 0 ? 4 * j : ((r < 2 ? r : r == 2 ? 6 : r - 1) * 4 + j) * 2;
#pragma unroll 1
            for (int k = 0; k < 16; k++) { const uint32_t a = p.acquire<2>(fb); p.load_b(a, PAGE, &P.map[r < 0 ? M_WKV : M_W1], r < 0 ? 0 : 128, fb, k, ch, r < 0 ? 2 : 0); }
          }
        } else {
          p.seen = 0;
          SP(5);
#pragma unroll 1
          for (int hl = 0; hl < 4; hl++) {
            const int ffn = hl & 1;
            const CUtensorMap* xmap = &P.map[ffn ? M_XA_LD : hl ? M_OUT_LD : M_XIN];
            const int xpar = ffn ? g : g & 1, xrow = ffn ? 0 : (g >> 1) * 128;
            if (hl) {
              p.pat = ffn ? Pat<3>::v : Pat<7>::v; p.addr = 0;
#pragma unroll 1
              for (int s = 0; s < 2; s++) { const uint32_t a = p.acquire<2>(fb); p.load_wide(P, ffn, a, fb, 2 * j + s, 2 * j); }
#pragma unroll 1
              for (int s = 0; s < 2; s++) { const uint32_t a = p.acquire<1>(fb); p.load_narrow(P, ffn, a, fb, 2 * j + s, j); }
            } else { p.pat = (Pat<0>::v >> 12) | 0x55500000u; p.addr = 0; p.n = 6; }
            if (hl == 0) SP(6);
            uint32_t fb0 = 0;
#pragma unroll 1
            for (int m = hl ? 0 : 2; m < 14; m++) {
              const int hf = m >= 7, mm = m - 7 * hf, jj = mm == j ? 7 : mm;
              int k = 2 * jj + hf;
              if (hl == 0) {
                const int pr = (m >> 1) + 1;
                k = 2 * (j && pr == 2 ? j : pr == j ? 2 : pr) + (m & 1);
              }
              const uint32_t a = p.acquire<3>(fb);
              p.load_wide(P, ffn, a + PAGE, fb, k, 2 * j);
              if (hl) {
                if (m == 0) { fb0 = fb; continue; }
                if (m == 1) {
                  const int j0 = j ? 0 : 7;
                  p.flag = scratch<uint32_t>(P, g * G_BLOCK + G_FLAGS + (ffn ? (hl >> 1) * EV_N + EV_XA : EV_XB) * 128);
                  p.ready = 0; p.need((1u << j0) | (1u << j));
                  tma_ld3(a - 3 * PAGE, xmap, fb0, j0 * 128, xpar, xrow);
                }
                if (m < 7) p.need(1u << jj); else if (m == 7) p.next();
              }
              tma_ld3(a, xmap, fb, k * 64, xpar, xrow);
            }
            if (hl == 0) { mbar_wait(sb + BAR_TAG, 0); asm volatile("ld.shared.u32 %0, [%1];" : "=r"(p.base) : "r"(sb + SM_TAG) : "memory"); p.base = (p.base - 1) * 255; }
            static_assert(Pat<1>::v == Pat<4>::v, "");
            p.pat = Pat<1>::v;
#pragma unroll 1
            for (int m = 0; m < 14; m++) {
              const int k = (m >> 1) == (hl ? j : 0) ? 14 + (m & 1) : m;
              const uint32_t a = p.acquire<2>(fb);
              p.load_narrow(P, ffn, a + PAGE, fb, k, j);
              tma_ld3(a, xmap, fb, k * 64, xpar, xrow);
            }
            if (!ffn) {
              p.pat = Pat<2>::v;
              uint32_t a = p.acquire<2>(fb);
              tma_ld3(a, xmap, fb, j * 128, xpar, xrow); tma_ld3(a + PAGE, xmap, fb, j * 128 + 64, xpar, xrow);
#pragma unroll 1
              for (int s = 0; s < 16; s++) {
                if (!(s & 1)) a = p.acquire<2>(fb); else a += PAGE;
                p.load_b(a, 8192, &P.map[M_WO], 0, fb, o_chunk(s, j), 2 * j, 1);
              }
            } else {
              p.pat = Pat<5>::v; p.addr = 6 * PAGE;
#pragma unroll 1
              for (int s = 16; s < 48; s++) {
                const int pi = (s >> 1) & 7;
                const int k = (s < 32 ? pi : pi == 4 ? j : pi == j ? 4 : pi) * 2 + (s & 1);
                const uint32_t a = p.acquire<3>(fb);
                p.load_wide(P, 1, a + PAGE, fb, k, (s & 48) + 2 * j);
                tma_ld3(a, xmap, fb, k * 64, g, 0);
              }
              p.pat = Pat<6>::v;
#pragma unroll 1
              for (int q = 0; q < 4; q++) {
                p.next();
                const int k0 = q == 0 ? 0 : q == 1 ? 48 : q * 16 - 16, k1 = k0 + (q == 1 ? 8 : 16);
#pragma unroll 1
                for (int k = k0; k < k1; k++) {
                  const uint32_t a = p.acquire<2>(fb);
                  p.load_b(a + PAGE, 8192, &P.map[M_W2], 0, fb, k, 2 * j, 1);
                  tma_ld3(a, &P.map[M_H_LD], fb, k * 64, g, 0);
                }
              }
            }
            TL(2, 1 + hl);
          }
        }
        p.finish();
      }
    } else if (!spare) {
      mbar_wait(sb + BAR_XIN + CS_START, 0);
      if (elect_one()) prefetch_l2(ptr_add(P.wqkv, (role * 3 + (warp - 9)) * 16384u), 16384);
      const uint32_t tag = ld_relaxed(epoch_ptr(P)) + 1;
      if (warp == 10 && lane == 0) { asm volatile("st.shared.u32 [%0], %1;" :: "r"(sb + SM_TAG), "r"(tag) : "memory"); mbar_arrive(sb + BAR_TAG); }
      {
        const uint32_t part = warp - 9, col = DM + role * 16 + (lane & 1) * 8;
        const int cnt = part ? 21 : 22;
        const uint4* wp = ptr_add((const uint4*)P.wqkv, ((part ? 16 + part * 336 : 0) + (lane >> 1)) * 6144u + col * 2);
        float s[8] = {0, 0, 0, 0, 0, 0, 0, 0};
        uint4 v[4];
#pragma unroll
        for (int i = 0; i < 4; i++) v[i] = __ldcg(wp + i * (16 * 6144 / 16));
#pragma unroll 1
        for (int b = 4; b < 28; b += 4) {
          wp += 64 * 6144 / 16;
#pragma unroll
          for (int i = 0; i < 4; i++) {
            s[0] += bf_lo(v[i].x); s[1] += bf_hi(v[i].x); s[2] += bf_lo(v[i].y); s[3] += bf_hi(v[i].y);
            s[4] += bf_lo(v[i].z); s[5] += bf_hi(v[i].z); s[6] += bf_lo(v[i].w); s[7] += bf_hi(v[i].w);
            v[i] = make_uint4(0, 0, 0, 0);
            if (b + i < cnt) v[i] = __ldcg(wp + i * (16 * 6144 / 16));
          }
        }
#pragma unroll
        for (int e = 0; e < 4; e++) { const bool h = lane & 16; const float t = __shfl_xor_sync(0xffffffffu, h ? s[e] : s[e + 4], 16); s[e] = (h ? s[e + 4] : s[e]) + t; }
#pragma unroll
        for (int e = 0; e < 2; e++) { const bool h = lane & 8; const float t = __shfl_xor_sync(0xffffffffu, h ? s[e] : s[e + 2], 8); s[e] = (h ? s[e + 2] : s[e]) + t; }
        { const bool h = lane & 4; const float t = __shfl_xor_sync(0xffffffffu, h ? s[0] : s[1], 4); s[0] = (h ? s[1] : s[0]) + t; }
        s[0] += __shfl_xor_sync(0xffffffffu, s[0], 2);
        if (!(lane & 2) || part == 0) st_relaxed(scratch<uint32_t>(P, G_CS + (col + (lane >> 2)) * 16 + ((lane & 2) ? 3 : part) * 4), tagf((lane & 2) ? 0.f : s[0], tag));
        __syncwarp();
      }
      if (warp == 11 && lane == 0) TL(2, 30);
      {
        const uint32_t cspos = sb + SM_CS + ((lane & 16) + ((lane >> 1) & 3) * 4 + ((lane >> 3) & 1) * 2 + (lane & 1)) * 4;
#pragma unroll 1
        for (int it = 0; it < (warp == 10 ? 8 : 1); it++) {
          const int t = it & 3;
          if (it) mbar_wait(sb + BAR_CSE, (it - 1) & 1);
          if (t == 1) mbar_wait(sb + BAR_SEMPTY, 0);
#pragma unroll 1
          for (int b = it ? 0 : warp - 9; b < (it == 0 ? warp - 8 : t < 2 ? 3 : 2); b++) {
            uint32_t c0, c1;
            if (b < 2) { c0 = (t ? 2048 + t * 1024 + b * FF : 1024 + b * 1024) + j * 128; c1 = c0 + 64; }
            else if (t) { c0 = 6144 + j * 64; c1 = c0 + FF; }
            else { c0 = j * 128; c1 = c0 + 64; }
            const uint4* p0 = scratch<uint4>(P, G_CS + (c0 + lane) * 16u);
            const uint4* p1 = scratch<uint4>(P, G_CS + (c1 + lane) * 16u);
            uint4 v[4]; uint32_t spins = 0; bool ok;
            do {
              if (spins) __nanosleep(200);
              v[0] = ld_relaxed4(p0); v[1] = ld_relaxed4(p0 + 32); v[2] = ld_relaxed4(p1); v[3] = ld_relaxed4(p1 + 32);
              ok = tag_ok4(v[0], tag) && tag_ok4(v[1], tag) && tag_ok4(v[2], tag) && tag_ok4(v[3], tag);
              spin_check(++spins);
            } while (__any_sync(0xffffffffu, !ok));
#pragma unroll
            for (int m = 0; m < 4; m++) sts32f(cspos + b * 512 + m * 128, (untag(v[m].x) + untag(v[m].y)) + (untag(v[m].z) + untag(v[m].w)));
            __syncwarp();
            if (lane == 0) mbar_arrive(sb + BAR_CSF + (b ? 8 : 0));
          }
          if (lane == 0) { if (t >= 2) mbar_arrive(sb + BAR_CSF + 8); TL(2, 16 + it + (warp == 11 ? 8 : warp == 9 ? 9 : 0)); }
          if (t == 3) {
            if (g >= 2) {
              uint4* op = scratch<uint4>(P, G_HALO + (((it >> 2) * 16 + g - 2) * 8 + j) * 4096u + lane * 16u);
#pragma unroll 1
              for (int i = 0; i < 8; i++) { st_b128(op, 0, 0, 0, 0); op += 32; }
            }
          }
        }
      }
      if (warp == 11) {
        if (elect_one()) prefetch_l2(ptr_add(P.wo, role * 16384u), 16384);
        uint32_t* const fl = scratch<uint32_t>(P, g * G_BLOCK + G_FLAGS);
        uint32_t seen = 0;
#pragma unroll 1
        for (int e = EV_XA; e < EV_N + EV_XB; e++) {
          if (e == EV_XB) continue;
          const bool clr = (e & 7) == EV_XA;
          uint32_t* const f = ptr_add(fl, (clr ? 16 + e : e) * 128u);
          if (clr) {
            uint4* op = scratch<uint4>(P, g * G_BLOCK + G_O + j * 32768u + lane * 16u);
#pragma unroll 1
            for (int i = 0; i < 64; i++) { st_b128(op, 0, 0, 0, 0); op += 32; __nanosleep(CLR_NS); }
            __syncwarp();
            if (lane == 0) red_release(f, 1u << j);
          }
          uint32_t spins = 0, m;
          while ((m = ld_relaxed(f) - (tag - 1) * 255) != 255) { __nanosleep(m ? 50 : 500); spin_check(++spins); }
          asm volatile("fence.acquire.gpu;" ::: "memory");
          if (lane == 0) {
            if (clr) mbar_arrive(sb + BAR_CLR);
            else asm volatile("st.release.cta.shared.u32 [%0], %1;" :: "r"(sb + SM_SEEN), "r"(++seen) : "memory");
          }
          if (e == EV_H3) {
#pragma unroll 1
            for (int i = 0; i < 7; i++) { if (elect_one()) prefetch_l2(ptr_add(P.w2, (i * 128 + role) * 8192u), 8192); __nanosleep(500); }
          }
          __syncwarp();
        }
      } else if (warp == 9) {
        if (elect_one()) {
          prefetch_map(&P.map[M_WQ]); prefetch_map(&P.map[M_XA_ST]); prefetch_map(&P.map[M_XA_LD]); prefetch_map(&P.map[M_OUT_LD]); prefetch_map(&P.map[M_WO]); prefetch_map(&P.map[M_W1 + rank]);
          prefetch_map(&P.map[M_H_ST]); prefetch_map(&P.map[M_H_LD]); prefetch_map(&P.map[M_W1H + rank]); prefetch_map(&P.map[M_W2]); prefetch_map(&P.map[M_OUT_ST]);
          uint32_t* fl = scratch<uint32_t>(P, g * G_BLOCK + G_FLAGS);
          int pe = 0;
#pragma unroll 1
          for (int e = 0; e < 2 * EV_N; e++) {
            const int q = e & 7;
            const bool is_h = q >= EV_H0 && q < EV_XB, last = e >= EV_N + EV_XB;
            const CUtensorMap* map = &P.map[q >= EV_XB ? M_OUT_ST : is_h ? M_H_ST : M_XA_ST];
            const int col = q == EV_H3 ? 3072 - 64 + j * 64 : (q == EV_H1 ? 1024 : q == EV_H2 ? 2048 : 0) + j * 128;
            const int row = q >= EV_XB ? (g >> 1) * 128 : 0, par = q >= EV_XB ? g & 1 : g;
#pragma unroll 1
            for (int hb = is_h ? q == EV_H3 : q & 1; hb <= (is_h ? 1 : q & 1); hb++) {
#pragma unroll
              for (int wg = 0; wg < 2; wg++) {
                mbar_wait(sb + BAR_SFULL + 16 * wg + 8 * (pe & 1), (pe >> 1) & 1);
                if (wg == 0) TL(3, 20 + e);
                tma_st3(map, sb + SM_STAGE + wg * PAGE + hb * 8192, col + hb * 64, par, row + wg * 64);
              }
              pe++;
            }
            bulk_commit();
            if (e != EV_N + EV_XB) bulk_wait<0>();
            TL(3, 40 + e);
            if (is_h || (q & 1)) mbar_arrive(sb + BAR_SEMPTY);
            if (!last) red_release(fl, 1u << j);
            TL(3, e);
            fl += 32;
          }
          *epoch_ptr(P) = tag;
        }
      }
    }
  } else {
    if (EARLY_PF && !spare) {
      if (warp == 0) asm volatile("prefetch.global.L2 [%0];" :: "l"(ptr_add(P.x, (2 * ((g >> 1) * 128 + j * 16 + (lane >> 1)) + (g & 1)) * 2048u + (lane & 1) * 128u)));
      else if (warp < 3 && (warp == 1 || lane < 16)) asm volatile("prefetch.global.L2 [%0];" :: "l"(ptr_add(P.wqkv, role * 6144u + (warp - 1) * 4096u + lane * 128u)));
      __syncwarp();
    }
    asm volatile("barrier.cluster.arrive.relaxed.aligned;" ::: "memory");
    asm volatile("setmaxnreg.inc.sync.aligned.u32 232;");
    SP(4);
    asm volatile("barrier.cluster.wait.acquire.aligned;" ::: "memory");
    SP(5);
    const int wg = warp >> 2;
    const int quad = lane & 3, gr = lane >> 2;
    Cons c; c.sb = sb; c.n = 0; c.off = 0; c.prev = 0; c.lane = lane;
    c.ebar = mapa(sb + BAR_EMPTY - 64, shared_b() ? lane & 1 : rank);
    const uint32_t stage = sb + SM_STAGE + wg * PAGE;
    const uint32_t dstage = desc_lo(stage, 16);
    if (spare) {
      const uint32_t tag = ld_relaxed(epoch_ptr(P)) + 1;
      const int tid = threadIdx.x & 127;
#pragma unroll
      for (int i = 0; i < 4; i++) sts128(stage + (i * 128 + tid) * 16, 0x3f803f80u, 0x3f803f80u, 0x3f803f80u, 0x3f803f80u);
      fence_async_smem();
      bar_sync(2 + wg, 128);
      c.db0 = desc_lo(sb + wg * PAGE, 8192);
#pragma unroll 1
      for (int r = -1; r < 7; r++) {
        float acc[64];
#pragma unroll 1
        for (int k = 0; k < 16; k++) c.step_ab<128, 2>(acc, dstage, c.db0 + c.off, k);
        c.drain();
        acc_fence<64>(acc);
        {
          float v = 0;
#pragma unroll
          for (int i = 0; i < 32; i++) asm("{\n.reg .pred p;\nsetp.eq.u32 p, %2, %3;\nselp.f32 %0, %1, %0, p;\n}" : "+f"(v) : "f"(acc[4 * (i >> 1) + (i & 1)]), "r"(tid >> 2), "r"(i));
          st_b128(scratch<uint4>(P, G_CS + (uint32_t)((r < 0 ? j * 256 + wg * 128 : 3 * DM + wg * FF + ((r < 2 ? r : r == 2 ? 6 : r - 1) * 4 + j) * 128) + (tid >> 3) * 8 + quad * 2 + (gr & 1)) * 16u),
                  tagf(v, tag), tag & 15u, tag & 15u, tag & 15u);
        }
        __syncwarp();
      }
      if (wg == 0) {
        const uint32_t* p = scratch<uint32_t>(P, (tid >> 3) * G_BLOCK + G_STATS + (tid & 7) * 8u);
        uint32_t spins = 0;
        while (__any_sync(0xffffffffu, (ld_relaxed(p) ^ tag) & 15u)) spin_check(++spins);
      }
      bar_sync(1, 256);
      if (threadIdx.x == 0) *epoch_ptr(P) = tag;
    } else {
    c.da0 = desc_lo(sb + wg * 8192, 16); c.db0 = desc_lo(sb, 8192);
    uint32_t sphase = 1, sfull = sb + BAR_SFULL + 16 * wg;
    const uint32_t maddr = stage + ((warp & 3) * 16 + (lane & 15)) * 128 + (((lane >> 4) ^ (lane & 7)) << 4);
    const uint32_t csaddr = sb + SM_CS + quad * 16;
    float st[8] = {0, 0, 0, 0, 0, 0, 0, 0};
    float* const mean = st; float* const rstd = st + 2;
    SP(6);

    auto stage_wait = [&]() { mbar_wait_fast(sb + BAR_SEMPTY, sphase); sphase ^= 1; };
    auto stage_publish = [&]() { fence_async_smem(); __syncwarp(); if (lane == 0) mbar_arrive(sfull); sfull ^= 8; };
    auto cs_load = [&](uint32_t (&cs)[16], int grp) {
#pragma unroll
      for (int i = 0; i < 4; i++) lds128(csaddr + grp * 256 + i * 64, cs[4 * i], cs[4 * i + 1], cs[4 * i + 2], cs[4 * i + 3]);
    };
    auto cs_apply = [&](float* acc, uint32_t (&cs)[16]) {
      acc_fence<32>(acc);
#pragma unroll
      for (int b = 0; b < 8; b++) {
        acc[4 * b] -= mean[0] * __uint_as_float(cs[2 * b]); acc[4 * b + 1] -= mean[0] * __uint_as_float(cs[2 * b + 1]);
        acc[4 * b + 2] -= mean[1] * __uint_as_float(cs[2 * b]); acc[4 * b + 3] -= mean[1] * __uint_as_float(cs[2 * b + 1]);
      }
      acc_fence<32>(acc);
    };
    auto glu_pair = [&](float g0, float g1, float u0, float u1, int r) {
      const float nl = -LOG2E * rstd[r], r2 = rstd[r] * rstd[r];
      return pack_bf16(g0 * u0 * r2 * rcp(1.0f + ex2(g0 * nl)), g1 * u1 * r2 * rcp(1.0f + ex2(g1 * nl)));
    };
    auto glu_slice = [&](uint32_t (&pk)[64], int i) {
      uint32_t hp[4];
#pragma unroll
      for (int e = 0; e < 4; e++) {
        asm volatile("" : "+r"(pk[4 * i + e]), "+r"(pk[32 + 4 * i + e]));
        const uint32_t pg = pk[4 * i + e], pu = pk[32 + 4 * i + e];
        hp[e] = glu_pair(bf_lo(pg), bf_hi(pg), bf_lo(pu), bf_hi(pu), e & 1);
      }
      stsm4((maddr ^ ((i & 3) << 5)) + (i >> 2) * 8192, hp[0], hp[1], hp[2], hp[3]);
    };
    auto glu_slice_acc = [&](float (&acc)[128], int i) {
      uint32_t hp[4];
      acc_fence<8>(acc + 8 * i);
#pragma unroll
      for (int e = 0; e < 4; e++) hp[e] = glu_pair(acc[8 * i + 2 * e], acc[8 * i + 2 * e + 1], acc[64 + 8 * i + 2 * e], acc[64 + 8 * i + 2 * e + 1], e & 1);
      stsm4((maddr ^ ((i & 3) << 5)) + (i >> 2) * 8192, hp[0], hp[1], hp[2], hp[3]);
    };
    auto stage_x = [&](float (&x)[64], int hf) {
#pragma unroll
      for (int i = 4 * hf; i < 4 * hf + 4; i++)
        stsm4((maddr ^ ((i & 3) << 5)) + hf * 8192, pack_bf16(x[8 * i], x[8 * i + 1]), pack_bf16(x[8 * i + 2], x[8 * i + 3]),
              pack_bf16(x[8 * i + 4], x[8 * i + 5]), pack_bf16(x[8 * i + 6], x[8 * i + 7]));
      stage_publish();
    };

    float acc[128];
    mbar_wait_fast(sb + BAR_XIN, 0);
    SP(7);
    c.step_own<256>(acc, dstage, 0);
    mbar_wait_fast(sb + BAR_XIN + 8, 0);
    SP(8);
#pragma unroll 1
    for (int hl = 0;; hl++) {
      int t = hl & 1;
      float acc2[64];
      c.step_own<256>(acc, dstage + 512, 1);
#pragma unroll
      for (int s = 0; s < 2; s++) c.step_own<128>(acc2, dstage + s * 512, s);
#pragma unroll 1
      for (int s = 2; s < 11; s++) {
        const uint32_t apage = (c.off << 4) - (SM_STAGE + wg * 8192);
        c.step<256>(acc);
        int act = s;
        asm volatile("" : "+r"(act));
        auto get_tag = [&]() { uint32_t tag; asm volatile("ld.shared.u32 %0, [%1];" : "=r"(tag) : "r"(sb + SM_TAG) : "memory"); return tag; };
        auto stat_ptr = [&]() { return scratch<uint2>(P, g * G_BLOCK + G_STATS + (hl * 128 + warp * 16 + (lane_now() >> 2)) * 64u); };
        auto stat_get = [&]() {
          const uint2* sp = ptr_add(stat_ptr(), (lane_now() & 3) * 16);
          const uint4 a = ld_relaxed4(sp), b = ld_relaxed4(sp + 64);
          st[0] = __uint_as_float(a.x); st[1] = __uint_as_float(a.y); st[2] = __uint_as_float(a.z); st[3] = __uint_as_float(a.w);
          st[4] = __uint_as_float(b.x); st[5] = __uint_as_float(b.y); st[6] = __uint_as_float(b.z); st[7] = __uint_as_float(b.w);
        };
        switch (act) {
          case 4: case 5: {
            const uint32_t ra = maddr + ((hl || j == 0) ? (s & 1) * 8192 : apage);
#pragma unroll
            for (int i = 0; i < 4; i++) {
              uint32_t v[4];
              ldsm4(ra ^ (i << 5), v[0], v[1], v[2], v[3]);
              if (i == 0 && s == 4) { st[0] = bf_lo(v[0]); st[1] = bf_lo(v[1]); st[2] = st[3] = st[4] = st[5] = 0; }
#pragma unroll
              for (int e = 0; e < 4; e++) {
                const float a = bf_lo(v[e]) - st[e & 1], b = bf_hi(v[e]) - st[e & 1];
                st[2 + (e & 1)] += a + b; st[4 + (e & 1)] += a * a; st[4 + (e & 1)] += b * b;
              }
            }
          } break;
          case 6: {
            mbar_wait_fast(sb + BAR_TAG, 0);
            const uint32_t tag = get_tag();
#pragma unroll
            for (int r = 0; r < 2; r++) {
              const float mt = st[r] + st[2 + r] * (1.0f / 32);
              float m = mt + __shfl_xor_sync(0xffffffffu, mt, 1); m += __shfl_xor_sync(0xffffffffu, m, 2); m *= 0.25f;
              float q = st[4 + r] - st[2 + r] * st[2 + r] * (1.0f / 32) + 32.0f * (mt - m) * (mt - m);
              q += __shfl_xor_sync(0xffffffffu, q, 1); q += __shfl_xor_sync(0xffffffffu, q, 2);
              if (quad == 0) st_relaxed2(ptr_add(stat_ptr(), r * 512 + j * 8), tagf(m, tag), tagf(q, tag));
            }
          } break;
          case 8: stat_get(); break;
          case 10: {
            const uint32_t tag = get_tag();
            uint32_t spins = 0;
            for (;;) {
              uint32_t bad = 0;
#pragma unroll
              for (int i = 0; i < 8; i++) bad |= __float_as_uint(st[i]) ^ tag;
              if (!__any_sync(0xffffffffu, bad & 15u)) break;
              stat_get(); spin_check(++spins);
            }
            float mr[4];
#pragma unroll
            for (int r = 0; r < 2; r++) {
              const float m0 = untag(__float_as_uint(st[4 * r])), m1 = untag(__float_as_uint(st[4 * r + 2]));
              float m = m0 + m1; m += __shfl_xor_sync(0xffffffffu, m, 1); m += __shfl_xor_sync(0xffffffffu, m, 2); m *= 0.125f;
              float q = untag(__float_as_uint(st[4 * r + 1])) + untag(__float_as_uint(st[4 * r + 3])) + 128.0f * ((m0 - m) * (m0 - m) + (m1 - m) * (m1 - m));
              q += __shfl_xor_sync(0xffffffffu, q, 1); q += __shfl_xor_sync(0xffffffffu, q, 2);
              mr[r] = m; mr[2 + r] = rsqrtf(fmaxf(q, 0.f) * (1.0f / DM) + LN_EPS);
            }
            st[0] = mr[0]; st[1] = mr[1]; st[2] = mr[2]; st[3] = mr[3];
          } break;
          default: break;
        }
      }
#pragma unroll 1
      for (;;) {
      const int it = (hl >> 1) * 4 + t;
#pragma unroll
      for (int s = 0; s < 4; s++) {
        uint32_t cs[16];
        c.step<256>(acc);
        if (!(s & 1)) mbar_wait_fast(sb + BAR_CSF + 4 * s, t & 1);
        if (s >= 2 && t <= 1) { cs_load(cs, 2 + s); cs_apply(acc2 + 32 * (s - 2), cs); }
        cs_load(cs, s);
        c.drain();
        cs_apply(acc + 32 * s, cs);
      }
      c.step<256>(acc);
      if (lane == 0) mbar_arrive(sb + BAR_CSE);
      c.drain();
      acc_fence<128>(acc);
      TLC(1 + it * 6);
      uint32_t pkB[64];
      if (t == 2) {
#pragma unroll
        for (int i = 0; i < 64; i++) pkB[i] = pack_bf16(acc[2 * i], acc[2 * i + 1]);
      } else if (t == 0) {
        uint32_t pkA[64];
        auto kv_pack = [&](int v, int r) {
#pragma unroll
          for (int i = 32 * v + r; i < 32 * v + 32; i += 2) { acc_fence<2>(acc + 2 * i); pkA[i] = pack_bf16(acc[2 * i] * rstd[r], acc[2 * i + 1] * rstd[r]); }
        };
        const uint32_t l16 = lane_now() * 16u;
        uint4* const xs = ptr_add((uint4*)smem_raw, SM_STAGE + l16);
        uint4* const hp = scratch<uint4>(P, G_HALO + (((hl >> 1) * 16 + g) * 8 + j) * 4096u + l16);
        {
          uint4* const dst = (warp == 7 && g < 14) ? hp : ptr_add(xs, warp * 4096u);
#pragma unroll
          for (int s = 0; s < 2; s++) {
            c.steps<128>(acc2, s ? 2 : 1 + wg);
            if (s == 0) stage_wait();
            kv_pack(s, 1);
#pragma unroll
            for (int i = 4 * s; i < 4 * s + 4; i++) { pkA[8 * i + 1] = pkt_head(pkA[8 * i + 1]); gen_store(dst + i * 32, pkA[8 * i + 1], pkA[8 * i + 3], pkA[8 * i + 5], pkA[8 * i + 7]); }
          }
        }
        __syncwarp();
        if (lane == 0) mbar_arrive(sb + BAR_XFULL);
#pragma unroll
        for (int s = 0; s < 2; s++) {
          c.steps<128>(acc2, 2);
#pragma unroll
          for (int i = 33 - s; i < 64; i += 2) pkA[i] = movm(pkA[i]);
          kv_pack(1 - s, 0);
        }
        uint32_t kvH[32];
        {
          const uint4* const src = (warp == 0 && g >= 2) ? hp - 2 * 8 * 256 : ptr_add(xs, (warp ? warp - 1 : 0) * 4096u);
          c.steps<128>(acc2, 2);
          mbar_wait_fast(sb + BAR_XFULL, hl >> 1);
#pragma unroll
          for (int i = 0; i < 8; i++) gen_load(src + i * 32, kvH + 4 * i);
          c.steps<128>(acc2, 3 - wg);
          uint32_t spins = 0;
          while (__any_sync(0xffffffffu, !(kvH[0] && kvH[4] && kvH[8] && kvH[12] && kvH[16] && kvH[20] && kvH[24] && kvH[28]))) {
#pragma unroll
            for (int i = 0; i < 8; i++) gen_load(src + i * 32, kvH + 4 * i);
            spin_check(++spins);
          }
        }
#pragma unroll
        for (int i = 16; i < 32; i++) kvH[i] = movm(kvH[i]);
        mbar_wait_fast(sb + BAR_CLR, hl >> 1);
        c.steps<128>(acc2, 2);
        AP(0);
#pragma unroll 1
        for (int i = 0; i < 2; i++) c.wait_full(i);
        AP(1);
        c.drain();
        AP(2);
        acc_fence<64>(acc2);
        TLC(2 + it * 6);
        uint32_t q[32];
#pragma unroll
        for (int i = 0; i < 32; i++) q[i] = pack_bf16(acc2[2 * i], acc2[2 * i + 1]);
        const uint32_t zm = bar_sync_zero(1, 256);
        AP(3);
        uint32_t ob[4][16];
        uint4* const omail = scratch<uint4>(P, g * G_BLOCK + G_O + warp * 2048u + l16);
        auto o_fetch = [&](uint32_t (&v0)[16], uint32_t (&v1)[16], const uint4* p0, const uint4* p1) {
#pragma unroll
          for (int i = 0; i < 4; i++) pkt_load(p0 + i * 32, v0 + 4 * i);
#pragma unroll
          for (int i = 0; i < 4; i++) pkt_load(p1 + i * 32, v1 + 4 * i);
        };
        {
          const uint32_t ra = maddr - (SM_STAGE + wg * 8192) + (c.off << 4);
#pragma unroll
          for (int i = 0; i < 8; i++) { uint32_t* v = ob[2 + (i >> 2)] + 4 * (i & 3); ldsm4((ra ^ ((i & 3) << 5)) + (i >> 2) * PAGE, v[0], v[1], v[2], v[3]); }
          const uint32_t rbar = 64 + ((c.n & 7) << 3);
          c.advance<2>();
          const float hv = (warp == 0 && g < 2) ? -INFINITY : 0.f;
          const float hinit[4] = {hv, hv, hv, hv};
          const bool c0 = (2 * quad <= gr), c1 = (2 * quad + 1 <= gr);
          const uint32_t lm = (c0 ? 0xffffu : 0u) | (c1 ? 0xffff0000u : 0u);
          const float sc[2] = {rstd[0] * (0.17677669529663687f * LOG2E), rstd[1] * (0.17677669529663687f * LOG2E)};
          float lg[4][4], mx[4][2];
#pragma unroll
          for (int h = 0; h < 4; h++) {
            const int b = h * 4;
            float sH[4], sL[4], sU[4];
            q[2 * b] |= zm;
            mma16816(sH, q[2 * b], q[2 * b + 1], q[2 * b + 2], q[2 * b + 3], kvH[b], kvH[b + 1], hinit);
            mma16816z(sL, q[2 * b], q[2 * b + 1], q[2 * b + 2], q[2 * b + 3], pkA[2 * b], pkA[2 * b + 2]);
            mma16816z(sU, q[2 * b], q[2 * b + 1], q[2 * b + 2], q[2 * b + 3], pkA[2 * b + 1], pkA[2 * b + 3]);
            mma16816(sH, q[2 * b + 4], q[2 * b + 5], q[2 * b + 6], q[2 * b + 7], kvH[b + 2], kvH[b + 3], sH);
            mma16816(sL, q[2 * b + 4], q[2 * b + 5], q[2 * b + 6], q[2 * b + 7], pkA[2 * b + 4], pkA[2 * b + 6], sL);
            mma16816(sU, q[2 * b + 4], q[2 * b + 5], q[2 * b + 6], q[2 * b + 7], pkA[2 * b + 5], pkA[2 * b + 7], sU);
            lg[h][0] = c0 ? sL[0] : sH[0]; lg[h][1] = c1 ? sL[1] : sH[1]; lg[h][2] = c0 ? sU[2] : sL[2]; lg[h][3] = c1 ? sU[3] : sL[3];
            mx[h][0] = fmaxf(lg[h][0], lg[h][1]); mx[h][1] = fmaxf(lg[h][2], lg[h][3]);
          }
#pragma unroll
          for (int o = 1; o < 4; o <<= 1) {
#pragma unroll
            for (int i = 0; i < 8; i++) mx[i >> 1][i & 1] = fmaxf(mx[i >> 1][i & 1], __shfl_xor_sync(0xffffffffu, mx[i >> 1][i & 1], o));
          }
          AP(4);
          uint32_t z = zm;
#pragma unroll
          for (int hf = 0; hf < 2; hf++) {
#pragma unroll
            for (int hh = 0; hh < 2; hh++) {
              const int h = hf * 2 + hh, b = h * 4;
              const uint32_t pa = pack_bf16(ex2((lg[h][0] - mx[h][0]) * sc[0]), ex2((lg[h][1] - mx[h][0]) * sc[0]));
              const uint32_t pb = pack_bf16(ex2((lg[h][2] - mx[h][1]) * sc[1]), ex2((lg[h][3] - mx[h][1]) * sc[1]));
              float sum[4];
              mma1688z(sum, pa, pb, 0x3f803f80u);
              const uint32_t p0 = pa & ~lm, p1 = pa & z, p2 = pa & lm, p3 = pb & ~lm, p4 = pb & z, p5 = pb & lm;
              const float ra = rcp(sum[0]), rb = rcp(sum[2]);
#pragma unroll
              for (int d = 0; d < 4; d++) {
                float o[4];
                mma16816z(o, p0, p1, p2, p3, kvH[16 + b + d], pkA[32 + 2 * (b + d)]);
                mma1688(o, p4, p5, pkA[32 + 2 * (b + d) + 1], o);
                ob[hf][(hh * 4 + d) * 2] = pack_bf16(o[0] * ra, o[1] * ra); ob[hf][(hh * 4 + d) * 2 + 1] = pack_bf16(o[2] * rb, o[3] * rb);
              }
            }
#pragma unroll
            for (int i = 0; i < 4; i++) ob[hf][4 * i] = pkt_head(ob[hf][4 * i]);
            if (hf == 0) {
              AP(5);
              uint4* op = ptr_add(omail, j * 32768u);
#pragma unroll
              for (int i = 0; i < 4; i++) st_b128(op + i * 32, ob[0][4 * i], ob[0][4 * i + 1], ob[0][4 * i + 2], ob[0][4 * i + 3]);
              z = late_zero(zm);
              AP(6);
            }
          }
#pragma unroll
          for (int i = 0; i < 32; i++) { acc2[2 * i] = bf_lo(ob[2 + (i >> 4)][i & 15]); acc2[2 * i + 1] = bf_hi(ob[2 + (i >> 4)][i & 15]); }
          acc_fence<64>(acc2);
          if (lane < 2) mbar_arrive_cluster(c.ebar + rbar);
#pragma unroll
          for (int i = 0; i < 4; i++) sts128(stage + (warp & 3) * 2048 + i * 512 + l16, ob[1][4 * i], ob[1][4 * i + 1], ob[1][4 * i + 2], ob[1][4 * i + 3]);
          AP(7);
          bar_sync(1, 256);
        }
        TLC(3 + it * 6);
        AP(8);
        uint64_t todo;
        { const uint32_t o7 = 0x6543210u | (7u << (4 * j) & 0xfffffffu); todo = (uint64_t)(o7 * 2) | (uint64_t)(o7 * 2 + 0x1111111u) << 28; }
        const uint4* p0 = ptr_add(omail, ((uint32_t)todo & 15u) << 14);
        const uint4* p1 = ptr_add(omail, ((uint32_t)todo & 240u) << 10);
#pragma unroll 1
        for (int s0 = 0; s0 < 16; s0 += 4) {
#pragma unroll
          for (int b = 0; b < 4; b += 2) {
            const bool more = b == 0 || s0 < 12;
            uint32_t (&y0)[16] = ob[b ^ 2], (&y1)[16] = ob[b ^ 3];
            if (WO_ORDER == 1 && b == 0 && s0 == 0) y0[0] = 0;
            else if (more) o_fetch(y0, y1, p0, p1);
            c.issue_rs2(acc2, ob[b], ob[b + 1]);
            if (more) {
              const uint32_t z = late_zero(zm);
              c.wait_full(0);
              if (s0 + b == 0) AP(9);
              uint32_t spins = 0;
              while (__builtin_expect(__any_sync(0xffffffffu, (y0[0] == z || y0[4] == z || y0[8] == z || y0[12] == z) | (y1[0] == z || y1[4] == z || y1[8] == z || y1[12] == z)), 0)) {
                o_fetch(y0, y1, p0, p1);
                spin_check(++spins);
              }
              if (b == 0 && s0 == 0) {
                fence_async_smem();
                __syncwarp();
                if (elect_one()) {
                  asm volatile("cp.async.bulk.global.shared::cta.bulk_group [%0], [%1], 2048;"
                               :: "l"(scratch<uint4>(P, g * G_BLOCK + G_O + (2 * j + 1) * 16384u + warp * 2048u)), "r"(stage + (warp & 3) * 2048) : "memory");
                  bulk_commit();
                }
              }
              todo >>= 8;
              p0 = ptr_add(omail, ((uint32_t)todo & 15u) << 14); p1 = ptr_add(omail, ((uint32_t)todo & 240u) << 10);
              asm volatile("" : "+l"(p0), "+l"(p1));
            } else { if (elect_one()) bulk_wait<0>(); __syncwarp(); }
            c.drain();
            if (s0 + b == 0) AP(11);
            if (s0 + b == 2) AP(12);
            if (s0 + b == 4) AP(13);
            if (s0 + b == 14) AP(14);
          }
        }
        break;
      } else {
        c.steps<128>(acc2, 1 + wg);
        stage_wait();
        glu_slice_acc(acc, 0);
#pragma unroll
        for (int s = 1; s < 8; s++) { c.steps<128>(acc2, (s & 1) || t == 3 ? 2 : 1); if (s == 4) stage_publish(); glu_slice_acc(acc, s); }
        c.steps<128>(acc2, 2 - wg);
        stage_publish();
        if (t == 3) c.steps<128>(acc2, 39);
        if (t == 3) stage_wait();
        c.drain();
        acc_fence<64>(acc2);
        if (t == 3) break;
        TLC(2 + it * 6);
        c.off = 6 << 10; asm volatile("" : "+r"(c.off));
        c.step<256>(acc, 0);
        acc_fence<64>(acc2);
#pragma unroll
        for (int i = 0; i < 16; i++) {
          pkB[16 + i] = pack_bf16(acc2[2 * i], acc2[2 * i + 1]); pkB[48 + i] = pack_bf16(acc2[32 + 2 * i], acc2[32 + 2 * i + 1]);
          pkB[i] = 0; pkB[32 + i] = 0;
        }
      }
      t++;
#pragma unroll 1
      for (int s = 3 - t; s < 8; s++) {
        c.step<256>(acc, s);
        int act = (t == 3 || s >= 4) ? s : 8;
        asm volatile("" : "+r"(act));
        if (act < 8) {
          if (!(act & 3)) { if (act && t == 3) stage_publish(); else stage_wait(); }
          auto f = [&](int i) { glu_slice(pkB, i); };
          SELECT8(act, f);
        }
      }
#pragma unroll
      for (int s = 0; s < 2; s++) {
        const uint32_t ra = maddr - (SM_STAGE + wg * 8192) + (c.off << 4);
        c.step<256>(acc);
        if (s == 0) stage_publish();
#pragma unroll
        for (int i = 0; i < 4; i++) {
          uint32_t v[4];
          ldsm4(ra ^ (i << 5), v[0], v[1], v[2], v[3]);
#pragma unroll
          for (int e = 0; e < 4; e++) { acc2[32 * s + 8 * i + 2 * e] = bf_lo(v[e]); acc2[32 * s + 8 * i + 2 * e + 1] = bf_hi(v[e]); }
        }
        acc_fence<32>(acc2 + 32 * s);
      }
      c.step<256>(acc);
      }
      const int it = (hl >> 1) * 4 + t;
      acc_fence<64>(acc2);
      TLC(4 + it * 6);
      stage_x(acc2, 0);
      if (hl == 3) { stage_x(acc2, 1); TLC(5 + it * 6); TLG(63); break; }
      bar_sync(2 + wg, 128);
      TLC(5 + it * 6);
      c.off = 0; asm volatile("" : "+r"(c.off));
      c.step_own<256>(acc, dstage, 0);
      acc_fence<32>(acc2 + 32);
      stage_x(acc2, 1);
      bar_sync(2 + wg, 128);
    }
    }
  }
}

typedef CUresult (*EncodeFn)(CUtensorMap*, CUtensorMapDataType, cuuint32_t, void*, const cuuint64_t*, const cuuint64_t*, const cuuint32_t*,
                             const cuuint32_t*, CUtensorMapInterleave, CUtensorMapSwizzle, CUtensorMapL2promotion, CUtensorMapFloatOOBfill);

void encode(EncodeFn fn, CUtensorMap* m, const void* ptr, int rank, const cuuint64_t* dims, const cuuint64_t* strides, const cuuint32_t* box) {
  cuuint32_t es[5] = {1, 1, 1, 1, 1};
  fn(m, CU_TENSOR_MAP_DATA_TYPE_BFLOAT16, rank, const_cast<void*>(ptr), dims, strides, box, es, CU_TENSOR_MAP_INTERLEAVE_NONE,
     CU_TENSOR_MAP_SWIZZLE_128B, CU_TENSOR_MAP_L2_PROMOTION_L2_128B, CU_TENSOR_MAP_FLOAT_OOB_FILL_NONE);
}

}

extern "C" void kernel_launch(void* const* d_in, const int* in_sizes, int n_in, void* d_out, int out_size) {
  const __nv_bfloat16* x = (const __nv_bfloat16*)d_in[0];
  const __nv_bfloat16* wqkv = (const __nv_bfloat16*)d_in[1];
  const __nv_bfloat16* wo = (const __nv_bfloat16*)d_in[2];
  const __nv_bfloat16* w1 = (const __nv_bfloat16*)d_in[4];
  const __nv_bfloat16* w3 = (const __nv_bfloat16*)d_in[5];
  const __nv_bfloat16* w2 = (const __nv_bfloat16*)d_in[6];

  void* fnp = nullptr; cudaDriverEntryPointQueryResult qr;
  cudaGetDriverEntryPoint("cuTensorMapEncodeTiled", &fnp, cudaEnableDefault, &qr);
  EncodeFn fn = (EncodeFn)fnp;
  void* sym;
  cudaGetSymbolAddress(&sym, g_scratch);
  uint8_t* scr = (uint8_t*)(((uintptr_t)sym + G_BLOCK - 1) / G_BLOCK * G_BLOCK);

  Params P = {};
  { cuuint64_t d[3] = {DM, 2, SEQ / 2}, s[2] = {DM * 2, DM * 4}; cuuint32_t b[3] = {64, 1, 128}, b2[3] = {64, 1, 64};
    encode(fn, &P.map[M_XIN], x, 3, d, s, b); encode(fn, &P.map[M_XIN64], x, 3, d, s, b2);
    encode(fn, &P.map[M_OUT_LD], d_out, 3, d, s, b); encode(fn, &P.map[M_OUT_ST], d_out, 3, d, s, b2); }
  { cuuint64_t d[3] = {DM, 16, 128}, s[2] = {G_BLOCK, DM * 2}; cuuint32_t b[3] = {64, 1, 128}, b2[3] = {64, 1, 64};
    encode(fn, &P.map[M_XA_LD], scr + G_XA, 3, d, s, b); encode(fn, &P.map[M_XA_ST], scr + G_XA, 3, d, s, b2); }
  { cuuint64_t d[3] = {FF, 16, 128}, s[2] = {G_BLOCK, FF * 2}; cuuint32_t b[3] = {64, 1, 128}, b2[3] = {64, 1, 64};
    encode(fn, &P.map[M_H_LD], scr + G_H, 3, d, s, b); encode(fn, &P.map[M_H_ST], scr + G_H, 3, d, s, b2); }
  { const cuuint32_t b2[3] = {64, 64, 2}, b1[3] = {64, 64, 1};
    { cuuint64_t d[3] = {64, DM, 48}, s[2] = {3 * DM * 2, 128}; encode(fn, &P.map[M_WKV], wqkv, 3, d, s, b2); encode(fn, &P.map[M_WQ], wqkv, 3, d, s, b1); }
    { cuuint64_t d[3] = {64, DM, 16}, s[2] = {DM * 2, 128}; encode(fn, &P.map[M_WO], wo, 3, d, s, b1); }
    { cuuint64_t d[3] = {64, FF, 16}, s[2] = {DM * 2, 128}; encode(fn, &P.map[M_W2], w2, 3, d, s, b1); }
    { cuuint64_t d[3] = {64, DM, FF / 64}, s[2] = {FF * 2, 128};
      encode(fn, &P.map[M_W1], w1, 3, d, s, b2); encode(fn, &P.map[M_W3], w3, 3, d, s, b2);
      encode(fn, &P.map[M_W1H], w1, 3, d, s, b1); encode(fn, &P.map[M_W3H], w3, 3, d, s, b1); }
  }
  P.scratch = scr; P.x = x; P.wqkv = wqkv; P.wo = wo; P.w2 = w2;
  int dev = 0, sms = 0;
  cudaGetDevice(&dev);
  cudaDeviceGetAttribute(&sms, cudaDevAttrMultiProcessorCount, dev);
  P.use_smid = (sms == 132);
  cudaFuncSetAttribute(fused_kernel, cudaFuncAttributeMaxDynamicSharedMemorySize, SM_ALLOC);
  fused_kernel<<<132, 384, SM_ALLOC>>>(P);
}
```

```cpp
#include <cuda_runtime.h>
#include <cuda_bf16.h>
#include <cuda.h>
#include <stdint.h>
#include <math.h>

namespace {

constexpr int SEQ = 2048, DM = 1024, FF = 3584;
constexpr float LN_EPS = 1e-5f;
constexpr float LOG2E = 1.4426950408889634f;

constexpr uint32_t G_BLOCK = 2u << 20;
constexpr uint32_t G_H = 0;
constexpr uint32_t G_O = G_H + 128 * FF * 2;
constexpr uint32_t G_STATS = G_O + 128 * DM * 2;
constexpr uint32_t G_FLAGS = G_STATS + 4 * 128 * 64;
static_assert(G_FLAGS + 4096 <= G_BLOCK, "");
constexpr uint32_t G_HALO = 16 * G_BLOCK;
constexpr uint32_t G_CS = G_HALO + 2 * 16 * 8 * 4096;
constexpr uint32_t G_EPOCH = G_CS + (3 * DM + 2 * FF) * 16;
__device__ __align__(1024) uint8_t g_scratch[18 * G_BLOCK];

enum { M_XIN, M_XIN64, M_H_LD, M_H_ST, M_OUT_LD, M_OUT_ST, M_WKV, M_WQ, M_WO, M_W1, M_W3, M_W1H, M_W3H, M_W2, M_COUNT };
struct alignas(64) Params {
  CUtensorMap map[M_COUNT];
  uint8_t* scratch;
  const __nv_bfloat16* x;
  const __nv_bfloat16* wqkv;
  const __nv_bfloat16* wo;
  const __nv_bfloat16* w2;
  int use_smid;
};

constexpr uint32_t PAGE = 16384, NPAGE = 12;
constexpr uint32_t SM_STAGE = NPAGE * PAGE;
constexpr uint32_t SM_BAR = SM_STAGE + 2 * PAGE;
constexpr uint32_t SM_CS = SM_BAR + 256;
constexpr uint32_t SM_TOTAL = SM_CS + 1536;
constexpr uint32_t SM_ALLOC = SM_TOTAL;
static_assert(SM_ALLOC <= 232448, "shared memory");
constexpr uint32_t BAR_FULL = SM_BAR, BAR_EMPTY = SM_BAR + 64, BAR_SFULL = SM_BAR + 128;
constexpr uint32_t BAR_XFULL = SM_BAR + 160, BAR_CSE = SM_BAR + 168;
constexpr uint32_t BAR_SEMPTY = SM_BAR + 176, BAR_CSF = SM_BAR + 184, BAR_XIN = SM_BAR + 200;
constexpr uint32_t BAR_CLR = SM_BAR + 240, BAR_TAG = SM_BAR + 216, SM_ROLE = SM_BAR + 224, SM_TAG = SM_BAR + 228, SM_SEEN = SM_BAR + 232;
enum { EV_XA, EV_XA2, EV_H0, EV_H3, EV_H1, EV_H2, EV_XB, EV_XB2, EV_N };

#define WO_HOLD 5
struct Sched { uint32_t pat[14]; uint32_t page0[14]; bool ok; };
constexpr int seg_steps(int seg) { return seg == 0 || seg == 3 ? 18 : seg == 1 || seg == 4 ? 14 : seg == 2 ? 9 : seg == 5 ? 32 : 56; }
constexpr int step_pages(int seg, int i) {
  return seg == 0 || seg == 3 ? (i < 2 ? 2 : i < 4 ? 1 : 3) : seg == 5 ? 3 : 2;
}
constexpr Sched make_sched() {
  Sched s = {};
  int owner[NPAGE] = {-1, -1, -1, -1, -1, -1, -1, -1, -1, -1, -1, -1};
  int n = 0, tail = 0, page = 0;
  s.ok = true;
  for (int sg = 0; sg < 14; sg++) {
    const int seg = sg % 7;
    if (seg == 1 || seg == 4 || seg == 6) page += 2;
    s.page0[sg] = page;
    for (int i = 0; i < seg_steps(seg); i++) {
      const int p = step_pages(seg, i);
      if (page + p > (int)NPAGE) { s.ok = false; return s; }
      int need = n - 8;
      for (int q = 0; q < p; q++) { if (owner[page + q] > need) need = owner[page + q]; owner[page + q] = n; }
      if (seg == 3 && i < 4 && need < n - i - WO_HOLD + (i > 2 ? 2 : i)) need = n - i - WO_HOLD + (i > 2 ? 2 : i);
      int nw = need + 1 - tail; if (nw < 0) nw = 0;
      tail += nw;
      if (i < 16) s.pat[sg] |= (uint32_t)nw << (2 * i); else if (nw != 1) s.ok = false;
      if (nw > 3) s.ok = false;
      page = (page + p) % NPAGE; n++;
    }
  }
  for (int sg = 0; sg < 7; sg++) if (s.page0[sg] != s.page0[sg + 7] || (sg && s.pat[sg] != s.pat[sg + 7])) s.ok = false;
  return s;
}
constexpr Sched SCHED = make_sched();
static_assert(SCHED.ok && SCHED.page0[0] == 0 && SCHED.page0[3] == 0 && SCHED.page0[5] == 6 && (SCHED.pat[0] & 0xfff) == 0, "ring schedule");
template <int SEG> struct Pat { static constexpr uint32_t v = SCHED.pat[SEG]; };

__device__ __forceinline__ uint32_t smem_u32(const void* p) { return (uint32_t)__cvta_generic_to_shared(p); }
__device__ __forceinline__ void mbar_init(uint32_t bar, uint32_t cnt) { asm volatile("mbarrier.init.shared::cta.b64 [%0], %1;" :: "r"(bar), "r"(cnt)); }
__device__ __forceinline__ void mbar_expect_tx(uint32_t bar, uint32_t bytes) { asm volatile("mbarrier.arrive.expect_tx.shared::cta.b64 _, [%0], %1;" :: "r"(bar), "r"(bytes) : "memory"); }
__device__ __forceinline__ void mbar_arrive(uint32_t bar) { asm volatile("mbarrier.arrive.shared::cta.b64 _, [%0];" :: "r"(bar) : "memory"); }
__device__ __forceinline__ void mbar_wait(uint32_t bar, uint32_t parity) {
  asm volatile("{\n.reg .pred p;\n.reg .u32 n;\nmov.u32 n, 0;\nLAB_WAIT:\n"
               "mbarrier.try_wait.parity.shared::cta.b64 p, [%0], %1;\n@p bra LAB_DONE;\n"
               "add.u32 n, n, 1;\nsetp.lt.u32 p, n, 4194304;\n@p bra LAB_WAIT;\ntrap;\nLAB_DONE:\n}" :: "r"(bar), "r"(parity) : "memory");
}
__device__ __forceinline__ void mbar_wait_fast(uint32_t bar, uint32_t parity) {
  asm volatile("{\n.reg .pred p;\nLAB_WAIT:\nmbarrier.try_wait.parity.shared::cta.b64 p, [%0], %1;\n@!p bra LAB_WAIT;\n}" :: "r"(bar), "r"(parity) : "memory");
}
__device__ __forceinline__ void spin_check(uint32_t n) { asm volatile("{\n.reg .pred p;\nsetp.ge.u32 p, %0, 4194304;\n@p st.volatile.global.u32 [%1], %0;\n}" :: "r"(n), "l"(0ull)); }
__device__ __forceinline__ void tma_ld3(uint32_t dst, const CUtensorMap* m, uint32_t bar, int c0, int c1, int c2) {
  asm volatile("cp.async.bulk.tensor.3d.shared::cluster.global.mbarrier::complete_tx::bytes [%0], [%1, {%3, %4, %5}], [%2];" :: "r"(dst), "l"(m), "r"(bar), "r"(c0), "r"(c1), "r"(c2) : "memory");
}
__device__ __forceinline__ void tma_ld3_mc(uint32_t dst, const CUtensorMap* m, uint32_t bar, int c0, int c1, int c2, uint16_t mask) {
  asm volatile("cp.async.bulk.tensor.3d.shared::cluster.global.mbarrier::complete_tx::bytes.multicast::cluster [%0], [%1, {%3, %4, %5}], [%2], %6;"
               :: "r"(dst), "l"(m), "r"(bar), "r"(c0), "r"(c1), "r"(c2), "h"(mask) : "memory");
}
__device__ __forceinline__ uint32_t mapa(uint32_t addr, uint32_t cta) { uint32_t r; asm("mapa.shared::cluster.u32 %0, %1, %2;" : "=r"(r) : "r"(addr), "r"(cta)); return r; }
__device__ __forceinline__ void mbar_arrive_cluster(uint32_t bar) { asm volatile("mbarrier.arrive.shared::cluster.b64 _, [%0];" :: "r"(bar) : "memory"); }
__device__ __forceinline__ void tma_st3(const CUtensorMap* m, uint32_t src, int c0, int c1, int c2) {
  asm volatile("cp.async.bulk.tensor.3d.global.shared::cta.bulk_group [%0, {%2, %3, %4}], [%1];" :: "l"(m), "r"(src), "r"(c0), "r"(c1), "r"(c2) : "memory");
}
__device__ __forceinline__ void bulk_commit() { asm volatile("cp.async.bulk.commit_group;" ::: "memory"); }
template <int N> __device__ __forceinline__ void bulk_wait() { asm volatile("cp.async.bulk.wait_group %0;" :: "n"(N) : "memory"); }
__device__ __forceinline__ void fence_async_smem() { asm volatile("fence.proxy.async.shared::cta;" ::: "memory"); }
__device__ __forceinline__ void fence_async_global() { asm volatile("fence.proxy.async.global;" ::: "memory"); }
__device__ __forceinline__ bool elect_one() { uint32_t p; asm volatile("{\n.reg .pred P;\nelect.sync _|P, 0xffffffff;\nselp.u32 %0, 1, 0, P;\n}" : "=r"(p)); return p; }
__device__ __forceinline__ void prefetch_map(const CUtensorMap* m) { asm volatile("prefetch.tensormap [%0];" :: "l"(m) : "memory"); }
__device__ __forceinline__ void prefetch_l2(const void* p, uint32_t bytes) { asm volatile("cp.async.bulk.prefetch.L2.global [%0], %1;" :: "l"(p), "r"(bytes) : "memory"); }
__device__ __forceinline__ void wgmma_fence() { asm volatile("wgmma.fence.sync.aligned;" ::: "memory"); }
__device__ __forceinline__ void wgmma_commit() { asm volatile("wgmma.commit_group.sync.aligned;" ::: "memory"); }
template <int N> __device__ __forceinline__ void wgmma_wait() { asm volatile("wgmma.wait_group.sync.aligned %0;" :: "n"(N) : "memory"); }
__device__ __forceinline__ uint32_t desc_lo(uint32_t addr, uint32_t lbo) { return ((addr & 0x3FFFF) >> 4) | ((lbo >> 4) << 16); }
__device__ __forceinline__ uint64_t desc64(uint32_t lo) { uint64_t r; asm("mov.b64 %0, {%1, %2};" : "=l"(r) : "r"(lo), "r"(0x40000040u)); return r; }
__device__ __forceinline__ void bar_sync(int id, int n) { asm volatile("bar.sync %0, %1;" :: "r"(id), "r"(n) : "memory"); }
__device__ __forceinline__ uint32_t pack_bf16(float lo, float hi) { uint32_t r; asm("cvt.rn.bf16x2.f32 %0, %1, %2;" : "=r"(r) : "f"(hi), "f"(lo)); return r; }
__device__ __forceinline__ float bf_lo(uint32_t v) { return __uint_as_float(v << 16); }
__device__ __forceinline__ float bf_hi(uint32_t v) { return __uint_as_float(v & 0xffff0000u); }
__device__ __forceinline__ float ex2(float x) { float r; asm("ex2.approx.ftz.f32 %0, %1;" : "=f"(r) : "f"(x)); return r; }
__device__ __forceinline__ float rcp(float x) { float r; asm("rcp.approx.ftz.f32 %0, %1;" : "=f"(r) : "f"(x)); return r; }
__device__ __forceinline__ void stsm4(uint32_t a, uint32_t r0, uint32_t r1, uint32_t r2, uint32_t r3) {
  asm volatile("stmatrix.sync.aligned.m8n8.x4.shared.b16 [%0], {%1, %2, %3, %4};" :: "r"(a), "r"(r0), "r"(r1), "r"(r2), "r"(r3) : "memory");
}
__device__ __forceinline__ void ldsm4(uint32_t a, uint32_t& r0, uint32_t& r1, uint32_t& r2, uint32_t& r3) {
  asm volatile("ldmatrix.sync.aligned.m8n8.x4.shared.b16 {%0, %1, %2, %3}, [%4];" : "=r"(r0), "=r"(r1), "=r"(r2), "=r"(r3) : "r"(a) : "memory");
}
__device__ __forceinline__ uint32_t movm(uint32_t v) { uint32_t r; asm volatile("movmatrix.sync.aligned.m8n8.trans.b16 %0, %1;" : "=r"(r) : "r"(v)); return r; }
__device__ __forceinline__ void sts128(uint32_t a, uint32_t r0, uint32_t r1, uint32_t r2, uint32_t r3) {
  asm volatile("st.shared.v4.b32 [%0], {%1, %2, %3, %4};" :: "r"(a), "r"(r0), "r"(r1), "r"(r2), "r"(r3) : "memory");
}
__device__ __forceinline__ void lds128(uint32_t a, uint32_t& r0, uint32_t& r1, uint32_t& r2, uint32_t& r3) {
  asm volatile("ld.shared.v4.b32 {%0, %1, %2, %3}, [%4];" : "=r"(r0), "=r"(r1), "=r"(r2), "=r"(r3) : "r"(a) : "memory");
}
__device__ __forceinline__ void sts32f(uint32_t a, float v) { asm volatile("st.shared.f32 [%0], %1;" :: "r"(a), "f"(v) : "memory"); }
__device__ __forceinline__ void mma16816(float (&d)[4], uint32_t a0, uint32_t a1, uint32_t a2, uint32_t a3, uint32_t b0, uint32_t b1, const float (&c)[4]) {
  asm("mma.sync.aligned.m16n8k16.row.col.f32.bf16.bf16.f32 {%0, %1, %2, %3}, {%4, %5, %6, %7}, {%8, %9}, {%10, %11, %12, %13};"
      : "=f"(d[0]), "=f"(d[1]), "=f"(d[2]), "=f"(d[3]) : "r"(a0), "r"(a1), "r"(a2), "r"(a3), "r"(b0), "r"(b1), "f"(c[0]), "f"(c[1]), "f"(c[2]), "f"(c[3]));
}
__device__ __forceinline__ void mma1688(float (&d)[4], uint32_t a0, uint32_t a1, uint32_t b0, const float (&c)[4]) {
  asm("mma.sync.aligned.m16n8k8.row.col.f32.bf16.bf16.f32 {%0, %1, %2, %3}, {%4, %5}, {%6}, {%7, %8, %9, %10};"
      : "=f"(d[0]), "=f"(d[1]), "=f"(d[2]), "=f"(d[3]) : "r"(a0), "r"(a1), "r"(b0), "f"(c[0]), "f"(c[1]), "f"(c[2]), "f"(c[3]));
}
__device__ __forceinline__ void mma16816z(float (&d)[4], uint32_t a0, uint32_t a1, uint32_t a2, uint32_t a3, uint32_t b0, uint32_t b1) {
  asm("mma.sync.aligned.m16n8k16.row.col.f32.bf16.bf16.f32 {%0, %1, %2, %3}, {%4, %5, %6, %7}, {%8, %9}, {0f00000000, 0f00000000, 0f00000000, 0f00000000};"
      : "=f"(d[0]), "=f"(d[1]), "=f"(d[2]), "=f"(d[3]) : "r"(a0), "r"(a1), "r"(a2), "r"(a3), "r"(b0), "r"(b1));
}
__device__ __forceinline__ void mma1688z(float (&d)[4], uint32_t a0, uint32_t a1, uint32_t b0) {
  asm("mma.sync.aligned.m16n8k8.row.col.f32.bf16.bf16.f32 {%0, %1, %2, %3}, {%4, %5}, {%6}, {0f00000000, 0f00000000, 0f00000000, 0f00000000};"
      : "=f"(d[0]), "=f"(d[1]), "=f"(d[2]), "=f"(d[3]) : "r"(a0), "r"(a1), "r"(b0));
}
__device__ __forceinline__ uint32_t bar_sync_zero(int id, int n) {
  uint32_t r;
  asm volatile("{\n.reg .pred p;\nsetp.eq.u32 p, %1, 0;\nbarrier.cta.red.popc.aligned.u32 %0, %1, %2, p;\n}" : "=r"(r) : "r"(id), "r"(n) : "memory");
  return r;
}
__device__ __forceinline__ uint32_t late_zero(uint32_t zm) { uint32_t c; asm volatile("mov.u32 %0, %%clock;" : "=r"(c) :: "memory"); return c & zm; }
__device__ __forceinline__ void st_b128(uint4* p, uint32_t a, uint32_t b, uint32_t c, uint32_t d) {
  asm volatile("{\n.reg .b128 t;\n.reg .b64 lo, hi;\nmov.b64 lo, {%0, %1};\nmov.b64 hi, {%2, %3};\nmov.b128 t, {lo, hi};\nst.relaxed.gpu.global.b128 [%4], t;\n}"
               :: "r"(a), "r"(b), "r"(c), "r"(d), "l"(p) : "memory");
}
__device__ __forceinline__ uint32_t pkt_head(uint32_t a) { return a ? a : 0x8000u; }
__device__ __forceinline__ void gen_store(uint4* p, uint32_t a, uint32_t b, uint32_t c, uint32_t d) {
  asm volatile("{\n.reg .b128 t;\n.reg .b64 lo, hi;\nmov.b64 lo, {%0, %1};\nmov.b64 hi, {%2, %3};\nmov.b128 t, {lo, hi};\nst.relaxed.gpu.b128 [%4], t;\n}"
               :: "r"(a), "r"(b), "r"(c), "r"(d), "l"(p) : "memory");
}
__device__ __forceinline__ void gen_load(const uint4* p, uint32_t* v) {
  asm volatile("{\n.reg .b128 t;\n.reg .b64 lo, hi;\nld.relaxed.gpu.b128 t, [%4];\nmov.b128 {lo, hi}, t;\nmov.b64 {%0, %1}, lo;\nmov.b64 {%2, %3}, hi;\n}"
               : "=r"(v[0]), "=r"(v[1]), "=r"(v[2]), "=r"(v[3]) : "l"(p) : "memory");
}
__device__ __forceinline__ void pkt_load(const uint4* p, uint32_t* v) {
  asm volatile("{\n.reg .b128 t;\n.reg .b64 lo, hi;\nld.relaxed.gpu.global.b128 t, [%4];\nmov.b128 {lo, hi}, t;\nmov.b64 {%0, %1}, lo;\nmov.b64 {%2, %3}, hi;\n}"
               : "=r"(v[0]), "=r"(v[1]), "=r"(v[2]), "=r"(v[3]) : "l"(p) : "memory");
}
__device__ __forceinline__ uint32_t ld_relaxed(const uint32_t* p) { uint32_t v; asm volatile("ld.relaxed.gpu.global.u32 %0, [%1];" : "=r"(v) : "l"(p) : "memory"); return v; }
__device__ __forceinline__ uint4 ld_relaxed4(const void* p) { uint4 v; asm volatile("ld.relaxed.gpu.global.v4.u32 {%0, %1, %2, %3}, [%4];" : "=r"(v.x), "=r"(v.y), "=r"(v.z), "=r"(v.w) : "l"(p) : "memory"); return v; }
__device__ __forceinline__ void st_relaxed(uint32_t* p, uint32_t v) { asm volatile("st.relaxed.gpu.global.u32 [%0], %1;" :: "l"(p), "r"(v) : "memory"); }
__device__ __forceinline__ void st_relaxed2(void* p, uint32_t a, uint32_t b) { asm volatile("st.relaxed.gpu.global.v2.u32 [%0], {%1, %2};" :: "l"(p), "r"(a), "r"(b) : "memory"); }
__device__ __forceinline__ void red_release(uint32_t* p, uint32_t v) { asm volatile("red.release.gpu.global.add.u32 [%0], %1;" :: "l"(p), "r"(v) : "memory"); }
__device__ __forceinline__ uint32_t tagf(float v, uint32_t tag) { return (__float_as_uint(v) & ~15u) | (tag & 15u); }
__device__ __forceinline__ bool tag_ok4(const uint4& v, uint32_t tag) { return (((v.x ^ tag) | (v.y ^ tag) | (v.z ^ tag) | (v.w ^ tag)) & 15u) == 0; }
__device__ __forceinline__ float untag(uint32_t v) { return __uint_as_float(v & ~15u); }
template <typename T> __device__ __forceinline__ T* ptr_add(T* p, uint32_t bytes) {
  uint64_t r;
  asm("{\n.reg .u32 lo, hi;\nmov.b64 {lo, hi}, %1;\nadd.cc.u32 lo, lo, %2;\naddc.u32 hi, hi, 0;\nmov.b64 %0, {lo, hi};\n}" : "=l"(r) : "l"(p), "r"(bytes));
  return (T*)r;
}
#define TL(who, slot) do {} while (0)
#define TLC(slot) do {} while (0)
#define TLE(slot) do {} while (0)
#define ST(who, n) do {} while (0)
#define AP(i) do {} while (0)
#define SP(v) do {} while (0)
#define TLG(slot) do {} while (0)
#define STA() do {} while (0)
#define STB(n) do {} while (0)

__device__ __forceinline__ void wgmma_n128(float (&d)[64], uint64_t da, uint64_t db, int scale_d) {
  asm volatile("{\n.reg .pred p;\nsetp.ne.b32 p, %66, 0;\n"
    "wgmma.mma_async.sync.aligned.m64n128k16.f32.bf16.bf16 "
    "{%0, %1, %2, %3, %4, %5, %6, %7, %8, %9, %10, %11, %12, %13, %14, %15, "
    "%16, %17, %18, %19, %20, %21, %22, %23, %24, %25, %26, %27, %28, %29, %30, %31, "
    "%32, %33, %34, %35, %36, %37, %38, %39, %40, %41, %42, %43, %44, %45, %46, %47, "
    "%48, %49, %50, %51, %52, %53, %54, %55, %56, %57, %58, %59, %60, %61, %62, %63}, "
    "%64, %65, p, 1, 1, 0, 1;\n}\n"
    : "+f"(d[0]), "+f"(d[1]), "+f"(d[2]), "+f"(d[3]), "+f"(d[4]), "+f"(d[5]), "+f"(d[6]), "+f"(d[7]),
      "+f"(d[8]), "+f"(d[9]), "+f"(d[10]), "+f"(d[11]), "+f"(d[12]), "+f"(d[13]), "+f"(d[14]), "+f"(d[15]),
      "+f"(d[16]), "+f"(d[17]), "+f"(d[18]), "+f"(d[19]), "+f"(d[20]), "+f"(d[21]), "+f"(d[22]), "+f"(d[23]),
      "+f"(d[24]), "+f"(d[25]), "+f"(d[26]), "+f"(d[27]), "+f"(d[28]), "+f"(d[29]), "+f"(d[30]), "+f"(d[31]),
      "+f"(d[32]), "+f"(d[33]), "+f"(d[34]), "+f"(d[35]), "+f"(d[36]), "+f"(d[37]), "+f"(d[38]), "+f"(d[39]),
      "+f"(d[40]), "+f"(d[41]), "+f"(d[42]), "+f"(d[43]), "+f"(d[44]), "+f"(d[45]), "+f"(d[46]), "+f"(d[47]),
      "+f"(d[48]), "+f"(d[49]), "+f"(d[50]), "+f"(d[51]), "+f"(d[52]), "+f"(d[53]), "+f"(d[54]), "+f"(d[55]),
      "+f"(d[56]), "+f"(d[57]), "+f"(d[58]), "+f"(d[59]), "+f"(d[60]), "+f"(d[61]), "+f"(d[62]), "+f"(d[63])
    : "l"(da), "l"(db), "r"(scale_d));
}
__device__ __forceinline__ void wgmma_n256(float (&d)[128], uint64_t da, uint64_t db, int scale_d) {
  asm volatile("{\n.reg .pred p;\nsetp.ne.b32 p, %130, 0;\n"
    "wgmma.mma_async.sync.aligned.m64n256k16.f32.bf16.bf16 "
    "{%0, %1, %2, %3, %4, %5, %6, %7, %8, %9, %10, %11, %12, %13, %14, %15, "
    "%16, %17, %18, %19, %20, %21, %22, %23, %24, %25, %26, %27, %28, %29, %30, %31, "
    "%32, %33, %34, %35, %36, %37, %38, %39, %40, %41, %42, %43, %44, %45, %46, %47, "
    "%48, %49, %50, %51, %52, %53, %54, %55, %56, %57, %58, %59, %60, %61, %62, %63, "
    "%64, %65, %66, %67, %68, %69, %70, %71, %72, %73, %74, %75, %76, %77, %78, %79, "
    "%80, %81, %82, %83, %84, %85, %86, %87, %88, %89, %90, %91, %92, %93, %94, %95, "
    "%96, %97, %98, %99, %100, %101, %102, %103, %104, %105, %106, %107, %108, %109, %110, %111, "
    "%112, %113, %114, %115, %116, %117, %118, %119, %120, %121, %122, %123, %124, %125, %126, %127}, "
    "%128, %129, p, 1, 1, 0, 1;\n}\n"
    : "+f"(d[0]), "+f"(d[1]), "+f"(d[2]), "+f"(d[3]), "+f"(d[4]), "+f"(d[5]), "+f"(d[6]), "+f"(d[7]),
      "+f"(d[8]), "+f"(d[9]), "+f"(d[10]), "+f"(d[11]), "+f"(d[12]), "+f"(d[13]), "+f"(d[14]), "+f"(d[15]),
      "+f"(d[16]), "+f"(d[17]), "+f"(d[18]), "+f"(d[19]), "+f"(d[20]), "+f"(d[21]), "+f"(d[22]), "+f"(d[23]),
      "+f"(d[24]), "+f"(d[25]), "+f"(d[26]), "+f"(d[27]), "+f"(d[28]), "+f"(d[29]), "+f"(d[30]), "+f"(d[31]),
      "+f"(d[32]), "+f"(d[33]), "+f"(d[34]), "+f"(d[35]), "+f"(d[36]), "+f"(d[37]), "+f"(d[38]), "+f"(d[39]),
      "+f"(d[40]), "+f"(d[41]), "+f"(d[42]), "+f"(d[43]), "+f"(d[44]), "+f"(d[45]), "+f"(d[46]), "+f"(d[47]),
      "+f"(d[48]), "+f"(d[49]), "+f"(d[50]), "+f"(d[51]), "+f"(d[52]), "+f"(d[53]), "+f"(d[54]), "+f"(d[55]),
      "+f"(d[56]), "+f"(d[57]), "+f"(d[58]), "+f"(d[59]), "+f"(d[60]), "+f"(d[61]), "+f"(d[62]), "+f"(d[63]),
      "+f"(d[64]), "+f"(d[65]), "+f"(d[66]), "+f"(d[67]), "+f"(d[68]), "+f"(d[69]), "+f"(d[70]), "+f"(d[71]),
      "+f"(d[72]), "+f"(d[73]), "+f"(d[74]), "+f"(d[75]), "+f"(d[76]), "+f"(d[77]), "+f"(d[78]), "+f"(d[79]),
      "+f"(d[80]), "+f"(d[81]), "+f"(d[82]), "+f"(d[83]), "+f"(d[84]), "+f"(d[85]), "+f"(d[86]), "+f"(d[87]),
      "+f"(d[88]), "+f"(d[89]), "+f"(d[90]), "+f"(d[91]), "+f"(d[92]), "+f"(d[93]), "+f"(d[94]), "+f"(d[95]),
      "+f"(d[96]), "+f"(d[97]), "+f"(d[98]), "+f"(d[99]), "+f"(d[100]), "+f"(d[101]), "+f"(d[102]), "+f"(d[103]),
      "+f"(d[104]), "+f"(d[105]), "+f"(d[106]), "+f"(d[107]), "+f"(d[108]), "+f"(d[109]), "+f"(d[110]), "+f"(d[111]),
      "+f"(d[112]), "+f"(d[113]), "+f"(d[114]), "+f"(d[115]), "+f"(d[116]), "+f"(d[117]), "+f"(d[118]), "+f"(d[119]),
      "+f"(d[120]), "+f"(d[121]), "+f"(d[122]), "+f"(d[123]), "+f"(d[124]), "+f"(d[125]), "+f"(d[126]), "+f"(d[127])
    : "l"(da), "l"(db), "r"(scale_d));
}
__device__ __forceinline__ void wgmma_rs_n128(float (&d)[64], const uint32_t* a, uint64_t db, int scale_d) {
  asm volatile("{\n.reg .pred p;\nsetp.ne.b32 p, %69, 0;\n"
    "wgmma.mma_async.sync.aligned.m64n128k16.f32.bf16.bf16 "
    "{%0, %1, %2, %3, %4, %5, %6, %7, %8, %9, %10, %11, %12, %13, %14, %15, "
    "%16, %17, %18, %19, %20, %21, %22, %23, %24, %25, %26, %27, %28, %29, %30, %31, "
    "%32, %33, %34, %35, %36, %37, %38, %39, %40, %41, %42, %43, %44, %45, %46, %47, "
    "%48, %49, %50, %51, %52, %53, %54, %55, %56, %57, %58, %59, %60, %61, %62, %63}, "
    "{%64, %65, %66, %67}, %68, p, 1, 1, 1;\n}\n"
    : "+f"(d[0]), "+f"(d[1]), "+f"(d[2]), "+f"(d[3]), "+f"(d[4]), "+f"(d[5]), "+f"(d[6]), "+f"(d[7]),
      "+f"(d[8]), "+f"(d[9]), "+f"(d[10]), "+f"(d[11]), "+f"(d[12]), "+f"(d[13]), "+f"(d[14]), "+f"(d[15]),
      "+f"(d[16]), "+f"(d[17]), "+f"(d[18]), "+f"(d[19]), "+f"(d[20]), "+f"(d[21]), "+f"(d[22]), "+f"(d[23]),
      "+f"(d[24]), "+f"(d[25]), "+f"(d[26]), "+f"(d[27]), "+f"(d[28]), "+f"(d[29]), "+f"(d[30]), "+f"(d[31]),
      "+f"(d[32]), "+f"(d[33]), "+f"(d[34]), "+f"(d[35]), "+f"(d[36]), "+f"(d[37]), "+f"(d[38]), "+f"(d[39]),
      "+f"(d[40]), "+f"(d[41]), "+f"(d[42]), "+f"(d[43]), "+f"(d[44]), "+f"(d[45]), "+f"(d[46]), "+f"(d[47]),
      "+f"(d[48]), "+f"(d[49]), "+f"(d[50]), "+f"(d[51]), "+f"(d[52]), "+f"(d[53]), "+f"(d[54]), "+f"(d[55]),
      "+f"(d[56]), "+f"(d[57]), "+f"(d[58]), "+f"(d[59]), "+f"(d[60]), "+f"(d[61]), "+f"(d[62]), "+f"(d[63])
    : "r"(a[0]), "r"(a[1]), "r"(a[2]), "r"(a[3]), "l"(db), "r"(scale_d));
}

template <int BN> __device__ __forceinline__ void wgmma(float (&d)[BN / 2], uint64_t a, uint64_t b, int s) {
  if constexpr (BN == 128) wgmma_n128(d, a, b, s);
  else wgmma_n256(d, a, b, s);
}

template <int N> __device__ __forceinline__ void acc_fence(float* a) {
#pragma unroll
  for (int i = 0; i < N; i++) asm volatile("" : "+f"(a[i]) :: "memory");
}

#define SELECT8(a, f) do { \
  if ((a) & 4) { if ((a) & 2) { if ((a) & 1) f(7); else f(6); } else { if ((a) & 1) f(5); else f(4); } } \
  else { if ((a) & 2) { if ((a) & 1) f(3); else f(2); } else { if ((a) & 1) f(1); else f(0); } } } while (0)
__device__ __forceinline__ uint32_t lane_now() { uint32_t l; asm volatile("mov.u32 %0, %%laneid;" : "=r"(l)); return l; }

struct Prod {
  uint32_t sb, n, tail, addr, pat, ready;
  uint32_t rank, flip; uint16_t mask;
  __device__ __forceinline__ void load_b(uint32_t dst, uint32_t half, const CUtensorMap* m, uint32_t mstep, uint32_t fb, int k, int ch, int cstep) {
    uint32_t h = rank;
    do { tma_ld3_mc(dst + h * half, ptr_add(m, h * mstep), fb, 0, k * 64, ch + h * cstep, mask); h ^= flip; } while (h != rank);
  }
  __device__ __forceinline__ void load_wide(const Params& P, int ffn, uint32_t dst, uint32_t fb, int k, int ch) {
    load_b(dst, PAGE, &P.map[ffn ? M_W1 : M_WKV], ffn ? 128 : 0, fb, k, ffn ? ch : ch + 16, ffn ? 0 : 16);
  }
  __device__ __forceinline__ void load_narrow(const Params& P, int ffn, uint32_t dst, uint32_t fb, int k, int j) {
    load_b(dst, 8192, &P.map[ffn ? M_W1H : M_WQ], ffn ? 128 : 0, fb, k, ffn ? 48 + j : 2 * j, ffn ? 0 : 1);
  }
  __device__ __forceinline__ void finish() {
#pragma unroll 1
    for (; tail < n; tail++) mbar_wait(sb + BAR_EMPTY + ((tail & 7) << 3), (tail >> 3) & 1);
  }
  template <int PAGES> __device__ __forceinline__ uint32_t acquire(uint32_t& fb) {
    uint32_t nw = pat & 3; pat = (pat >> 2) | 0x40000000u;
#pragma unroll 1
    for (; nw; nw--) { mbar_wait(sb + BAR_EMPTY + ((tail & 7) << 3), (tail >> 3) & 1); tail++; }
    ST(4, n);
    fb = sb + BAR_FULL + ((n & 7) << 3);
    mbar_expect_tx(fb, PAGES * PAGE);
    const uint32_t a = sb + addr;
    addr += PAGES * PAGE; if (addr >= NPAGE * PAGE) addr = 0;
    n++;
    return a;
  }
  const uint32_t* flag; uint32_t base, seen;
  __device__ __forceinline__ void acquire_fence() { asm volatile("fence.acquire.gpu;" ::: "memory"); fence_async_global(); }
  __device__ __forceinline__ void next() {
    uint32_t v, spins = 0;
    seen++;
    do { asm volatile("ld.acquire.cta.shared.u32 %0, [%1];" : "=r"(v) : "r"(sb + SM_SEEN) : "memory"); spin_check(++spins >> 4); } while (v < seen);
    fence_async_global();
  }
  __device__ __forceinline__ void need(uint32_t mask) {
    if ((ready & mask) != mask) {
      uint32_t spins = 0;
      do { ready = ld_relaxed(flag) - base; spin_check(++spins); } while ((ready & mask) != mask);
      acquire_fence();
    }
    ST(5, n - 1);
  }
};

struct Cons {
  uint32_t sb, n, off, prev;
  uint32_t ebar;
  uint32_t da0, db0;
  int lane;
  template <int PAGES> __device__ __forceinline__ void advance() {
    n++; off += PAGES << 10; if (off >= (NPAGE << 10)) off = 0;
    asm volatile("" : "+r"(n), "+r"(off));
  }
  template <int BN, int PAGES> __device__ __forceinline__ void step_ab(float (&acc)[BN / 2], uint32_t da, uint32_t db, int accumulate) {
    STA();
    mbar_wait_fast(sb + BAR_FULL + ((n & 7) << 3), (n >> 3) & 1);
    STB(n);
    const uint64_t da64 = desc64(da), db64 = desc64(db);
    wgmma_fence();
#pragma unroll
    for (int k = 0; k < 4; k++) wgmma<BN>(acc, da64 + 2 * k, db64 + 128 * k, k ? 1 : accumulate);
    wgmma_commit();
    wgmma_wait<1>();
    if (prev && lane < 2) mbar_arrive_cluster(ebar + prev);
    prev = 64 + ((n & 7) << 3);
    advance<PAGES>();
  }
  template <int BN> __device__ __forceinline__ void step(float (&acc)[BN / 2], int accumulate = 1) { step_ab<BN, BN / 128 + 1>(acc, da0 + off, db0 + 1024 + off, accumulate); }
  template <int BN> __device__ __forceinline__ void step_own(float (&acc)[BN / 2], uint32_t da, int accumulate) { step_ab<BN, BN / 128>(acc, da, db0 + off, accumulate); }
  __device__ __forceinline__ void wait_full(uint32_t i) { mbar_wait_fast(sb + BAR_FULL + (((n + i) & 7) << 3), ((n + i) >> 3) & 1); }
  __device__ __forceinline__ void issue_rs2(float (&acc)[64], uint32_t (&a0)[16], uint32_t (&a1)[16], int accumulate) {
    STA(); STB(n);
    const uint64_t db64 = desc64(db0 + off);
    wgmma_fence();
#pragma unroll
    for (int k = 0; k < 4; k++) wgmma_rs_n128(acc, a0 + 4 * k, db64 + 128 * k, k ? 1 : accumulate);
#pragma unroll
    for (int k = 0; k < 4; k++) wgmma_rs_n128(acc, a1 + 4 * k, db64 + 1024 + 128 * k, 1);
    wgmma_commit();
    prev = 64 + ((n & 7) << 3);
    advance<2>();
  }
  template <int BN> __device__ __forceinline__ void steps(float (&acc)[BN / 2], int cnt) {
#pragma unroll 1
    do { step<BN>(acc); } while (--cnt > 0);
  }
  __device__ __forceinline__ void drain() {
    wgmma_wait<0>();
    if (lane < 2) mbar_arrive_cluster(ebar + prev);
    prev = 0;
  }
};

#define MAPPING 2
__device__ __forceinline__ uint32_t role_of_sm(uint32_t smid) {
  const uint32_t t = smid >> 1;
  uint32_t q, i;
  if (t < 32) { q = t & 7; i = t >> 3; }
  else if (t < 60) { const uint32_t u = t - 32, d = (u * 37) >> 8; q = 1 + u - d * 7; i = 4 + d; }
  else if (t < 62) return 128 + smid - 120;
  else { q = 0; i = t - 58; }
  return (q * 2 + (smid & 1)) * 8 + i;
}

template <typename T> __device__ __forceinline__ T* scratch(const Params& P, uint32_t off) { return (T*)ptr_add(P.scratch, off); }
__device__ __forceinline__ uint32_t* epoch_ptr(const Params& P) { uint32_t b; asm volatile("mov.u32 %0, %%ctaid.x;" : "=r"(b)); return scratch<uint32_t>(P, G_EPOCH + b * 4u); }

__device__ __forceinline__ int o_chunk(int s, int j) { const int hf = s >= 9, m = s - 2 - 7 * hf; return s < 2 ? 2 * j + s : 2 * (m == j ? 7 : m) + hf; }

__global__ void __cluster_dims__(2, 1, 1) __launch_bounds__(384, 1) fused_kernel(const __grid_constant__ Params P) {
  extern __shared__ __align__(1024) uint8_t smem_raw[];
  SP(0);
  const uint32_t sb = __shfl_sync(0xffffffffu, smem_u32(smem_raw), 0);
  const int warp = __shfl_sync(0xffffffffu, threadIdx.x >> 5, 0);
  const int lane = threadIdx.x & 31;
  if (warp == 7 && elect_one()) { prefetch_map(&P.map[M_XIN64]); prefetch_map(&P.map[M_WKV]); prefetch_map(&P.map[M_XIN]); }
  uint32_t role = blockIdx.x < 128 ? ((blockIdx.x >> 4) * 2 + (blockIdx.x & 1)) * 8 + ((blockIdx.x >> 1) & 7) : blockIdx.x;
  if (P.use_smid) { uint32_t smid; asm volatile("mov.u32 %0, %%smid;" : "=r"(smid)); role = role_of_sm(smid); }
  const bool spare = role >= 128;
  const int g = role >> 3, j = role & 7;
  uint32_t rank; asm("mov.u32 %0, %%cluster_ctarank;" : "=r"(rank));
  auto shared_b = [&]() {
    uint32_t peer;
    asm volatile("ld.shared::cluster.u32 %0, [%1];" : "=r"(peer) : "r"(mapa(sb + SM_ROLE, rank ^ 1)) : "memory");
    return !spare && peer < 128 && (peer & 7) == (uint32_t)j;
  };
  SP(1);

  if (warp >= 8) {
    asm volatile("setmaxnreg.dec.sync.aligned.u32 40;");
    if (elect_one()) {
      if (warp == 8) {
#pragma unroll
        for (int i = 0; i < 6; i++) mbar_init(sb + BAR_FULL + 8 * i, 1);
        mbar_init(sb + BAR_XIN, 1); mbar_init(sb + BAR_XIN + 8, 1);
      } else if (warp == 9) {
#pragma unroll
        for (int i = 0; i < 8; i++) mbar_init(sb + BAR_EMPTY + 8 * i, 16);
      } else if (warp == 10) {
#pragma unroll
        for (int i = 0; i < 4; i++) mbar_init(sb + BAR_SFULL + 8 * i, 4);
        mbar_init(sb + BAR_CLR, 1); mbar_init(sb + BAR_FULL + 48, 1); mbar_init(sb + BAR_FULL + 56, 1);
      } else {
        sts128(sb + SM_ROLE, role, 0, 0, 0);
        mbar_init(sb + BAR_TAG, 1); mbar_init(sb + BAR_XFULL, 8); mbar_init(sb + BAR_CSE, 8);
        mbar_init(sb + BAR_SEMPTY, 1); mbar_init(sb + BAR_CSF, 1); mbar_init(sb + BAR_CSF + 8, 2);
      }
      asm volatile("fence.mbarrier_init.release.cluster;\nfence.release.sync_restrict::shared::cta.cluster;" ::: "memory");
      fence_async_smem();
    }
    __syncwarp();
    SP(2);
    asm volatile("barrier.cluster.arrive.relaxed.aligned;" ::: "memory");
    if (warp == 8 && !spare) {
      if (elect_one()) {
        const int par = g & 1, row = (g >> 1) * 128;
#pragma unroll 1
        for (int s = 0; s < 2; s++) {
          const uint32_t xb = sb + BAR_XIN + 8 * s, fb = sb + BAR_FULL + 8 * s;
          mbar_expect_tx(xb, PAGE); mbar_expect_tx(fb, 2 * PAGE);
#pragma unroll
          for (int h = 0; h < 2; h++) tma_ld3(sb + SM_STAGE + h * PAGE + s * 8192, &P.map[M_XIN64], xb, s * 64, par, row + h * 64);
#pragma unroll
          for (int h = 0; h < 2; h++) tma_ld3(sb + (2 * s + h) * PAGE, &P.map[M_WKV], fb, 0, s * 64, 16 + 16 * h + 2 * j);
        }
#pragma unroll 1
        for (int s = 0; s < 2; s++) {
          const uint32_t fb = sb + BAR_FULL + 16 + 8 * s;
          mbar_expect_tx(fb, PAGE);
          tma_ld3(sb + (4 + s) * PAGE, &P.map[M_WKV], fb, 0, s * 64, 2 * j);
        }
#pragma unroll 1
        for (int s = 0; s < 2; s++) {
          const uint32_t fb = sb + BAR_FULL + 32 + 8 * s, a = sb + (6 + 3 * s) * PAGE;
          const int k = (j == 1 ? 4 : 2) + s;
          mbar_expect_tx(fb, 3 * PAGE);
          tma_ld3(a, &P.map[M_XIN], fb, k * 64, par, row);
#pragma unroll
          for (int h = 0; h < 2; h++) tma_ld3(a + PAGE + h * PAGE, &P.map[M_WKV], fb, 0, k * 64, 16 + 16 * h + 2 * j);
        }
        spin_check((sb & 1023) << 22);
      }
      __syncwarp();
    }
    SP(3);
    asm volatile("barrier.cluster.wait.acquire.aligned;" ::: "memory");
    SP(4);
    if (warp == 8) {
      if (elect_one()) {
        Prod p; p.sb = sb; p.n = 0; p.tail = 0; p.ready = 0; p.addr = 0;
        { const bool mc = shared_b(); p.rank = rank; p.flip = !mc; p.mask = mc ? 3 : 1 << rank; }
        uint32_t fb;
        if (spare) {
          p.pat = 0x55555000u;
#pragma unroll 1
          for (int r = -1; r < 7; r++) {
            const int ch = r < 0 ? 4 * j : ((r < 2 ? r : r == 2 ? 6 : r - 1) * 4 + j) * 2;
#pragma unroll 1
            for (int k = 0; k < 16; k++) { const uint32_t a = p.acquire<2>(fb); p.load_b(a, PAGE, &P.map[r < 0 ? M_WKV : M_W1], r < 0 ? 0 : 128, fb, k, ch, r < 0 ? 2 : 0); }
          }
        } else {
          p.seen = 0;
          const int xpar = g & 1, xrow = (g >> 1) * 128;
          SP(5);
#pragma unroll 1
          for (int hl = 0; hl < 4; hl++) {
            const int ffn = hl & 1;
            const CUtensorMap* xmap = &P.map[hl ? M_OUT_LD : M_XIN];
            if (hl) {
              p.pat = ffn ? Pat<3>::v : Pat<7>::v;
#pragma unroll 1
              for (int s = 0; s < 2; s++) { const uint32_t a = p.acquire<2>(fb); p.load_wide(P, ffn, a, fb, 2 * j + s, 2 * j); }
#pragma unroll 1
              for (int s = 0; s < 2; s++) { const uint32_t a = p.acquire<1>(fb); p.load_narrow(P, ffn, a, fb, 2 * j + s, j); }
            } else { p.pat = (Pat<0>::v >> 12) | 0x55500000u; p.addr = 0; p.n = 6; }
            if (hl == 0) SP(6);
            uint32_t fb0 = 0;
#pragma unroll 1
            for (int m = hl ? 0 : 2; m < 14; m++) {
              const int hf = m >= 7, mm = m - 7 * hf, jj = mm == j ? 7 : mm;
              int k = 2 * jj + hf;
              if (hl == 0) {
                const int pr = (m >> 1) + 1;
                k = 2 * (j && pr == 2 ? j : pr == j ? 2 : pr) + (m & 1);
              }
              const uint32_t a = p.acquire<3>(fb);
              p.load_wide(P, ffn, a + PAGE, fb, k, 2 * j);
              if (hl) {
                if (m == 0) { fb0 = fb; continue; }
                if (m == 1) {
                  const int j0 = j ? 0 : 7;
                  p.flag = scratch<uint32_t>(P, g * G_BLOCK + G_FLAGS + (ffn ? (hl >> 1) * EV_N + EV_XA : EV_XB) * 128);
                  p.ready = 0; p.need((1u << j0) | (1u << j));
                  tma_ld3(a - 3 * PAGE, xmap, fb0, j0 * 128, xpar, xrow);
                }
                if (m < 7) p.need(1u << jj); else if (m == 7) p.next();
              }
              tma_ld3(a, xmap, fb, k * 64, xpar, xrow);
            }
            if (hl == 0) { mbar_wait(sb + BAR_TAG, 0); asm volatile("ld.shared.u32 %0, [%1];" : "=r"(p.base) : "r"(sb + SM_TAG) : "memory"); p.base = (p.base - 1) * 255; }
            static_assert(Pat<1>::v == Pat<4>::v, "");
            p.pat = Pat<1>::v; p.addr += 2 * PAGE;
#pragma unroll 1
            for (int m = 0; m < 14; m++) {
              const int k = (m >> 1) == (hl ? j : 0) ? 14 + (m & 1) : m;
              const uint32_t a = p.acquire<2>(fb);
              p.load_narrow(P, ffn, a + PAGE, fb, k, j);
              tma_ld3(a, xmap, fb, k * 64, xpar, xrow);
            }
            if (!ffn) {
              p.pat = Pat<2>::v;
              uint32_t a = 0;
#pragma unroll 1
              for (int s = 0; s < 16; s++) {
                if (!(s & 1)) a = p.acquire<2>(fb); else a += PAGE;
                p.load_b(a, 8192, &P.map[M_WO], 0, fb, o_chunk(s, j), 2 * j, 1);
              }
              a = p.acquire<2>(fb);
              tma_ld3(a, xmap, fb, j * 128, xpar, xrow); tma_ld3(a + PAGE, xmap, fb, j * 128 + 64, xpar, xrow);
            } else {
              p.pat = Pat<5>::v;
#pragma unroll 1
              for (int s = 16; s < 48; s++) {
                const int pi = (s >> 1) & 7;
                const int k = (s < 32 ? pi : pi == 4 ? j : pi == j ? 4 : pi) * 2 + (s & 1);
                const uint32_t a = p.acquire<3>(fb);
                p.load_wide(P, 1, a + PAGE, fb, k, (s & 48) + 2 * j);
                tma_ld3(a, xmap, fb, k * 64, xpar, xrow);
              }
              p.pat = Pat<6>::v; p.addr += 2 * PAGE;
#pragma unroll 1
              for (int q = 0; q < 4; q++) {
                p.next();
                const int k0 = q == 0 ? 0 : q == 1 ? 48 : q * 16 - 16, k1 = k0 + (q == 1 ? 8 : 16);
#pragma unroll 1
                for (int k = k0; k < k1; k++) {
                  const uint32_t a = p.acquire<2>(fb);
                  p.load_b(a + PAGE, 8192, &P.map[M_W2], 0, fb, k, 2 * j, 1);
                  tma_ld3(a, &P.map[M_H_LD], fb, k * 64, g, 0);
                }
              }
            }
            TL(2, 1 + hl);
          }
        }
        p.finish();
      }
    } else if (!spare) {
      mbar_wait(sb + BAR_XIN, 0);
      if (elect_one()) {
#pragma unroll 1
        for (int i = warp - 9; i < 8; i += 3) prefetch_l2(ptr_add(P.wqkv, (i * 128 + role) * 6144u + 2048u), 4096);
      }
      uint32_t tag;
      {
        const uint32_t part = warp - 9, col = DM + role * 16 + (lane & 1) * 8;
        const int cnt = part ? 21 : 22;
        const uint4* wp = ptr_add((const uint4*)P.wqkv, ((part ? 16 + part * 336 : 0) + (lane >> 1)) * 6144u + col * 2);
        float s[8] = {0, 0, 0, 0, 0, 0, 0, 0};
        uint4 v[4];
#pragma unroll
        for (int i = 0; i < 4; i++) v[i] = ld_relaxed4(wp + i * (16 * 6144 / 16));
        tag = ld_relaxed(epoch_ptr(P)) + 1;
        if (warp == 10 && lane == 0) { asm volatile("st.shared.u32 [%0], %1;" :: "r"(sb + SM_TAG), "r"(tag) : "memory"); mbar_arrive(sb + BAR_TAG); }
#pragma unroll 1
        for (int b = 4; b < 28; b += 4) {
          wp += 64 * 6144 / 16;
#pragma unroll
          for (int i = 0; i < 4; i++) {
            s[0] += bf_lo(v[i].x); s[1] += bf_hi(v[i].x); s[2] += bf_lo(v[i].y); s[3] += bf_hi(v[i].y);
            s[4] += bf_lo(v[i].z); s[5] += bf_hi(v[i].z); s[6] += bf_lo(v[i].w); s[7] += bf_hi(v[i].w);
            v[i] = make_uint4(0, 0, 0, 0);
            if (b + i < cnt) v[i] = __ldcg(wp + i * (16 * 6144 / 16));
          }
        }
#pragma unroll
        for (int e = 0; e < 4; e++) { const bool h = lane & 16; const float t = __shfl_xor_sync(0xffffffffu, h ? s[e] : s[e + 4], 16); s[e] = (h ? s[e + 4] : s[e]) + t; }
#pragma unroll
        for (int e = 0; e < 2; e++) { const bool h = lane & 8; const float t = __shfl_xor_sync(0xffffffffu, h ? s[e] : s[e + 2], 8); s[e] = (h ? s[e + 2] : s[e]) + t; }
        { const bool h = lane & 4; const float t = __shfl_xor_sync(0xffffffffu, h ? s[0] : s[1], 4); s[0] = (h ? s[1] : s[0]) + t; }
        s[0] += __shfl_xor_sync(0xffffffffu, s[0], 2);
        if (!(lane & 2) || part == 0) st_relaxed(scratch<uint32_t>(P, G_CS + (col + (lane >> 2)) * 16 + ((lane & 2) ? 3 : part) * 4), tagf((lane & 2) ? 0.f : s[0], tag));
        __syncwarp();
      }
      if (warp == 11 && lane == 0) TL(2, 30);
      {
        const uint32_t cspos = sb + SM_CS + ((lane & 16) + ((lane >> 1) & 3) * 4 + ((lane >> 3) & 1) * 2 + (lane & 1)) * 4;
#pragma unroll 1
        for (int it = 0; it < (warp == 10 ? 8 : 1); it++) {
          const int t = it & 3;
          if (it) mbar_wait(sb + BAR_CSE, (it - 1) & 1);
          if (t == 1) mbar_wait(sb + BAR_SEMPTY, 0);
#pragma unroll 1
          for (int b = it ? 0 : warp - 9; b < (it == 0 ? warp - 8 : t < 2 ? 3 : 2); b++) {
            uint32_t c0, c1;
            if (b < 2) { c0 = (t ? 2048 + t * 1024 + b * FF : 1024 + b * 1024) + j * 128; c1 = c0 + 64; }
            else if (t) { c0 = 6144 + j * 64; c1 = c0 + FF; }
            else { c0 = j * 128; c1 = c0 + 64; }
            const uint4* p0 = scratch<uint4>(P, G_CS + (c0 + lane) * 16u);
            const uint4* p1 = scratch<uint4>(P, G_CS + (c1 + lane) * 16u);
            uint4 v[4]; uint32_t spins = 0; bool ok;
            do {
              if (spins) __nanosleep(200);
              v[0] = ld_relaxed4(p0); v[1] = ld_relaxed4(p0 + 32); v[2] = ld_relaxed4(p1); v[3] = ld_relaxed4(p1 + 32);
              ok = tag_ok4(v[0], tag) && tag_ok4(v[1], tag) && tag_ok4(v[2], tag) && tag_ok4(v[3], tag);
              spin_check(++spins);
            } while (__any_sync(0xffffffffu, !ok));
#pragma unroll
            for (int m = 0; m < 4; m++) sts32f(cspos + b * 512 + m * 128, (untag(v[m].x) + untag(v[m].y)) + (untag(v[m].z) + untag(v[m].w)));
            __syncwarp();
            if (lane == 0) mbar_arrive(sb + BAR_CSF + (b ? 8 : 0));
          }
          if (lane == 0) { if (t >= 2) mbar_arrive(sb + BAR_CSF + 8); TL(2, 16 + it + (warp == 11 ? 8 : warp == 9 ? 9 : 0)); }
          if (t == 3) {
            if (g >= 2) {
              uint4* op = scratch<uint4>(P, G_HALO + (((it >> 2) * 16 + g - 2) * 8 + j) * 4096u + lane * 16u);
#pragma unroll 1
              for (int i = 0; i < 8; i++) { st_b128(op, 0, 0, 0, 0); op += 32; }
            }
          }
        }
      }
      if (warp == 11) {
        if (elect_one()) prefetch_l2(ptr_add(P.wo, role * 16384u), 16384);
        uint32_t* const fl = scratch<uint32_t>(P, g * G_BLOCK + G_FLAGS);
        uint32_t seen = 0;
#pragma unroll 1
        for (int e = EV_XA; e < EV_N + EV_XB; e++) {
          if (e == EV_XB) continue;
          const bool clr = (e & 7) == EV_XA;
          uint32_t* const f = ptr_add(fl, (clr ? 16 + e : e) * 128u);
          if (clr) {
            uint4* op = scratch<uint4>(P, g * G_BLOCK + G_O + j * 32768u + lane * 16u);
#pragma unroll 1
            for (int i = 0; i < 64; i++) { st_b128(op, 0, 0, 0, 0); op += 32; if (e || (i & 1)) __nanosleep(10); }
            __syncwarp();
            if (lane == 0) red_release(f, 1u << j);
          }
          uint32_t spins = 0, m;
          while ((m = ld_relaxed(f) - (tag - 1) * 255) != 255) { __nanosleep(m ? 50 : 500); spin_check(++spins); }
          asm volatile("fence.acquire.gpu;" ::: "memory");
          if (lane == 0) {
            if (clr) mbar_arrive(sb + BAR_CLR);
            else asm volatile("st.release.cta.shared.u32 [%0], %1;" :: "r"(sb + SM_SEEN), "r"(++seen) : "memory");
          }
          if (e == EV_H3) {
#pragma unroll 1
            for (int i = 0; i < 7; i++) { if (elect_one()) prefetch_l2(ptr_add(P.w2, (i * 128 + role) * 8192u), 8192); __nanosleep(500); }
          }
          __syncwarp();
        }
      } else if (warp == 9) {
        if (elect_one()) {
          prefetch_map(&P.map[M_WQ]); prefetch_map(&P.map[M_OUT_LD]); prefetch_map(&P.map[M_WO]); prefetch_map(&P.map[M_W1 + rank]);
          prefetch_map(&P.map[M_H_ST]); prefetch_map(&P.map[M_H_LD]); prefetch_map(&P.map[M_W1H + rank]); prefetch_map(&P.map[M_W2]); prefetch_map(&P.map[M_OUT_ST]);
          uint32_t* fl = scratch<uint32_t>(P, g * G_BLOCK + G_FLAGS);
          int pe = 0;
#pragma unroll 1
          for (int e = 0; e < 2 * EV_N; e++) {
            const int q = e & 7;
            const bool is_h = q >= EV_H0 && q < EV_XB, last = e >= EV_N + EV_XB;
            const CUtensorMap* map = &P.map[is_h ? M_H_ST : M_OUT_ST];
            const int col = q == EV_H3 ? 3072 - 64 + j * 64 : (q == EV_H1 ? 1024 : q == EV_H2 ? 2048 : 0) + j * 128;
            const int row = is_h ? 0 : (g >> 1) * 128, par = is_h ? g : g & 1;
#pragma unroll 1
            for (int hb = is_h ? q == EV_H3 : q & 1; hb <= (is_h ? 1 : q & 1); hb++) {
#pragma unroll
              for (int wg = 0; wg < 2; wg++) {
                mbar_wait(sb + BAR_SFULL + 16 * wg + 8 * (pe & 1), (pe >> 1) & 1);
                if (wg == 0) TL(3, 20 + e);
                tma_st3(map, sb + SM_STAGE + wg * PAGE + hb * 8192, col + hb * 64, par, row + wg * 64);
              }
              pe++;
            }
            bulk_commit();
            if (e != EV_N + EV_XB) bulk_wait<0>();
            TL(3, 40 + e);
            if (is_h || (q & 1)) mbar_arrive(sb + BAR_SEMPTY);
            if (!last) red_release(fl, 1u << j);
            TL(3, e);
            fl += 32;
          }
          *epoch_ptr(P) = tag;
        }
      }
    }
  } else {
    if (!spare) {
      if (warp == 0) asm volatile("prefetch.global.L2 [%0];" :: "l"(ptr_add(P.x, (2 * ((g >> 1) * 128 + j * 16 + (lane >> 1)) + (g & 1)) * 2048u + (lane & 1) * 128u)));
      else if (warp < 3 && (warp == 1 || lane < 16)) asm volatile("prefetch.global.L2 [%0];" :: "l"(ptr_add(P.wqkv, role * 6144u + (warp - 1) * 4096u + lane * 128u)));
      __syncwarp();
    }
    asm volatile("barrier.cluster.arrive.relaxed.aligned;" ::: "memory");
    asm volatile("setmaxnreg.inc.sync.aligned.u32 232;");
    SP(4);
    asm volatile("barrier.cluster.wait.acquire.aligned;" ::: "memory");
    SP(5);
    const int wg = warp >> 2;
    const int quad = lane & 3, gr = lane >> 2;
    Cons c; c.sb = sb; c.n = 0; c.off = 0; c.prev = 0; c.lane = lane;
    c.ebar = mapa(sb + BAR_EMPTY - 64, shared_b() ? lane & 1 : rank);
    const uint32_t stage = sb + SM_STAGE + wg * PAGE;
    const uint32_t dstage = desc_lo(stage, 16);
    if (spare) {
      const uint32_t tag = ld_relaxed(epoch_ptr(P)) + 1;
      const int tid = threadIdx.x & 127;
#pragma unroll
      for (int i = 0; i < 4; i++) sts128(stage + (i * 128 + tid) * 16, 0x3f803f80u, 0x3f803f80u, 0x3f803f80u, 0x3f803f80u);
      fence_async_smem();
      bar_sync(2 + wg, 128);
      c.db0 = desc_lo(sb + wg * PAGE, 8192);
#pragma unroll 1
      for (int r = -1; r < 7; r++) {
        float acc[64];
#pragma unroll 1
        for (int k = 0; k < 16; k++) c.step_ab<128, 2>(acc, dstage, c.db0 + c.off, k);
        c.drain();
        acc_fence<64>(acc);
        {
          float v = 0;
#pragma unroll
          for (int i = 0; i < 32; i++) asm("{\n.reg .pred p;\nsetp.eq.u32 p, %2, %3;\nselp.f32 %0, %1, %0, p;\n}" : "+f"(v) : "f"(acc[4 * (i >> 1) + (i & 1)]), "r"(tid >> 2), "r"(i));
          st_b128(scratch<uint4>(P, G_CS + (uint32_t)((r < 0 ? j * 256 + wg * 128 : 3 * DM + wg * FF + ((r < 2 ? r : r == 2 ? 6 : r - 1) * 4 + j) * 128) + (tid >> 3) * 8 + quad * 2 + (gr & 1)) * 16u),
                  tagf(v, tag), tag & 15u, tag & 15u, tag & 15u);
        }
        __syncwarp();
      }
      if (wg == 0) {
        const uint32_t* p = scratch<uint32_t>(P, (tid >> 3) * G_BLOCK + G_STATS + (tid & 7) * 8u);
        uint32_t spins = 0;
        while (__any_sync(0xffffffffu, (ld_relaxed(p) ^ tag) & 15u)) spin_check(++spins);
      }
      bar_sync(1, 256);
      if (threadIdx.x == 0) *epoch_ptr(P) = tag;
    } else {
    c.da0 = desc_lo(sb + wg * 8192, 16); c.db0 = desc_lo(sb, 8192);
    uint32_t sphase = 1, sfull = sb + BAR_SFULL + 16 * wg;
    const uint32_t maddr = stage + ((warp & 3) * 16 + (lane & 15)) * 128 + (((lane >> 4) ^ (lane & 7)) << 4);
    const uint32_t csaddr = sb + SM_CS + quad * 16;
    float st[8] = {0, 0, 0, 0, 0, 0, 0, 0};
    float* const mean = st; float* const rstd = st + 2;
    SP(6);

    auto stage_wait = [&]() { mbar_wait_fast(sb + BAR_SEMPTY, sphase); sphase ^= 1; };
    auto stage_publish = [&]() { fence_async_smem(); __syncwarp(); if (lane == 0) mbar_arrive(sfull); sfull ^= 8; };
    auto cs_load = [&](uint32_t (&cs)[16], int grp) {
#pragma unroll
      for (int i = 0; i < 4; i++) lds128(csaddr + grp * 256 + i * 64, cs[4 * i], cs[4 * i + 1], cs[4 * i + 2], cs[4 * i + 3]);
    };
    auto cs_apply = [&](float* acc, uint32_t (&cs)[16]) {
      acc_fence<32>(acc);
#pragma unroll
      for (int b = 0; b < 8; b++) {
        acc[4 * b] -= mean[0] * __uint_as_float(cs[2 * b]); acc[4 * b + 1] -= mean[0] * __uint_as_float(cs[2 * b + 1]);
        acc[4 * b + 2] -= mean[1] * __uint_as_float(cs[2 * b]); acc[4 * b + 3] -= mean[1] * __uint_as_float(cs[2 * b + 1]);
      }
      acc_fence<32>(acc);
    };
    auto glu_pair = [&](float g0, float g1, float u0, float u1, int r) {
      const float nl = -LOG2E * rstd[r], r2 = rstd[r] * rstd[r];
      return pack_bf16(g0 * u0 * r2 * rcp(1.0f + ex2(g0 * nl)), g1 * u1 * r2 * rcp(1.0f + ex2(g1 * nl)));
    };
    auto glu_slice = [&](uint32_t (&pk)[64], int i) {
      uint32_t hp[4];
#pragma unroll
      for (int e = 0; e < 4; e++) {
        asm volatile("" : "+r"(pk[4 * i + e]), "+r"(pk[32 + 4 * i + e]));
        const uint32_t pg = pk[4 * i + e], pu = pk[32 + 4 * i + e];
        hp[e] = glu_pair(bf_lo(pg), bf_hi(pg), bf_lo(pu), bf_hi(pu), e & 1);
      }
      stsm4((maddr ^ ((i & 3) << 5)) + (i >> 2) * 8192, hp[0], hp[1], hp[2], hp[3]);
    };
    auto glu_slice_acc = [&](float (&acc)[128], int i) {
      uint32_t hp[4];
      acc_fence<8>(acc + 8 * i);
#pragma unroll
      for (int e = 0; e < 4; e++) hp[e] = glu_pair(acc[8 * i + 2 * e], acc[8 * i + 2 * e + 1], acc[64 + 8 * i + 2 * e], acc[64 + 8 * i + 2 * e + 1], e & 1);
      stsm4((maddr ^ ((i & 3) << 5)) + (i >> 2) * 8192, hp[0], hp[1], hp[2], hp[3]);
    };
    auto stage_x = [&](float (&x)[64], int hf) {
#pragma unroll
      for (int i = 4 * hf; i < 4 * hf + 4; i++)
        stsm4((maddr ^ ((i & 3) << 5)) + hf * 8192, pack_bf16(x[8 * i], x[8 * i + 1]), pack_bf16(x[8 * i + 2], x[8 * i + 3]),
              pack_bf16(x[8 * i + 4], x[8 * i + 5]), pack_bf16(x[8 * i + 6], x[8 * i + 7]));
      stage_publish();
    };

    float acc[128];
    mbar_wait_fast(sb + BAR_XIN, 0);
    SP(7);
    c.step_own<256>(acc, dstage, 0);
    mbar_wait_fast(sb + BAR_XIN + 8, 0);
    SP(8);
#pragma unroll 1
    for (int hl = 0;; hl++) {
      int t = hl & 1;
      float acc2[64];
      c.step_own<256>(acc, dstage + 512, 1);
#pragma unroll
      for (int s = 0; s < 2; s++) c.step_own<128>(acc2, dstage + s * 512, s);
#pragma unroll 1
      for (int s = 2; s < 11; s++) {
        const uint32_t apage = (c.off << 4) - (SM_STAGE + wg * 8192);
        c.step<256>(acc);
        int act = s;
        asm volatile("" : "+r"(act));
        auto get_tag = [&]() { uint32_t tag; asm volatile("ld.shared.u32 %0, [%1];" : "=r"(tag) : "r"(sb + SM_TAG) : "memory"); return tag; };
        auto stat_ptr = [&]() { return scratch<uint2>(P, g * G_BLOCK + G_STATS + (hl * 128 + warp * 16 + (lane_now() >> 2)) * 64u); };
        auto stat_get = [&]() {
          const uint2* sp = ptr_add(stat_ptr(), (lane_now() & 3) * 16);
          const uint4 a = ld_relaxed4(sp), b = ld_relaxed4(sp + 64);
          st[0] = __uint_as_float(a.x); st[1] = __uint_as_float(a.y); st[2] = __uint_as_float(a.z); st[3] = __uint_as_float(a.w);
          st[4] = __uint_as_float(b.x); st[5] = __uint_as_float(b.y); st[6] = __uint_as_float(b.z); st[7] = __uint_as_float(b.w);
        };
        switch (act) {
          case 4: case 5: {
            const uint32_t ra = maddr + ((hl || j == 0) ? (s & 1) * 8192 : apage);
#pragma unroll
            for (int i = 0; i < 4; i++) {
              uint32_t v[4];
              ldsm4(ra ^ (i << 5), v[0], v[1], v[2], v[3]);
              if (i == 0 && s == 4) { st[0] = bf_lo(v[0]); st[1] = bf_lo(v[1]); st[2] = st[3] = st[4] = st[5] = 0; }
#pragma unroll
              for (int e = 0; e < 4; e++) {
                const float a = bf_lo(v[e]) - st[e & 1], b = bf_hi(v[e]) - st[e & 1];
                st[2 + (e & 1)] += a + b; st[4 + (e & 1)] += a * a; st[4 + (e & 1)] += b * b;
              }
            }
          } break;
          case 6: {
            mbar_wait_fast(sb + BAR_TAG, 0);
            const uint32_t tag = get_tag();
#pragma unroll
            for (int r = 0; r < 2; r++) {
              const float mt = st[r] + st[2 + r] * (1.0f / 32);
              float m = mt + __shfl_xor_sync(0xffffffffu, mt, 1); m += __shfl_xor_sync(0xffffffffu, m, 2); m *= 0.25f;
              float q = st[4 + r] - st[2 + r] * st[2 + r] * (1.0f / 32) + 32.0f * (mt - m) * (mt - m);
              q += __shfl_xor_sync(0xffffffffu, q, 1); q += __shfl_xor_sync(0xffffffffu, q, 2);
              if (quad == 0) st_relaxed2(ptr_add(stat_ptr(), r * 512 + j * 8), tagf(m, tag), tagf(q, tag));
            }
          } break;
          case 8: stat_get(); break;
          case 10: {
            const uint32_t tag = get_tag();
            uint32_t spins = 0;
            for (;;) {
              uint32_t bad = 0;
#pragma unroll
              for (int i = 0; i < 8; i++) bad |= __float_as_uint(st[i]) ^ tag;
              if (!__any_sync(0xffffffffu, bad & 15u)) break;
              stat_get(); spin_check(++spins);
            }
            float mr[4];
#pragma unroll
            for (int r = 0; r < 2; r++) {
              const float m0 = untag(__float_as_uint(st[4 * r])), m1 = untag(__float_as_uint(st[4 * r + 2]));
              float m = m0 + m1; m += __shfl_xor_sync(0xffffffffu, m, 1); m += __shfl_xor_sync(0xffffffffu, m, 2); m *= 0.125f;
              float q = untag(__float_as_uint(st[4 * r + 1])) + untag(__float_as_uint(st[4 * r + 3])) + 128.0f * ((m0 - m) * (m0 - m) + (m1 - m) * (m1 - m));
              q += __shfl_xor_sync(0xffffffffu, q, 1); q += __shfl_xor_sync(0xffffffffu, q, 2);
              mr[r] = m; mr[2 + r] = rsqrtf(fmaxf(q, 0.f) * (1.0f / DM) + LN_EPS);
            }
            st[0] = mr[0]; st[1] = mr[1]; st[2] = mr[2]; st[3] = mr[3];
          } break;
          default: break;
        }
      }
#pragma unroll 1
      for (;;) {
      const int it = (hl >> 1) * 4 + t;
#pragma unroll
      for (int s = 0; s < 4; s++) {
        uint32_t cs[16];
        c.step<256>(acc);
        if (!(s & 1)) mbar_wait_fast(sb + BAR_CSF + 4 * s, t & 1);
        if (s >= 2 && t <= 1) { cs_load(cs, 2 + s); cs_apply(acc2 + 32 * (s - 2), cs); }
        cs_load(cs, s);
        c.drain();
        cs_apply(acc + 32 * s, cs);
      }
      c.step<256>(acc);
      if (lane == 0) mbar_arrive(sb + BAR_CSE);
      c.drain();
      acc_fence<128>(acc);
      TLC(1 + it * 6);
      if (t != 2) c.off += 2 << 10;
      uint32_t pkB[64];
      if (t == 2) {
#pragma unroll
        for (int i = 0; i < 64; i++) pkB[i] = pack_bf16(acc[2 * i], acc[2 * i + 1]);
      } else if (t == 0) {
        uint32_t pkA[64];
        auto kv_pack = [&](int v, int r) {
#pragma unroll
          for (int i = 32 * v + r; i < 32 * v + 32; i += 2) { acc_fence<2>(acc + 2 * i); pkA[i] = pack_bf16(acc[2 * i] * rstd[r], acc[2 * i + 1] * rstd[r]); }
        };
        const uint32_t l16 = lane_now() * 16u;
        uint4* const xs = ptr_add((uint4*)smem_raw, SM_STAGE + l16);
        uint4* const hp = scratch<uint4>(P, G_HALO + (((hl >> 1) * 16 + g) * 8 + j) * 4096u + l16);
        {
          uint4* const dst = (warp == 7 && g < 14) ? hp : ptr_add(xs, warp * 4096u);
#pragma unroll
          for (int s = 0; s < 2; s++) {
            c.steps<128>(acc2, s ? 2 : 1 + wg);
            if (s == 0) stage_wait();
            kv_pack(s, 1);
#pragma unroll
            for (int i = 4 * s; i < 4 * s + 4; i++) { pkA[8 * i + 1] = pkt_head(pkA[8 * i + 1]); gen_store(dst + i * 32, pkA[8 * i + 1], pkA[8 * i + 3], pkA[8 * i + 5], pkA[8 * i + 7]); }
          }
        }
        __syncwarp();
        if (lane == 0) mbar_arrive(sb + BAR_XFULL);
#pragma unroll
        for (int s = 0; s < 2; s++) {
          c.steps<128>(acc2, 2);
#pragma unroll
          for (int i = 33 - s; i < 64; i += 2) pkA[i] = movm(pkA[i]);
          kv_pack(1 - s, 0);
        }
        uint32_t kvH[32];
        {
          const uint4* const src = (warp == 0 && g >= 2) ? hp - 2 * 8 * 256 : ptr_add(xs, (warp ? warp - 1 : 0) * 4096u);
          c.steps<128>(acc2, 2);
          mbar_wait_fast(sb + BAR_XFULL, hl >> 1);
#pragma unroll
          for (int i = 0; i < 8; i++) gen_load(src + i * 32, kvH + 4 * i);
          c.steps<128>(acc2, 3 - wg);
          uint32_t spins = 0;
          while (__any_sync(0xffffffffu, !(kvH[0] && kvH[4] && kvH[8] && kvH[12] && kvH[16] && kvH[20] && kvH[24] && kvH[28]))) {
#pragma unroll
            for (int i = 0; i < 8; i++) gen_load(src + i * 32, kvH + 4 * i);
            spin_check(++spins);
          }
        }
#pragma unroll
        for (int i = 16; i < 32; i++) kvH[i] = movm(kvH[i]);
        mbar_wait_fast(sb + BAR_CLR, hl >> 1);
        c.steps<128>(acc2, 2);
        AP(0);
        c.wait_full(0);
        AP(1);
        c.drain();
        AP(2);
        acc_fence<64>(acc2);
        TLC(2 + it * 6);
        uint32_t q[32];
#pragma unroll
        for (int i = 0; i < 32; i++) q[i] = pack_bf16(acc2[2 * i], acc2[2 * i + 1]);
        const uint32_t zm = bar_sync_zero(1, 256);
        AP(3);
        uint32_t ob[4][16];
        uint4* const omail = scratch<uint4>(P, g * G_BLOCK + G_O + warp * 2048u + l16);
        auto o_fetch = [&](uint32_t (&v0)[16], uint32_t (&v1)[16], const uint4* p0, const uint4* p1) {
#pragma unroll
          for (int i = 0; i < 4; i++) pkt_load(p0 + i * 32, v0 + 4 * i);
#pragma unroll
          for (int i = 0; i < 4; i++) pkt_load(p1 + i * 32, v1 + 4 * i);
        };
        {
          const float hv = (warp == 0 && g < 2) ? -INFINITY : 0.f;
          const float hinit[4] = {hv, hv, hv, hv};
          const bool c0 = (2 * quad <= gr), c1 = (2 * quad + 1 <= gr);
          const uint32_t lm = (c0 ? 0xffffu : 0u) | (c1 ? 0xffff0000u : 0u);
          const float sc[2] = {rstd[0] * (0.17677669529663687f * LOG2E), rstd[1] * (0.17677669529663687f * LOG2E)};
          float lg[4][4], mx[4][2];
#pragma unroll
          for (int h = 0; h < 4; h++) {
            const int b = h * 4;
            float sH[4], sL[4], sU[4];
            q[2 * b] |= zm;
            mma16816(sH, q[2 * b], q[2 * b + 1], q[2 * b + 2], q[2 * b + 3], kvH[b], kvH[b + 1], hinit);
            mma16816z(sL, q[2 * b], q[2 * b + 1], q[2 * b + 2], q[2 * b + 3], pkA[2 * b], pkA[2 * b + 2]);
            mma16816z(sU, q[2 * b], q[2 * b + 1], q[2 * b + 2], q[2 * b + 3], pkA[2 * b + 1], pkA[2 * b + 3]);
            mma16816(sH, q[2 * b + 4], q[2 * b + 5], q[2 * b + 6], q[2 * b + 7], kvH[b + 2], kvH[b + 3], sH);
            mma16816(sL, q[2 * b + 4], q[2 * b + 5], q[2 * b + 6], q[2 * b + 7], pkA[2 * b + 4], pkA[2 * b + 6], sL);
            mma16816(sU, q[2 * b + 4], q[2 * b + 5], q[2 * b + 6], q[2 * b + 7], pkA[2 * b + 5], pkA[2 * b + 7], sU);
            lg[h][0] = c0 ? sL[0] : sH[0]; lg[h][1] = c1 ? sL[1] : sH[1]; lg[h][2] = c0 ? sU[2] : sL[2]; lg[h][3] = c1 ? sU[3] : sL[3];
            mx[h][0] = fmaxf(lg[h][0], lg[h][1]); mx[h][1] = fmaxf(lg[h][2], lg[h][3]);
          }
#pragma unroll
          for (int o = 1; o < 4; o <<= 1) {
#pragma unroll
            for (int i = 0; i < 8; i++) mx[i >> 1][i & 1] = fmaxf(mx[i >> 1][i & 1], __shfl_xor_sync(0xffffffffu, mx[i >> 1][i & 1], o));
          }
          AP(4);
          uint32_t z = zm;
#pragma unroll
          for (int hf = 0; hf < 2; hf++) {
#pragma unroll
            for (int hh = 0; hh < 2; hh++) {
              const int h = hf * 2 + hh, b = h * 4;
              const uint32_t pa = pack_bf16(ex2((lg[h][0] - mx[h][0]) * sc[0]), ex2((lg[h][1] - mx[h][0]) * sc[0]));
              const uint32_t pb = pack_bf16(ex2((lg[h][2] - mx[h][1]) * sc[1]), ex2((lg[h][3] - mx[h][1]) * sc[1]));
              float sum[4];
              mma1688z(sum, pa, pb, 0x3f803f80u);
              const uint32_t p0 = pa & ~lm, p1 = pa & z, p2 = pa & lm, p3 = pb & ~lm, p4 = pb & z, p5 = pb & lm;
              const float ra = rcp(sum[0]), rb = rcp(sum[2]);
#pragma unroll
              for (int d = 0; d < 4; d++) {
                float o[4];
                mma16816z(o, p0, p1, p2, p3, kvH[16 + b + d], pkA[32 + 2 * (b + d)]);
                mma1688(o, p4, p5, pkA[32 + 2 * (b + d) + 1], o);
                ob[hf][(hh * 4 + d) * 2] = pack_bf16(o[0] * ra, o[1] * ra); ob[hf][(hh * 4 + d) * 2 + 1] = pack_bf16(o[2] * rb, o[3] * rb);
              }
            }
#pragma unroll
            for (int i = 0; i < 4; i++) ob[hf][4 * i] = pkt_head(ob[hf][4 * i]);
            if (hf == 0) {
              AP(5);
              uint4* op = ptr_add(omail, j * 32768u);
#pragma unroll
              for (int i = 0; i < 4; i++) st_b128(op + i * 32, ob[0][4 * i], ob[0][4 * i + 1], ob[0][4 * i + 2], ob[0][4 * i + 3]);
              z = late_zero(zm);
              AP(6);
            }
          }
#pragma unroll
          for (int i = 0; i < 4; i++) sts128(stage + (warp & 3) * 2048 + i * 512 + l16, ob[1][4 * i], ob[1][4 * i + 1], ob[1][4 * i + 2], ob[1][4 * i + 3]);
          AP(7);
          bar_sync(1, 256);
        }
        TLC(3 + it * 6);
        AP(8);
        uint64_t todo;
        { const uint32_t o7 = 0x6543210u | (7u << (4 * j) & 0xfffffffu); todo = (uint64_t)(o7 * 2) | (uint64_t)(o7 * 2 + 0x1111111u) << 28; }
        const uint4* p0 = ptr_add(omail, ((uint32_t)todo & 15u) << 14);
        const uint4* p1 = ptr_add(omail, ((uint32_t)todo & 240u) << 10);
        auto batch = [&](int b, bool first) {
          uint32_t (&y0)[16] = ob[b ^ 2], (&y1)[16] = ob[b ^ 3];
          o_fetch(y0, y1, p0, p1);
          c.issue_rs2(acc2, ob[b], ob[b + 1], !first);
          const uint32_t z = late_zero(zm);
          c.wait_full(0);
          uint32_t spins = 0;
          while (__builtin_expect(__any_sync(0xffffffffu, (y0[0] == z || y0[4] == z || y0[8] == z || y0[12] == z) | (y1[0] == z || y1[4] == z || y1[8] == z || y1[12] == z)), 0)) {
            o_fetch(y0, y1, p0, p1);
            spin_check(++spins);
          }
          if (first) {
            fence_async_smem();
            __syncwarp();
            if (elect_one()) {
              asm volatile("cp.async.bulk.global.shared::cta.bulk_group [%0], [%1], 2048;"
                           :: "l"(scratch<uint4>(P, g * G_BLOCK + G_O + (2 * j + 1) * 16384u + warp * 2048u)), "r"(stage + (warp & 3) * 2048) : "memory");
              bulk_commit();
            }
          }
          todo >>= 8;
          p0 = ptr_add(omail, ((uint32_t)todo & 15u) << 14); p1 = ptr_add(omail, ((uint32_t)todo & 240u) << 10);
          asm volatile("" : "+l"(p0), "+l"(p1));
          c.drain();
        };
        batch(0, true);
#pragma unroll 1
        for (int i = 0; i < 3; i++) { batch(2, false); batch(0, false); }
        c.issue_rs2(acc2, ob[2], ob[3], 1);
        if (elect_one()) bulk_wait<0>();
        __syncwarp();
        {
          c.wait_full(0);
          const uint32_t ra = maddr - (SM_STAGE + wg * 8192) + (c.off << 4);
          float res[64];
#pragma unroll
          for (int i = 0; i < 8; i++) {
            uint32_t v[4];
            ldsm4((ra ^ ((i & 3) << 5)) + (i >> 2) * PAGE, v[0], v[1], v[2], v[3]);
#pragma unroll
            for (int e = 0; e < 4; e++) { res[8 * i + 2 * e] = bf_lo(v[e]); res[8 * i + 2 * e + 1] = bf_hi(v[e]); }
          }
          acc_fence<64>(res);
          if (lane < 2) mbar_arrive_cluster(c.ebar + 64 + ((c.n & 7) << 3));
          c.advance<2>();
          c.drain();
          acc_fence<64>(acc2);
#pragma unroll
          for (int i = 0; i < 64; i++) acc2[i] += res[i];
        }
        break;
      } else {
        c.steps<128>(acc2, 1 + wg);
        stage_wait();
        glu_slice_acc(acc, 0);
#pragma unroll
        for (int s = 1; s < 8; s++) { c.steps<128>(acc2, (s & 1) || t == 3 ? 2 : 1); if (s == 4) stage_publish(); glu_slice_acc(acc, s); }
        c.steps<128>(acc2, 2 - wg);
        stage_publish();
        if (t == 3) c.steps<128>(acc2, 39);
        if (t == 3) stage_wait();
        c.drain();
        acc_fence<64>(acc2);
        if (t == 3) break;
        TLC(2 + it * 6);
        c.step<256>(acc, 0);
        acc_fence<64>(acc2);
#pragma unroll
        for (int i = 0; i < 16; i++) {
          pkB[16 + i] = pack_bf16(acc2[2 * i], acc2[2 * i + 1]); pkB[48 + i] = pack_bf16(acc2[32 + 2 * i], acc2[32 + 2 * i + 1]);
          pkB[i] = 0; pkB[32 + i] = 0;
        }
      }
      t++;
#pragma unroll 1
      for (int s = 3 - t; s < 8; s++) {
        c.step<256>(acc, s);
        int act = (t == 3 || s >= 4) ? s : 8;
        asm volatile("" : "+r"(act));
        if (act < 8) {
          if (!(act & 3)) { if (act && t == 3) stage_publish(); else stage_wait(); }
          auto f = [&](int i) { glu_slice(pkB, i); };
          SELECT8(act, f);
        }
      }
#pragma unroll
      for (int s = 0; s < 2; s++) {
        const uint32_t ra = maddr - (SM_STAGE + wg * 8192) + (c.off << 4);
        c.step<256>(acc);
        if (s == 0) stage_publish();
#pragma unroll
        for (int i = 0; i < 4; i++) {
          uint32_t v[4];
          ldsm4(ra ^ (i << 5), v[0], v[1], v[2], v[3]);
#pragma unroll
          for (int e = 0; e < 4; e++) { acc2[32 * s + 8 * i + 2 * e] = bf_lo(v[e]); acc2[32 * s + 8 * i + 2 * e + 1] = bf_hi(v[e]); }
        }
        acc_fence<32>(acc2 + 32 * s);
      }
      c.step<256>(acc);
      }
      const int it = (hl >> 1) * 4 + t;
      acc_fence<64>(acc2);
      TLC(4 + it * 6);
      stage_x(acc2, 0);
      if (hl == 3) { stage_x(acc2, 1); TLE(47); TLG(63); break; }
      bar_sync(2 + wg, 128);
      TLC(5 + it * 6);
      c.step_own<256>(acc, dstage, 0);
      acc_fence<32>(acc2 + 32);
      stage_x(acc2, 1);
      bar_sync(2 + wg, 128);
    }
    }
  }
}

typedef CUresult (*EncodeFn)(CUtensorMap*, CUtensorMapDataType, cuuint32_t, void*, const cuuint64_t*, const cuuint64_t*, const cuuint32_t*,
                             const cuuint32_t*, CUtensorMapInterleave, CUtensorMapSwizzle, CUtensorMapL2promotion, CUtensorMapFloatOOBfill);

void encode(EncodeFn fn, CUtensorMap* m, const void* ptr, int rank, const cuuint64_t* dims, const cuuint64_t* strides, const cuuint32_t* box) {
  cuuint32_t es[5] = {1, 1, 1, 1, 1};
  fn(m, CU_TENSOR_MAP_DATA_TYPE_BFLOAT16, rank, const_cast<void*>(ptr), dims, strides, box, es, CU_TENSOR_MAP_INTERLEAVE_NONE,
     CU_TENSOR_MAP_SWIZZLE_128B, CU_TENSOR_MAP_L2_PROMOTION_L2_128B, CU_TENSOR_MAP_FLOAT_OOB_FILL_NONE);
}

}

extern "C" void kernel_launch(void* const* d_in, const int* in_sizes, int n_in, void* d_out, int out_size) {
  const __nv_bfloat16* x = (const __nv_bfloat16*)d_in[0];
  const __nv_bfloat16* wqkv = (const __nv_bfloat16*)d_in[1];
  const __nv_bfloat16* wo = (const __nv_bfloat16*)d_in[2];
  const __nv_bfloat16* w1 = (const __nv_bfloat16*)d_in[4];
  const __nv_bfloat16* w3 = (const __nv_bfloat16*)d_in[5];
  const __nv_bfloat16* w2 = (const __nv_bfloat16*)d_in[6];

  void* fnp = nullptr; cudaDriverEntryPointQueryResult qr;
  cudaGetDriverEntryPoint("cuTensorMapEncodeTiled", &fnp, cudaEnableDefault, &qr);
  EncodeFn fn = (EncodeFn)fnp;
  void* sym;
  cudaGetSymbolAddress(&sym, g_scratch);
  uint8_t* scr = (uint8_t*)(((uintptr_t)sym + G_BLOCK - 1) / G_BLOCK * G_BLOCK);

  Params P = {};
  { cuuint64_t d[3] = {DM, 2, SEQ / 2}, s[2] = {DM * 2, DM * 4}; cuuint32_t b[3] = {64, 1, 128}, b2[3] = {64, 1, 64};
    encode(fn, &P.map[M_XIN], x, 3, d, s, b); encode(fn, &P.map[M_XIN64], x, 3, d, s, b2);
    encode(fn, &P.map[M_OUT_LD], d_out, 3, d, s, b); encode(fn, &P.map[M_OUT_ST], d_out, 3, d, s, b2); }
  { cuuint64_t d[3] = {FF, 16, 128}, s[2] = {G_BLOCK, FF * 2}; cuuint32_t b[3] = {64, 1, 128}, b2[3] = {64, 1, 64};
    encode(fn, &P.map[M_H_LD], scr + G_H, 3, d, s, b); encode(fn, &P.map[M_H_ST], scr + G_H, 3, d, s, b2); }
  { const cuuint32_t b2[3] = {64, 64, 2}, b1[3] = {64, 64, 1};
    { cuuint64_t d[3] = {64, DM, 48}, s[2] = {3 * DM * 2, 128}; encode(fn, &P.map[M_WKV], wqkv, 3, d, s, b2); encode(fn, &P.map[M_WQ], wqkv, 3, d, s, b1); }
    { cuuint64_t d[3] = {64, DM, 16}, s[2] = {DM * 2, 128}; encode(fn, &P.map[M_WO], wo, 3, d, s, b1); }
    { cuuint64_t d[3] = {64, FF, 16}, s[2] = {DM * 2, 128}; encode(fn, &P.map[M_W2], w2, 3, d, s, b1); }
    { cuuint64_t d[3] = {64, DM, FF / 64}, s[2] = {FF * 2, 128};
      encode(fn, &P.map[M_W1], w1, 3, d, s, b2); encode(fn, &P.map[M_W3], w3, 3, d, s, b2);
      encode(fn, &P.map[M_W1H], w1, 3, d, s, b1); encode(fn, &P.map[M_W3H], w3, 3, d, s, b1); }
  }
  P.scratch = scr; P.x = x; P.wqkv = wqkv; P.wo = wo; P.w2 = w2;
  int dev = 0, sms = 0;
  cudaGetDevice(&dev);
  cudaDeviceGetAttribute(&sms, cudaDevAttrMultiProcessorCount, dev);
  P.use_smid = (sms == 132);
  cudaFuncSetAttribute(fused_kernel, cudaFuncAttributeMaxDynamicSharedMemorySize, SM_ALLOC);
  fused_kernel<<<132, 384, SM_ALLOC>>>(P);
}
```

```cpp
#include <cuda_runtime.h>
#include <cuda_bf16.h>
#include <cuda.h>
#include <stdint.h>
#include <math.h>

namespace {

constexpr int SEQ = 2048, DM = 1024, FF = 3584;
constexpr float LN_EPS = 1e-5f;
constexpr float LOG2E = 1.4426950408889634f;

constexpr uint32_t G_BLOCK = 2u << 20;
constexpr uint32_t G_H = 0;
constexpr uint32_t G_O = G_H + 128 * FF * 2;
constexpr uint32_t G_STATS = G_O + 128 * DM * 2;
constexpr uint32_t G_FLAGS = G_STATS + 4 * 128 * 64;
static_assert(G_FLAGS + 4096 <= G_BLOCK, "");
constexpr uint32_t G_HALO = 16 * G_BLOCK;
constexpr uint32_t G_CS = G_HALO + 2 * 16 * 8 * 4096;
constexpr uint32_t G_EPOCH = G_CS + (3 * DM + 2 * FF) * 16;
__device__ __align__(1024) uint8_t g_scratch[18 * G_BLOCK];

enum { M_XIN, M_XIN64, M_H_LD, M_H_ST, M_OUT_LD, M_OUT_ST, M_WKV, M_WQ, M_WO, M_W1, M_W3, M_W1H, M_W3H, M_W2, M_COUNT };
struct alignas(64) Params {
  CUtensorMap map[M_COUNT];
  uint8_t* scratch;
  const __nv_bfloat16* x;
  const __nv_bfloat16* wqkv;
  const __nv_bfloat16* wo;
  const __nv_bfloat16* w2;
  int use_smid;
};

constexpr uint32_t PAGE = 16384, NPAGE = 12;
constexpr uint32_t SM_STAGE = NPAGE * PAGE;
constexpr uint32_t SM_BAR = SM_STAGE + 2 * PAGE;
constexpr uint32_t SM_CS = SM_BAR + 256;
constexpr uint32_t SM_TOTAL = SM_CS + 1536;
constexpr uint32_t SM_ALLOC = SM_TOTAL;
static_assert(SM_ALLOC <= 232448, "shared memory");
constexpr uint32_t BAR_FULL = SM_BAR, BAR_EMPTY = SM_BAR + 64, BAR_SFULL = SM_BAR + 128;
constexpr uint32_t BAR_XFULL = SM_BAR + 160, BAR_CSE = SM_BAR + 168;
constexpr uint32_t BAR_SEMPTY = SM_BAR + 176, BAR_CSF = SM_BAR + 184, BAR_XIN = SM_BAR + 200;
constexpr uint32_t BAR_CLR = SM_BAR + 240, BAR_TAG = SM_BAR + 216, SM_ROLE = SM_BAR + 224, SM_TAG = SM_BAR + 228, SM_SEEN = SM_BAR + 232;
enum { EV_XA, EV_XA2, EV_H0, EV_H3, EV_H1, EV_H2, EV_XB, EV_XB2, EV_N };

#define WO_HOLD 5
struct Sched { uint32_t pat[14]; uint32_t page0[14]; bool ok; };
constexpr int seg_steps(int seg) { return seg == 0 || seg == 3 ? 18 : seg == 1 || seg == 4 ? 14 : seg == 2 ? 9 : seg == 5 ? 32 : 56; }
constexpr int step_pages(int seg, int i) {
  return seg == 0 || seg == 3 ? (i < 2 ? 2 : i < 4 ? 1 : 3) : seg == 5 ? 3 : 2;
}
constexpr Sched make_sched() {
  Sched s = {};
  int owner[NPAGE] = {-1, -1, -1, -1, -1, -1, -1, -1, -1, -1, -1, -1};
  int n = 0, tail = 0, page = 0;
  s.ok = true;
  for (int sg = 0; sg < 14; sg++) {
    const int seg = sg % 7;
    if (seg == 1 || seg == 4 || seg == 6) page += 2;
    s.page0[sg] = page;
    for (int i = 0; i < seg_steps(seg); i++) {
      const int p = step_pages(seg, i);
      if (page + p > (int)NPAGE) { s.ok = false; return s; }
      int need = n - 8;
      for (int q = 0; q < p; q++) { if (owner[page + q] > need) need = owner[page + q]; owner[page + q] = n; }
      if (seg == 3 && i < 4 && need < n - i - WO_HOLD + (i > 2 ? 2 : i)) need = n - i - WO_HOLD + (i > 2 ? 2 : i);
      int nw = need + 1 - tail; if (nw < 0) nw = 0;
      tail += nw;
      if (i < 16) s.pat[sg] |= (uint32_t)nw << (2 * i); else if (nw != 1) s.ok = false;
      if (nw > 3) s.ok = false;
      page = (page + p) % NPAGE; n++;
    }
  }
  for (int sg = 0; sg < 7; sg++) if (s.page0[sg] != s.page0[sg + 7] || (sg && s.pat[sg] != s.pat[sg + 7])) s.ok = false;
  return s;
}
constexpr Sched SCHED = make_sched();
static_assert(SCHED.ok && SCHED.page0[0] == 0 && SCHED.page0[3] == 0 && SCHED.page0[5] == 6 && (SCHED.pat[0] & 0xfff) == 0, "ring schedule");
template <int SEG> struct Pat { static constexpr uint32_t v = SCHED.pat[SEG]; };

__device__ __forceinline__ uint32_t smem_u32(const void* p) { return (uint32_t)__cvta_generic_to_shared(p); }
__device__ __forceinline__ void mbar_init(uint32_t bar, uint32_t cnt) { asm volatile("mbarrier.init.shared::cta.b64 [%0], %1;" :: "r"(bar), "r"(cnt)); }
__device__ __forceinline__ void mbar_expect_tx(uint32_t bar, uint32_t bytes) { asm volatile("mbarrier.arrive.expect_tx.shared::cta.b64 _, [%0], %1;" :: "r"(bar), "r"(bytes) : "memory"); }
__device__ __forceinline__ void mbar_arrive(uint32_t bar) { asm volatile("mbarrier.arrive.shared::cta.b64 _, [%0];" :: "r"(bar) : "memory"); }
__device__ __forceinline__ void mbar_wait(uint32_t bar, uint32_t parity) {
  asm volatile("{\n.reg .pred p;\n.reg .u32 n;\nmov.u32 n, 0;\nLAB_WAIT:\n"
               "mbarrier.try_wait.parity.shared::cta.b64 p, [%0], %1;\n@p bra LAB_DONE;\n"
               "add.u32 n, n, 1;\nsetp.lt.u32 p, n, 4194304;\n@p bra LAB_WAIT;\ntrap;\nLAB_DONE:\n}" :: "r"(bar), "r"(parity) : "memory");
}
__device__ __forceinline__ void mbar_wait_fast(uint32_t bar, uint32_t parity) {
  asm volatile("{\n.reg .pred p;\nLAB_WAIT:\nmbarrier.try_wait.parity.shared::cta.b64 p, [%0], %1;\n@!p bra LAB_WAIT;\n}" :: "r"(bar), "r"(parity) : "memory");
}
__device__ __forceinline__ void spin_check(uint32_t n) { asm volatile("{\n.reg .pred p;\nsetp.ge.u32 p, %0, 4194304;\n@p st.volatile.global.u32 [%1], %0;\n}" :: "r"(n), "l"(0ull)); }
__device__ __forceinline__ void tma_ld3(uint32_t dst, const CUtensorMap* m, uint32_t bar, int c0, int c1, int c2) {
  asm volatile("cp.async.bulk.tensor.3d.shared::cluster.global.mbarrier::complete_tx::bytes [%0], [%1, {%3, %4, %5}], [%2];" :: "r"(dst), "l"(m), "r"(bar), "r"(c0), "r"(c1), "r"(c2) : "memory");
}
__device__ __forceinline__ void tma_ld3_mc(uint32_t dst, const CUtensorMap* m, uint32_t bar, int c0, int c1, int c2, uint16_t mask) {
  asm volatile("cp.async.bulk.tensor.3d.shared::cluster.global.mbarrier::complete_tx::bytes.multicast::cluster [%0], [%1, {%3, %4, %5}], [%2], %6;"
               :: "r"(dst), "l"(m), "r"(bar), "r"(c0), "r"(c1), "r"(c2), "h"(mask) : "memory");
}
__device__ __forceinline__ uint32_t mapa(uint32_t addr, uint32_t cta) { uint32_t r; asm("mapa.shared::cluster.u32 %0, %1, %2;" : "=r"(r) : "r"(addr), "r"(cta)); return r; }
__device__ __forceinline__ void mbar_arrive_cluster(uint32_t bar) { asm volatile("mbarrier.arrive.shared::cluster.b64 _, [%0];" :: "r"(bar) : "memory"); }
__device__ __forceinline__ void tma_st3(const CUtensorMap* m, uint32_t src, int c0, int c1, int c2) {
  asm volatile("cp.async.bulk.tensor.3d.global.shared::cta.bulk_group [%0, {%2, %3, %4}], [%1];" :: "l"(m), "r"(src), "r"(c0), "r"(c1), "r"(c2) : "memory");
}
__device__ __forceinline__ void bulk_commit() { asm volatile("cp.async.bulk.commit_group;" ::: "memory"); }
template <int N> __device__ __forceinline__ void bulk_wait() { asm volatile("cp.async.bulk.wait_group %0;" :: "n"(N) : "memory"); }
__device__ __forceinline__ void fence_async_smem() { asm volatile("fence.proxy.async.shared::cta;" ::: "memory"); }
__device__ __forceinline__ void fence_async_global() { asm volatile("fence.proxy.async.global;" ::: "memory"); }
__device__ __forceinline__ bool elect_one() { uint32_t p; asm volatile("{\n.reg .pred P;\nelect.sync _|P, 0xffffffff;\nselp.u32 %0, 1, 0, P;\n}" : "=r"(p)); return p; }
__device__ __forceinline__ void prefetch_map(const CUtensorMap* m) { asm volatile("prefetch.tensormap [%0];" :: "l"(m) : "memory"); }
__device__ __forceinline__ void prefetch_l2(const void* p, uint32_t bytes) { asm volatile("cp.async.bulk.prefetch.L2.global [%0], %1;" :: "l"(p), "r"(bytes) : "memory"); }
__device__ __forceinline__ void wgmma_fence() { asm volatile("wgmma.fence.sync.aligned;" ::: "memory"); }
__device__ __forceinline__ void wgmma_commit() { asm volatile("wgmma.commit_group.sync.aligned;" ::: "memory"); }
template <int N> __device__ __forceinline__ void wgmma_wait() { asm volatile("wgmma.wait_group.sync.aligned %0;" :: "n"(N) : "memory"); }
__device__ __forceinline__ uint32_t desc_lo(uint32_t addr, uint32_t lbo) { return ((addr & 0x3FFFF) >> 4) | ((lbo >> 4) << 16); }
__device__ __forceinline__ uint64_t desc64(uint32_t lo) { uint64_t r; asm("mov.b64 %0, {%1, %2};" : "=l"(r) : "r"(lo), "r"(0x40000040u)); return r; }
__device__ __forceinline__ void bar_sync(int id, int n) { asm volatile("bar.sync %0, %1;" :: "r"(id), "r"(n) : "memory"); }
__device__ __forceinline__ uint32_t pack_bf16(float lo, float hi) { uint32_t r; asm("cvt.rn.bf16x2.f32 %0, %1, %2;" : "=r"(r) : "f"(hi), "f"(lo)); return r; }
__device__ __forceinline__ float bf_lo(uint32_t v) { return __uint_as_float(v << 16); }
__device__ __forceinline__ float bf_hi(uint32_t v) { return __uint_as_float(v & 0xffff0000u); }
__device__ __forceinline__ float ex2(float x) { float r; asm("ex2.approx.ftz.f32 %0, %1;" : "=f"(r) : "f"(x)); return r; }
__device__ __forceinline__ float rcp(float x) { float r; asm("rcp.approx.ftz.f32 %0, %1;" : "=f"(r) : "f"(x)); return r; }
__device__ __forceinline__ void stsm4(uint32_t a, uint32_t r0, uint32_t r1, uint32_t r2, uint32_t r3) {
  asm volatile("stmatrix.sync.aligned.m8n8.x4.shared.b16 [%0], {%1, %2, %3, %4};" :: "r"(a), "r"(r0), "r"(r1), "r"(r2), "r"(r3) : "memory");
}
__device__ __forceinline__ void ldsm4(uint32_t a, uint32_t& r0, uint32_t& r1, uint32_t& r2, uint32_t& r3) {
  asm volatile("ldmatrix.sync.aligned.m8n8.x4.shared.b16 {%0, %1, %2, %3}, [%4];" : "=r"(r0), "=r"(r1), "=r"(r2), "=r"(r3) : "r"(a) : "memory");
}
__device__ __forceinline__ uint32_t movm(uint32_t v) { uint32_t r; asm volatile("movmatrix.sync.aligned.m8n8.trans.b16 %0, %1;" : "=r"(r) : "r"(v)); return r; }
__device__ __forceinline__ void sts128(uint32_t a, uint32_t r0, uint32_t r1, uint32_t r2, uint32_t r3) {
  asm volatile("st.shared.v4.b32 [%0], {%1, %2, %3, %4};" :: "r"(a), "r"(r0), "r"(r1), "r"(r2), "r"(r3) : "memory");
}
__device__ __forceinline__ void lds128(uint32_t a, uint32_t& r0, uint32_t& r1, uint32_t& r2, uint32_t& r3) {
  asm volatile("ld.shared.v4.b32 {%0, %1, %2, %3}, [%4];" : "=r"(r0), "=r"(r1), "=r"(r2), "=r"(r3) : "r"(a) : "memory");
}
__device__ __forceinline__ uint32_t add_bf16x2(uint32_t a, uint32_t b) { uint32_t r; asm("add.rn.bf16x2 %0, %1, %2;" : "=r"(r) : "r"(a), "r"(b)); return r; }
__device__ __forceinline__ void sts32f(uint32_t a, float v) { asm volatile("st.shared.f32 [%0], %1;" :: "r"(a), "f"(v) : "memory"); }
__device__ __forceinline__ void mma16816(float (&d)[4], uint32_t a0, uint32_t a1, uint32_t a2, uint32_t a3, uint32_t b0, uint32_t b1, const float (&c)[4]) {
  asm("mma.sync.aligned.m16n8k16.row.col.f32.bf16.bf16.f32 {%0, %1, %2, %3}, {%4, %5, %6, %7}, {%8, %9}, {%10, %11, %12, %13};"
      : "=f"(d[0]), "=f"(d[1]), "=f"(d[2]), "=f"(d[3]) : "r"(a0), "r"(a1), "r"(a2), "r"(a3), "r"(b0), "r"(b1), "f"(c[0]), "f"(c[1]), "f"(c[2]), "f"(c[3]));
}
__device__ __forceinline__ void mma1688(float (&d)[4], uint32_t a0, uint32_t a1, uint32_t b0, const float (&c)[4]) {
  asm("mma.sync.aligned.m16n8k8.row.col.f32.bf16.bf16.f32 {%0, %1, %2, %3}, {%4, %5}, {%6}, {%7, %8, %9, %10};"
      : "=f"(d[0]), "=f"(d[1]), "=f"(d[2]), "=f"(d[3]) : "r"(a0), "r"(a1), "r"(b0), "f"(c[0]), "f"(c[1]), "f"(c[2]), "f"(c[3]));
}
__device__ __forceinline__ void mma16816z(float (&d)[4], uint32_t a0, uint32_t a1, uint32_t a2, uint32_t a3, uint32_t b0, uint32_t b1) {
  asm("mma.sync.aligned.m16n8k16.row.col.f32.bf16.bf16.f32 {%0, %1, %2, %3}, {%4, %5, %6, %7}, {%8, %9}, {0f00000000, 0f00000000, 0f00000000, 0f00000000};"
      : "=f"(d[0]), "=f"(d[1]), "=f"(d[2]), "=f"(d[3]) : "r"(a0), "r"(a1), "r"(a2), "r"(a3), "r"(b0), "r"(b1));
}
__device__ __forceinline__ void mma1688z(float (&d)[4], uint32_t a0, uint32_t a1, uint32_t b0) {
  asm("mma.sync.aligned.m16n8k8.row.col.f32.bf16.bf16.f32 {%0, %1, %2, %3}, {%4, %5}, {%6}, {0f00000000, 0f00000000, 0f00000000, 0f00000000};"
      : "=f"(d[0]), "=f"(d[1]), "=f"(d[2]), "=f"(d[3]) : "r"(a0), "r"(a1), "r"(b0));
}
__device__ __forceinline__ uint32_t bar_sync_zero(int id, int n) {
  uint32_t r;
  asm volatile("{\n.reg .pred p;\nsetp.eq.u32 p, %1, 0;\nbarrier.cta.red.popc.aligned.u32 %0, %1, %2, p;\n}" : "=r"(r) : "r"(id), "r"(n) : "memory");
  return r;
}
__device__ __forceinline__ uint32_t late_zero(uint32_t zm) { uint32_t c; asm volatile("mov.u32 %0, %%clock;" : "=r"(c) :: "memory"); return c & zm; }
__device__ __forceinline__ void st_b128(uint4* p, uint32_t a, uint32_t b, uint32_t c, uint32_t d) {
  asm volatile("{\n.reg .b128 t;\n.reg .b64 lo, hi;\nmov.b64 lo, {%0, %1};\nmov.b64 hi, {%2, %3};\nmov.b128 t, {lo, hi};\nst.relaxed.gpu.global.b128 [%4], t;\n}"
               :: "r"(a), "r"(b), "r"(c), "r"(d), "l"(p) : "memory");
}
__device__ __forceinline__ uint32_t pkt_head(uint32_t a) { return a ? a : 0x8000u; }
__device__ __forceinline__ void gen_store(uint4* p, uint32_t a, uint32_t b, uint32_t c, uint32_t d) {
  asm volatile("{\n.reg .b128 t;\n.reg .b64 lo, hi;\nmov.b64 lo, {%0, %1};\nmov.b64 hi, {%2, %3};\nmov.b128 t, {lo, hi};\nst.relaxed.gpu.b128 [%4], t;\n}"
               :: "r"(a), "r"(b), "r"(c), "r"(d), "l"(p) : "memory");
}
__device__ __forceinline__ void gen_load(const uint4* p, uint32_t* v) {
  asm volatile("{\n.reg .b128 t;\n.reg .b64 lo, hi;\nld.relaxed.gpu.b128 t, [%4];\nmov.b128 {lo, hi}, t;\nmov.b64 {%0, %1}, lo;\nmov.b64 {%2, %3}, hi;\n}"
               : "=r"(v[0]), "=r"(v[1]), "=r"(v[2]), "=r"(v[3]) : "l"(p) : "memory");
}
__device__ __forceinline__ void pkt_load(const uint4* p, uint32_t* v) {
  asm volatile("{\n.reg .b128 t;\n.reg .b64 lo, hi;\nld.relaxed.gpu.global.b128 t, [%4];\nmov.b128 {lo, hi}, t;\nmov.b64 {%0, %1}, lo;\nmov.b64 {%2, %3}, hi;\n}"
               : "=r"(v[0]), "=r"(v[1]), "=r"(v[2]), "=r"(v[3]) : "l"(p) : "memory");
}
__device__ __forceinline__ uint32_t ld_relaxed(const uint32_t* p) { uint32_t v; asm volatile("ld.relaxed.gpu.global.u32 %0, [%1];" : "=r"(v) : "l"(p) : "memory"); return v; }
__device__ __forceinline__ uint4 ld_relaxed4(const void* p) { uint4 v; asm volatile("ld.relaxed.gpu.global.v4.u32 {%0, %1, %2, %3}, [%4];" : "=r"(v.x), "=r"(v.y), "=r"(v.z), "=r"(v.w) : "l"(p) : "memory"); return v; }
__device__ __forceinline__ void st_relaxed(uint32_t* p, uint32_t v) { asm volatile("st.relaxed.gpu.global.u32 [%0], %1;" :: "l"(p), "r"(v) : "memory"); }
__device__ __forceinline__ void st_relaxed2(void* p, uint32_t a, uint32_t b) { asm volatile("st.relaxed.gpu.global.v2.u32 [%0], {%1, %2};" :: "l"(p), "r"(a), "r"(b) : "memory"); }
__device__ __forceinline__ void red_release(uint32_t* p, uint32_t v) { asm volatile("red.release.gpu.global.add.u32 [%0], %1;" :: "l"(p), "r"(v) : "memory"); }
__device__ __forceinline__ uint32_t tagf(float v, uint32_t tag) { return (__float_as_uint(v) & ~15u) | (tag & 15u); }
__device__ __forceinline__ bool tag_ok4(const uint4& v, uint32_t tag) { return (((v.x ^ tag) | (v.y ^ tag) | (v.z ^ tag) | (v.w ^ tag)) & 15u) == 0; }
__device__ __forceinline__ float untag(uint32_t v) { return __uint_as_float(v & ~15u); }
template <typename T> __device__ __forceinline__ T* ptr_add(T* p, uint32_t bytes) {
  uint64_t r;
  asm("{\n.reg .u32 lo, hi;\nmov.b64 {lo, hi}, %1;\nadd.cc.u32 lo, lo, %2;\naddc.u32 hi, hi, 0;\nmov.b64 %0, {lo, hi};\n}" : "=l"(r) : "l"(p), "r"(bytes));
  return (T*)r;
}
#define TL(who, slot) do {} while (0)
#define TLC(slot) do {} while (0)
#define TLE(slot) do {} while (0)
#define ST(who, n) do {} while (0)
#define AP(i) do {} while (0)
#define SP(v) do {} while (0)
#define TLG(slot) do {} while (0)
#define STA() do {} while (0)
#define STB(n) do {} while (0)

__device__ __forceinline__ void wgmma_n128(float (&d)[64], uint64_t da, uint64_t db, int scale_d) {
  asm volatile("{\n.reg .pred p;\nsetp.ne.b32 p, %66, 0;\n"
    "wgmma.mma_async.sync.aligned.m64n128k16.f32.bf16.bf16 "
    "{%0, %1, %2, %3, %4, %5, %6, %7, %8, %9, %10, %11, %12, %13, %14, %15, "
    "%16, %17, %18, %19, %20, %21, %22, %23, %24, %25, %26, %27, %28, %29, %30, %31, "
    "%32, %33, %34, %35, %36, %37, %38, %39, %40, %41, %42, %43, %44, %45, %46, %47, "
    "%48, %49, %50, %51, %52, %53, %54, %55, %56, %57, %58, %59, %60, %61, %62, %63}, "
    "%64, %65, p, 1, 1, 0, 1;\n}\n"
    : "+f"(d[0]), "+f"(d[1]), "+f"(d[2]), "+f"(d[3]), "+f"(d[4]), "+f"(d[5]), "+f"(d[6]), "+f"(d[7]),
      "+f"(d[8]), "+f"(d[9]), "+f"(d[10]), "+f"(d[11]), "+f"(d[12]), "+f"(d[13]), "+f"(d[14]), "+f"(d[15]),
      "+f"(d[16]), "+f"(d[17]), "+f"(d[18]), "+f"(d[19]), "+f"(d[20]), "+f"(d[21]), "+f"(d[22]), "+f"(d[23]),
      "+f"(d[24]), "+f"(d[25]), "+f"(d[26]), "+f"(d[27]), "+f"(d[28]), "+f"(d[29]), "+f"(d[30]), "+f"(d[31]),
      "+f"(d[32]), "+f"(d[33]), "+f"(d[34]), "+f"(d[35]), "+f"(d[36]), "+f"(d[37]), "+f"(d[38]), "+f"(d[39]),
      "+f"(d[40]), "+f"(d[41]), "+f"(d[42]), "+f"(d[43]), "+f"(d[44]), "+f"(d[45]), "+f"(d[46]), "+f"(d[47]),
      "+f"(d[48]), "+f"(d[49]), "+f"(d[50]), "+f"(d[51]), "+f"(d[52]), "+f"(d[53]), "+f"(d[54]), "+f"(d[55]),
      "+f"(d[56]), "+f"(d[57]), "+f"(d[58]), "+f"(d[59]), "+f"(d[60]), "+f"(d[61]), "+f"(d[62]), "+f"(d[63])
    : "l"(da), "l"(db), "r"(scale_d));
}
__device__ __forceinline__ void wgmma_n256(float (&d)[128], uint64_t da, uint64_t db, int scale_d) {
  asm volatile("{\n.reg .pred p;\nsetp.ne.b32 p, %130, 0;\n"
    "wgmma.mma_async.sync.aligned.m64n256k16.f32.bf16.bf16 "
    "{%0, %1, %2, %3, %4, %5, %6, %7, %8, %9, %10, %11, %12, %13, %14, %15, "
    "%16, %17, %18, %19, %20, %21, %22, %23, %24, %25, %26, %27, %28, %29, %30, %31, "
    "%32, %33, %34, %35, %36, %37, %38, %39, %40, %41, %42, %43, %44, %45, %46, %47, "
    "%48, %49, %50, %51, %52, %53, %54, %55, %56, %57, %58, %59, %60, %61, %62, %63, "
    "%64, %65, %66, %67, %68, %69, %70, %71, %72, %73, %74, %75, %76, %77, %78, %79, "
    "%80, %81, %82, %83, %84, %85, %86, %87, %88, %89, %90, %91, %92, %93, %94, %95, "
    "%96, %97, %98, %99, %100, %101, %102, %103, %104, %105, %106, %107, %108, %109, %110, %111, "
    "%112, %113, %114, %115, %116, %117, %118, %119, %120, %121, %122, %123, %124, %125, %126, %127}, "
    "%128, %129, p, 1, 1, 0, 1;\n}\n"
    : "+f"(d[0]), "+f"(d[1]), "+f"(d[2]), "+f"(d[3]), "+f"(d[4]), "+f"(d[5]), "+f"(d[6]), "+f"(d[7]),
      "+f"(d[8]), "+f"(d[9]), "+f"(d[10]), "+f"(d[11]), "+f"(d[12]), "+f"(d[13]), "+f"(d[14]), "+f"(d[15]),
      "+f"(d[16]), "+f"(d[17]), "+f"(d[18]), "+f"(d[19]), "+f"(d[20]), "+f"(d[21]), "+f"(d[22]), "+f"(d[23]),
      "+f"(d[24]), "+f"(d[25]), "+f"(d[26]), "+f"(d[27]), "+f"(d[28]), "+f"(d[29]), "+f"(d[30]), "+f"(d[31]),
      "+f"(d[32]), "+f"(d[33]), "+f"(d[34]), "+f"(d[35]), "+f"(d[36]), "+f"(d[37]), "+f"(d[38]), "+f"(d[39]),
      "+f"(d[40]), "+f"(d[41]), "+f"(d[42]), "+f"(d[43]), "+f"(d[44]), "+f"(d[45]), "+f"(d[46]), "+f"(d[47]),
      "+f"(d[48]), "+f"(d[49]), "+f"(d[50]), "+f"(d[51]), "+f"(d[52]), "+f"(d[53]), "+f"(d[54]), "+f"(d[55]),
      "+f"(d[56]), "+f"(d[57]), "+f"(d[58]), "+f"(d[59]), "+f"(d[60]), "+f"(d[61]), "+f"(d[62]), "+f"(d[63]),
      "+f"(d[64]), "+f"(d[65]), "+f"(d[66]), "+f"(d[67]), "+f"(d[68]), "+f"(d[69]), "+f"(d[70]), "+f"(d[71]),
      "+f"(d[72]), "+f"(d[73]), "+f"(d[74]), "+f"(d[75]), "+f"(d[76]), "+f"(d[77]), "+f"(d[78]), "+f"(d[79]),
      "+f"(d[80]), "+f"(d[81]), "+f"(d[82]), "+f"(d[83]), "+f"(d[84]), "+f"(d[85]), "+f"(d[86]), "+f"(d[87]),
      "+f"(d[88]), "+f"(d[89]), "+f"(d[90]), "+f"(d[91]), "+f"(d[92]), "+f"(d[93]), "+f"(d[94]), "+f"(d[95]),
      "+f"(d[96]), "+f"(d[97]), "+f"(d[98]), "+f"(d[99]), "+f"(d[100]), "+f"(d[101]), "+f"(d[102]), "+f"(d[103]),
      "+f"(d[104]), "+f"(d[105]), "+f"(d[106]), "+f"(d[107]), "+f"(d[108]), "+f"(d[109]), "+f"(d[110]), "+f"(d[111]),
      "+f"(d[112]), "+f"(d[113]), "+f"(d[114]), "+f"(d[115]), "+f"(d[116]), "+f"(d[117]), "+f"(d[118]), "+f"(d[119]),
      "+f"(d[120]), "+f"(d[121]), "+f"(d[122]), "+f"(d[123]), "+f"(d[124]), "+f"(d[125]), "+f"(d[126]), "+f"(d[127])
    : "l"(da), "l"(db), "r"(scale_d));
}
__device__ __forceinline__ void wgmma_rs_n128(float (&d)[64], const uint32_t* a, uint64_t db, int scale_d) {
  asm volatile("{\n.reg .pred p;\nsetp.ne.b32 p, %69, 0;\n"
    "wgmma.mma_async.sync.aligned.m64n128k16.f32.bf16.bf16 "
    "{%0, %1, %2, %3, %4, %5, %6, %7, %8, %9, %10, %11, %12, %13, %14, %15, "
    "%16, %17, %18, %19, %20, %21, %22, %23, %24, %25, %26, %27, %28, %29, %30, %31, "
    "%32, %33, %34, %35, %36, %37, %38, %39, %40, %41, %42, %43, %44, %45, %46, %47, "
    "%48, %49, %50, %51, %52, %53, %54, %55, %56, %57, %58, %59, %60, %61, %62, %63}, "
    "{%64, %65, %66, %67}, %68, p, 1, 1, 1;\n}\n"
    : "+f"(d[0]), "+f"(d[1]), "+f"(d[2]), "+f"(d[3]), "+f"(d[4]), "+f"(d[5]), "+f"(d[6]), "+f"(d[7]),
      "+f"(d[8]), "+f"(d[9]), "+f"(d[10]), "+f"(d[11]), "+f"(d[12]), "+f"(d[13]), "+f"(d[14]), "+f"(d[15]),
      "+f"(d[16]), "+f"(d[17]), "+f"(d[18]), "+f"(d[19]), "+f"(d[20]), "+f"(d[21]), "+f"(d[22]), "+f"(d[23]),
      "+f"(d[24]), "+f"(d[25]), "+f"(d[26]), "+f"(d[27]), "+f"(d[28]), "+f"(d[29]), "+f"(d[30]), "+f"(d[31]),
      "+f"(d[32]), "+f"(d[33]), "+f"(d[34]), "+f"(d[35]), "+f"(d[36]), "+f"(d[37]), "+f"(d[38]), "+f"(d[39]),
      "+f"(d[40]), "+f"(d[41]), "+f"(d[42]), "+f"(d[43]), "+f"(d[44]), "+f"(d[45]), "+f"(d[46]), "+f"(d[47]),
      "+f"(d[48]), "+f"(d[49]), "+f"(d[50]), "+f"(d[51]), "+f"(d[52]), "+f"(d[53]), "+f"(d[54]), "+f"(d[55]),
      "+f"(d[56]), "+f"(d[57]), "+f"(d[58]), "+f"(d[59]), "+f"(d[60]), "+f"(d[61]), "+f"(d[62]), "+f"(d[63])
    : "r"(a[0]), "r"(a[1]), "r"(a[2]), "r"(a[3]), "l"(db), "r"(scale_d));
}

template <int BN> __device__ __forceinline__ void wgmma(float (&d)[BN / 2], uint64_t a, uint64_t b, int s) {
  if constexpr (BN == 128) wgmma_n128(d, a, b, s);
  else wgmma_n256(d, a, b, s);
}

template <int N> __device__ __forceinline__ void acc_fence(float* a) {
#pragma unroll
  for (int i = 0; i < N; i++) asm volatile("" : "+f"(a[i]) :: "memory");
}

#define SELECT8(a, f) do { \
  if ((a) & 4) { if ((a) & 2) { if ((a) & 1) f(7); else f(6); } else { if ((a) & 1) f(5); else f(4); } } \
  else { if ((a) & 2) { if ((a) & 1) f(3); else f(2); } else { if ((a) & 1) f(1); else f(0); } } } while (0)
__device__ __forceinline__ uint32_t lane_now() { uint32_t l; asm volatile("mov.u32 %0, %%laneid;" : "=r"(l)); return l; }

struct Prod {
  uint32_t sb, n, tail, addr, pat, ready;
  uint32_t rank, flip; uint16_t mask;
  __device__ __forceinline__ void load_b(uint32_t dst, uint32_t half, const CUtensorMap* m, uint32_t mstep, uint32_t fb, int k, int ch, int cstep) {
    uint32_t h = rank;
    do { tma_ld3_mc(dst + h * half, ptr_add(m, h * mstep), fb, 0, k * 64, ch + h * cstep, mask); h ^= flip; } while (h != rank);
  }
  __device__ __forceinline__ void load_wide(const Params& P, int ffn, uint32_t dst, uint32_t fb, int k, int ch) {
    load_b(dst, PAGE, &P.map[ffn ? M_W1 : M_WKV], ffn ? 128 : 0, fb, k, ffn ? ch : ch + 16, ffn ? 0 : 16);
  }
  __device__ __forceinline__ void load_narrow(const Params& P, int ffn, uint32_t dst, uint32_t fb, int k, int j) {
    load_b(dst, 8192, &P.map[ffn ? M_W1H : M_WQ], ffn ? 128 : 0, fb, k, ffn ? 48 + j : 2 * j, ffn ? 0 : 1);
  }
  __device__ __forceinline__ void finish() {
#pragma unroll 1
    for (; tail < n; tail++) mbar_wait(sb + BAR_EMPTY + ((tail & 7) << 3), (tail >> 3) & 1);
  }
  template <int PAGES> __device__ __forceinline__ uint32_t acquire(uint32_t& fb) {
    uint32_t nw = pat & 3; pat = (pat >> 2) | 0x40000000u;
#pragma unroll 1
    for (; nw; nw--) { mbar_wait(sb + BAR_EMPTY + ((tail & 7) << 3), (tail >> 3) & 1); tail++; }
    ST(4, n);
    fb = sb + BAR_FULL + ((n & 7) << 3);
    mbar_expect_tx(fb, PAGES * PAGE);
    const uint32_t a = sb + addr;
    addr += PAGES * PAGE; if (addr >= NPAGE * PAGE) addr = 0;
    n++;
    return a;
  }
  const uint32_t* flag; uint32_t base, seen;
  __device__ __forceinline__ void acquire_fence() { asm volatile("fence.acquire.gpu;" ::: "memory"); fence_async_global(); }
  __device__ __forceinline__ void next() {
    uint32_t v, spins = 0;
    seen++;
    do { asm volatile("ld.acquire.cta.shared.u32 %0, [%1];" : "=r"(v) : "r"(sb + SM_SEEN) : "memory"); spin_check(++spins >> 4); } while (v < seen);
    fence_async_global();
  }
  __device__ __forceinline__ void need(uint32_t mask) {
    if ((ready & mask) != mask) {
      uint32_t spins = 0;
      do { ready = ld_relaxed(flag) - base; spin_check(++spins); } while ((ready & mask) != mask);
      acquire_fence();
    }
    ST(5, n - 1);
  }
};

struct Cons {
  uint32_t sb, n, off, prev;
  uint32_t ebar;
  uint32_t da0, db0;
  int lane;
  template <int PAGES> __device__ __forceinline__ void advance() {
    n++; off += PAGES << 10; if (off >= (NPAGE << 10)) off = 0;
    asm volatile("" : "+r"(n), "+r"(off));
  }
  template <int BN, int PAGES> __device__ __forceinline__ void step_ab(float (&acc)[BN / 2], uint32_t da, uint32_t db, int accumulate) {
    STA();
    mbar_wait_fast(sb + BAR_FULL + ((n & 7) << 3), (n >> 3) & 1);
    STB(n);
    const uint64_t da64 = desc64(da), db64 = desc64(db);
    wgmma_fence();
#pragma unroll
    for (int k = 0; k < 4; k++) wgmma<BN>(acc, da64 + 2 * k, db64 + 128 * k, k ? 1 : accumulate);
    wgmma_commit();
    wgmma_wait<1>();
    if (prev && lane < 2) mbar_arrive_cluster(ebar + prev);
    prev = 64 + ((n & 7) << 3);
    advance<PAGES>();
  }
  template <int BN> __device__ __forceinline__ void step(float (&acc)[BN / 2], int accumulate = 1) { step_ab<BN, BN / 128 + 1>(acc, da0 + off, db0 + 1024 + off, accumulate); }
  template <int BN> __device__ __forceinline__ void step_own(float (&acc)[BN / 2], uint32_t da, int accumulate) { step_ab<BN, BN / 128>(acc, da, db0 + off, accumulate); }
  __device__ __forceinline__ void wait_full(uint32_t i) { mbar_wait_fast(sb + BAR_FULL + (((n + i) & 7) << 3), ((n + i) >> 3) & 1); }
  __device__ __forceinline__ void issue_rs2(float (&acc)[64], uint32_t (&a0)[16], uint32_t (&a1)[16], int accumulate) {
    STA(); STB(n);
    const uint64_t db64 = desc64(db0 + off);
    wgmma_fence();
#pragma unroll
    for (int k = 0; k < 4; k++) wgmma_rs_n128(acc, a0 + 4 * k, db64 + 128 * k, k ? 1 : accumulate);
#pragma unroll
    for (int k = 0; k < 4; k++) wgmma_rs_n128(acc, a1 + 4 * k, db64 + 1024 + 128 * k, 1);
    wgmma_commit();
    prev = 64 + ((n & 7) << 3);
    advance<2>();
  }
  template <int BN> __device__ __forceinline__ void steps(float (&acc)[BN / 2], int cnt) {
#pragma unroll 1
    do { step<BN>(acc); } while (--cnt > 0);
  }
  __device__ __forceinline__ void drain() {
    wgmma_wait<0>();
    if (lane < 2) mbar_arrive_cluster(ebar + prev);
    prev = 0;
  }
};

#define MAPPING 2
__device__ __forceinline__ uint32_t role_of_sm(uint32_t smid) {
  const uint32_t t = smid >> 1;
  uint32_t q, i;
  if (t < 32) { q = t & 7; i = t >> 3; }
  else if (t < 60) { const uint32_t u = t - 32, d = (u * 37) >> 8; q = 1 + u - d * 7; i = 4 + d; }
  else if (t < 62) return 128 + smid - 120;
  else { q = 0; i = t - 58; }
  return (q * 2 + (smid & 1)) * 8 + i;
}

template <typename T> __device__ __forceinline__ T* scratch(const Params& P, uint32_t off) { return (T*)ptr_add(P.scratch, off); }
__device__ __forceinline__ uint32_t* epoch_ptr(const Params& P) { uint32_t b; asm volatile("mov.u32 %0, %%ctaid.x;" : "=r"(b)); return scratch<uint32_t>(P, G_EPOCH + b * 4u); }

__device__ __forceinline__ int o_chunk(int s, int j) { const int hf = s >= 9, m = s - 2 - 7 * hf; return s < 2 ? 2 * j + s : 2 * (m == j ? 7 : m) + hf; }

__global__ void __cluster_dims__(2, 1, 1) __launch_bounds__(384, 1) fused_kernel(const __grid_constant__ Params P) {
  extern __shared__ __align__(1024) uint8_t smem_raw[];
  SP(0);
  const uint32_t sb = __shfl_sync(0xffffffffu, smem_u32(smem_raw), 0);
  const int warp = __shfl_sync(0xffffffffu, threadIdx.x >> 5, 0);
  const int lane = threadIdx.x & 31;
  if (warp == 7 && elect_one()) { prefetch_map(&P.map[M_XIN64]); prefetch_map(&P.map[M_WKV]); prefetch_map(&P.map[M_XIN]); }
  uint32_t role = blockIdx.x < 128 ? ((blockIdx.x >> 4) * 2 + (blockIdx.x & 1)) * 8 + ((blockIdx.x >> 1) & 7) : blockIdx.x;
  if (P.use_smid) { uint32_t smid; asm volatile("mov.u32 %0, %%smid;" : "=r"(smid)); role = role_of_sm(smid); }
  const bool spare = role >= 128;
  const int g = role >> 3, j = role & 7;
  uint32_t rank; asm("mov.u32 %0, %%cluster_ctarank;" : "=r"(rank));
  auto shared_b = [&]() {
    uint32_t peer;
    asm volatile("ld.shared::cluster.u32 %0, [%1];" : "=r"(peer) : "r"(mapa(sb + SM_ROLE, rank ^ 1)) : "memory");
    return !spare && peer < 128 && (peer & 7) == (uint32_t)j;
  };
  SP(1);

  if (warp >= 8) {
    asm volatile("setmaxnreg.dec.sync.aligned.u32 40;");
    if (elect_one()) {
      if (warp == 8) {
#pragma unroll
        for (int i = 0; i < 6; i++) mbar_init(sb + BAR_FULL + 8 * i, 1);
        mbar_init(sb + BAR_XIN, 1); mbar_init(sb + BAR_XIN + 8, 1);
      } else if (warp == 9) {
#pragma unroll
        for (int i = 0; i < 8; i++) mbar_init(sb + BAR_EMPTY + 8 * i, 16);
      } else if (warp == 10) {
#pragma unroll
        for (int i = 0; i < 4; i++) mbar_init(sb + BAR_SFULL + 8 * i, 4);
        mbar_init(sb + BAR_CLR, 1); mbar_init(sb + BAR_FULL + 48, 1); mbar_init(sb + BAR_FULL + 56, 1);
      } else {
        sts128(sb + SM_ROLE, role, 0, 0, 0);
        mbar_init(sb + BAR_TAG, 1); mbar_init(sb + BAR_XFULL, 8); mbar_init(sb + BAR_CSE, 8);
        mbar_init(sb + BAR_SEMPTY, 1); mbar_init(sb + BAR_CSF, 1); mbar_init(sb + BAR_CSF + 8, 2);
      }
      asm volatile("fence.mbarrier_init.release.cluster;\nfence.release.sync_restrict::shared::cta.cluster;" ::: "memory");
      fence_async_smem();
    }
    __syncwarp();
    SP(2);
    asm volatile("barrier.cluster.arrive.relaxed.aligned;" ::: "memory");
    if (warp == 8 && !spare) {
      if (elect_one()) {
        const int par = g & 1, row = (g >> 1) * 128;
#pragma unroll 1
        for (int s = 0; s < 2; s++) {
          const uint32_t xb = sb + BAR_XIN + 8 * s, fb = sb + BAR_FULL + 8 * s;
          mbar_expect_tx(xb, PAGE); mbar_expect_tx(fb, 2 * PAGE);
#pragma unroll
          for (int h = 0; h < 2; h++) tma_ld3(sb + SM_STAGE + h * PAGE + s * 8192, &P.map[M_XIN64], xb, s * 64, par, row + h * 64);
#pragma unroll
          for (int h = 0; h < 2; h++) tma_ld3(sb + (2 * s + h) * PAGE, &P.map[M_WKV], fb, 0, s * 64, 16 + 16 * h + 2 * j);
        }
#pragma unroll 1
        for (int s = 0; s < 2; s++) {
          const uint32_t fb = sb + BAR_FULL + 16 + 8 * s;
          mbar_expect_tx(fb, PAGE);
          tma_ld3(sb + (4 + s) * PAGE, &P.map[M_WKV], fb, 0, s * 64, 2 * j);
        }
#pragma unroll 1
        for (int s = 0; s < 2; s++) {
          const uint32_t fb = sb + BAR_FULL + 32 + 8 * s, a = sb + (6 + 3 * s) * PAGE;
          const int k = (j == 1 ? 4 : 2) + s;
          mbar_expect_tx(fb, 3 * PAGE);
          tma_ld3(a, &P.map[M_XIN], fb, k * 64, par, row);
#pragma unroll
          for (int h = 0; h < 2; h++) tma_ld3(a + PAGE + h * PAGE, &P.map[M_WKV], fb, 0, k * 64, 16 + 16 * h + 2 * j);
        }
        spin_check((sb & 1023) << 22);
      }
      __syncwarp();
    }
    SP(3);
    asm volatile("barrier.cluster.wait.acquire.aligned;" ::: "memory");
    SP(4);
    if (warp == 8) {
      if (elect_one()) {
        Prod p; p.sb = sb; p.n = 0; p.tail = 0; p.ready = 0; p.addr = 0;
        { const bool mc = shared_b(); p.rank = rank; p.flip = !mc; p.mask = mc ? 3 : 1 << rank; }
        uint32_t fb;
        if (spare) {
          p.pat = 0x55555000u;
#pragma unroll 1
          for (int r = -1; r < 7; r++) {
            const int ch = r < 0 ? 4 * j : ((r < 2 ? r : r == 2 ? 6 : r - 1) * 4 + j) * 2;
#pragma unroll 1
            for (int k = 0; k < 16; k++) { const uint32_t a = p.acquire<2>(fb); p.load_b(a, PAGE, &P.map[r < 0 ? M_WKV : M_W1], r < 0 ? 0 : 128, fb, k, ch, r < 0 ? 2 : 0); }
          }
        } else {
          p.seen = 0;
          const int xpar = g & 1, xrow = (g >> 1) * 128;
          SP(5);
#pragma unroll 1
          for (int hl = 0; hl < 4; hl++) {
            const int ffn = hl & 1;
            const CUtensorMap* xmap = &P.map[hl ? M_OUT_LD : M_XIN];
            if (hl) {
              p.pat = ffn ? Pat<3>::v : Pat<7>::v;
#pragma unroll 1
              for (int s = 0; s < 2; s++) { const uint32_t a = p.acquire<2>(fb); p.load_wide(P, ffn, a, fb, 2 * j + s, 2 * j); }
#pragma unroll 1
              for (int s = 0; s < 2; s++) { const uint32_t a = p.acquire<1>(fb); p.load_narrow(P, ffn, a, fb, 2 * j + s, j); }
            } else { p.pat = (Pat<0>::v >> 12) | 0x55500000u; p.addr = 0; p.n = 6; }
            if (hl == 0) SP(6);
            uint32_t fb0 = 0;
#pragma unroll 1
            for (int m = hl ? 0 : 2; m < 14; m++) {
              const int hf = m >= 7, mm = m - 7 * hf, jj = mm == j ? 7 : mm;
              int k = 2 * jj + hf;
              if (hl == 0) {
                const int pr = (m >> 1) + 1;
                k = 2 * (j && pr == 2 ? j : pr == j ? 2 : pr) + (m & 1);
              }
              const uint32_t a = p.acquire<3>(fb);
              p.load_wide(P, ffn, a + PAGE, fb, k, 2 * j);
              if (hl) {
                if (m == 0) { fb0 = fb; continue; }
                if (m == 1) {
                  const int j0 = j ? 0 : 7;
                  p.flag = scratch<uint32_t>(P, g * G_BLOCK + G_FLAGS + (ffn ? (hl >> 1) * EV_N + EV_XA : EV_XB) * 128);
                  p.ready = 0; p.need((1u << j0) | (1u << j));
                  tma_ld3(a - 3 * PAGE, xmap, fb0, j0 * 128, xpar, xrow);
                }
                if (m < 7) p.need(1u << jj); else if (m == 7) p.next();
              }
              tma_ld3(a, xmap, fb, k * 64, xpar, xrow);
            }
            if (hl == 0) { mbar_wait(sb + BAR_TAG, 0); asm volatile("ld.shared.u32 %0, [%1];" : "=r"(p.base) : "r"(sb + SM_TAG) : "memory"); p.base = (p.base - 1) * 255; }
            static_assert(Pat<1>::v == Pat<4>::v, "");
            p.pat = Pat<1>::v; p.addr += 2 * PAGE;
#pragma unroll 1
            for (int m = 0; m < 14; m++) {
              const int k = (m >> 1) == (hl ? j : 0) ? 14 + (m & 1) : m;
              const uint32_t a = p.acquire<2>(fb);
              p.load_narrow(P, ffn, a + PAGE, fb, k, j);
              tma_ld3(a, xmap, fb, k * 64, xpar, xrow);
            }
            if (!ffn) {
              p.pat = Pat<2>::v;
              uint32_t a = 0;
#pragma unroll 1
              for (int s = 0; s < 16; s++) {
                if (!(s & 1)) a = p.acquire<2>(fb); else a += PAGE;
                p.load_b(a, 8192, &P.map[M_WO], 0, fb, o_chunk(s, j), 2 * j, 1);
              }
              a = p.acquire<2>(fb);
              tma_ld3(a, xmap, fb, j * 128, xpar, xrow); tma_ld3(a + PAGE, xmap, fb, j * 128 + 64, xpar, xrow);
            } else {
              p.pat = Pat<5>::v;
#pragma unroll 1
              for (int s = 16; s < 48; s++) {
                const int pi = (s >> 1) & 7;
                const int k = (s < 32 ? pi : pi == 4 ? j : pi == j ? 4 : pi) * 2 + (s & 1);
                const uint32_t a = p.acquire<3>(fb);
                p.load_wide(P, 1, a + PAGE, fb, k, (s & 48) + 2 * j);
                tma_ld3(a, xmap, fb, k * 64, xpar, xrow);
              }
              p.pat = Pat<6>::v; p.addr += 2 * PAGE;
#pragma unroll 1
              for (int q = 0; q < 4; q++) {
                p.next();
                const int k0 = q == 0 ? 0 : q == 1 ? 48 : q * 16 - 16, k1 = k0 + (q == 1 ? 8 : 16);
#pragma unroll 1
                for (int k = k0; k < k1; k++) {
                  const uint32_t a = p.acquire<2>(fb);
                  p.load_b(a + PAGE, 8192, &P.map[M_W2], 0, fb, k, 2 * j, 1);
                  tma_ld3(a, &P.map[M_H_LD], fb, k * 64, g, 0);
                }
              }
            }
            TL(2, 1 + hl);
          }
        }
        p.finish();
      }
    } else if (!spare) {
      mbar_wait(sb + BAR_XIN, 0);
      if (elect_one()) {
#pragma unroll 1
        for (int i = warp - 9; i < 8; i += 3) prefetch_l2(ptr_add(P.wqkv, (i * 128 + role) * 6144u + 2048u), 4096);
      }
      uint32_t tag;
      {
        const uint32_t part = warp - 9, col = DM + role * 16 + (lane & 1) * 8;
        const int cnt = part ? 21 : 22;
        const uint4* wp = ptr_add((const uint4*)P.wqkv, ((part ? 16 + part * 336 : 0) + (lane >> 1)) * 6144u + col * 2);
        float s[8] = {0, 0, 0, 0, 0, 0, 0, 0};
        uint4 v[4];
#pragma unroll
        for (int i = 0; i < 4; i++) v[i] = ld_relaxed4(wp + i * (16 * 6144 / 16));
        tag = ld_relaxed(epoch_ptr(P)) + 1;
        if (warp == 10 && lane == 0) { asm volatile("st.shared.u32 [%0], %1;" :: "r"(sb + SM_TAG), "r"(tag) : "memory"); mbar_arrive(sb + BAR_TAG); }
#pragma unroll 1
        for (int b = 4; b < 28; b += 4) {
          wp += 64 * 6144 / 16;
#pragma unroll
          for (int i = 0; i < 4; i++) {
            s[0] += bf_lo(v[i].x); s[1] += bf_hi(v[i].x); s[2] += bf_lo(v[i].y); s[3] += bf_hi(v[i].y);
            s[4] += bf_lo(v[i].z); s[5] += bf_hi(v[i].z); s[6] += bf_lo(v[i].w); s[7] += bf_hi(v[i].w);
            v[i] = make_uint4(0, 0, 0, 0);
            if (b + i < cnt) v[i] = __ldcg(wp + i * (16 * 6144 / 16));
          }
        }
#pragma unroll
        for (int e = 0; e < 4; e++) { const bool h = lane & 16; const float t = __shfl_xor_sync(0xffffffffu, h ? s[e] : s[e + 4], 16); s[e] = (h ? s[e + 4] : s[e]) + t; }
#pragma unroll
        for (int e = 0; e < 2; e++) { const bool h = lane & 8; const float t = __shfl_xor_sync(0xffffffffu, h ? s[e] : s[e + 2], 8); s[e] = (h ? s[e + 2] : s[e]) + t; }
        { const bool h = lane & 4; const float t = __shfl_xor_sync(0xffffffffu, h ? s[0] : s[1], 4); s[0] = (h ? s[1] : s[0]) + t; }
        s[0] += __shfl_xor_sync(0xffffffffu, s[0], 2);
        if (!(lane & 2) || part == 0) st_relaxed(scratch<uint32_t>(P, G_CS + (col + (lane >> 2)) * 16 + ((lane & 2) ? 3 : part) * 4), tagf((lane & 2) ? 0.f : s[0], tag));
        __syncwarp();
      }
      if (warp == 11 && lane == 0) TL(2, 30);
      {
        const uint32_t cspos = sb + SM_CS + ((lane & 16) + ((lane >> 1) & 3) * 4 + ((lane >> 3) & 1) * 2 + (lane & 1)) * 4;
#pragma unroll 1
        for (int it = 0; it < (warp == 10 ? 8 : 1); it++) {
          const int t = it & 3;
          if (it) mbar_wait(sb + BAR_CSE, (it - 1) & 1);
          if (t == 1) mbar_wait(sb + BAR_SEMPTY, 0);
#pragma unroll 1
          for (int b = it ? 0 : warp - 9; b < (it == 0 ? warp - 8 : t < 2 ? 3 : 2); b++) {
            uint32_t c0, c1;
            if (b < 2) { c0 = (t ? 2048 + t * 1024 + b * FF : 1024 + b * 1024) + j * 128; c1 = c0 + 64; }
            else if (t) { c0 = 6144 + j * 64; c1 = c0 + FF; }
            else { c0 = j * 128; c1 = c0 + 64; }
            const uint4* p0 = scratch<uint4>(P, G_CS + (c0 + lane) * 16u);
            const uint4* p1 = scratch<uint4>(P, G_CS + (c1 + lane) * 16u);
            uint4 v[4]; uint32_t spins = 0; bool ok;
            do {
              if (spins) __nanosleep(200);
              v[0] = ld_relaxed4(p0); v[1] = ld_relaxed4(p0 + 32); v[2] = ld_relaxed4(p1); v[3] = ld_relaxed4(p1 + 32);
              ok = tag_ok4(v[0], tag) && tag_ok4(v[1], tag) && tag_ok4(v[2], tag) && tag_ok4(v[3], tag);
              spin_check(++spins);
            } while (__any_sync(0xffffffffu, !ok));
#pragma unroll
            for (int m = 0; m < 4; m++) sts32f(cspos + b * 512 + m * 128, (untag(v[m].x) + untag(v[m].y)) + (untag(v[m].z) + untag(v[m].w)));
            __syncwarp();
            if (lane == 0) mbar_arrive(sb + BAR_CSF + (b ? 8 : 0));
          }
          if (lane == 0) { if (t >= 2) mbar_arrive(sb + BAR_CSF + 8); TL(2, 16 + it + (warp == 11 ? 8 : warp == 9 ? 9 : 0)); }
          if (t == 3) {
            if (g >= 2) {
              uint4* op = scratch<uint4>(P, G_HALO + (((it >> 2) * 16 + g - 2) * 8 + j) * 4096u + lane * 16u);
#pragma unroll 1
              for (int i = 0; i < 8; i++) { st_b128(op, 0, 0, 0, 0); op += 32; }
            }
          }
        }
      }
      if (warp == 11) {
        if (elect_one()) prefetch_l2(ptr_add(P.wo, role * 16384u), 16384);
        uint32_t* const fl = scratch<uint32_t>(P, g * G_BLOCK + G_FLAGS);
        uint32_t seen = 0;
#pragma unroll 1
        for (int e = EV_XA; e < EV_N + EV_XB; e++) {
          if (e == EV_XB) continue;
          const bool clr = (e & 7) == EV_XA;
          uint32_t* const f = ptr_add(fl, (clr ? 16 + e : e) * 128u);
          if (clr) {
            uint4* op = scratch<uint4>(P, g * G_BLOCK + G_O + j * 32768u + lane * 16u);
#pragma unroll 1
            for (int i = 0; i < 64; i++) { st_b128(op, 0, 0, 0, 0); op += 32; if (e || (i & 1)) __nanosleep(10); }
            __syncwarp();
            if (lane == 0) red_release(f, 1u << j);
          }
          uint32_t spins = 0, m;
          while ((m = ld_relaxed(f) - (tag - 1) * 255) != 255) { __nanosleep(m ? 50 : 500); spin_check(++spins); }
          asm volatile("fence.acquire.gpu;" ::: "memory");
          if (lane == 0) {
            if (clr) mbar_arrive(sb + BAR_CLR);
            else asm volatile("st.release.cta.shared.u32 [%0], %1;" :: "r"(sb + SM_SEEN), "r"(++seen) : "memory");
          }
          if (e == EV_H3) {
#pragma unroll 1
            for (int i = 0; i < 7; i++) { if (elect_one()) prefetch_l2(ptr_add(P.w2, (i * 128 + role) * 8192u), 8192); __nanosleep(500); }
          }
          __syncwarp();
        }
      } else if (warp == 9) {
        if (elect_one()) {
          prefetch_map(&P.map[M_WQ]); prefetch_map(&P.map[M_OUT_LD]); prefetch_map(&P.map[M_WO]); prefetch_map(&P.map[M_W1 + rank]);
          prefetch_map(&P.map[M_H_ST]); prefetch_map(&P.map[M_H_LD]); prefetch_map(&P.map[M_W1H + rank]); prefetch_map(&P.map[M_W2]); prefetch_map(&P.map[M_OUT_ST]);
          uint32_t* fl = scratch<uint32_t>(P, g * G_BLOCK + G_FLAGS);
          int pe = 0;
#pragma unroll 1
          for (int e = 0; e < 2 * EV_N; e++) {
            const int q = e & 7;
            const bool is_h = q >= EV_H0 && q < EV_XB, last = e >= EV_N + EV_XB;
            const CUtensorMap* map = &P.map[is_h ? M_H_ST : M_OUT_ST];
            const int col = q == EV_H3 ? 3072 - 64 + j * 64 : (q == EV_H1 ? 1024 : q == EV_H2 ? 2048 : 0) + j * 128;
            const int row = is_h ? 0 : (g >> 1) * 128, par = is_h ? g : g & 1;
#pragma unroll 1
            for (int hb = is_h ? q == EV_H3 : q & 1; hb <= (is_h ? 1 : q & 1); hb++) {
#pragma unroll
              for (int wg = 0; wg < 2; wg++) {
                mbar_wait(sb + BAR_SFULL + 16 * wg + 8 * (pe & 1), (pe >> 1) & 1);
                if (wg == 0) TL(3, 20 + e);
                tma_st3(map, sb + SM_STAGE + wg * PAGE + hb * 8192, col + hb * 64, par, row + wg * 64);
              }
              pe++;
            }
            bulk_commit();
            if (e != EV_N + EV_XB) bulk_wait<0>();
            TL(3, 40 + e);
            if (is_h || (q & 1)) mbar_arrive(sb + BAR_SEMPTY);
            if (!last) red_release(fl, 1u << j);
            TL(3, e);
            fl += 32;
          }
          *epoch_ptr(P) = tag;
        }
      }
    }
  } else {
    if (!spare) {
      if (warp == 0) asm volatile("prefetch.global.L2 [%0];" :: "l"(ptr_add(P.x, (2 * ((g >> 1) * 128 + j * 16 + (lane >> 1)) + (g & 1)) * 2048u + (lane & 1) * 128u)));
      else if (warp < 3 && (warp == 1 || lane < 16)) asm volatile("prefetch.global.L2 [%0];" :: "l"(ptr_add(P.wqkv, role * 6144u + (warp - 1) * 4096u + lane * 128u)));
      __syncwarp();
    }
    asm volatile("barrier.cluster.arrive.relaxed.aligned;" ::: "memory");
    asm volatile("setmaxnreg.inc.sync.aligned.u32 232;");
    SP(4);
    asm volatile("barrier.cluster.wait.acquire.aligned;" ::: "memory");
    SP(5);
    const int wg = warp >> 2;
    const int quad = lane & 3, gr = lane >> 2;
    Cons c; c.sb = sb; c.n = 0; c.off = 0; c.prev = 0; c.lane = lane;
    c.ebar = mapa(sb + BAR_EMPTY - 64, shared_b() ? lane & 1 : rank);
    const uint32_t stage = sb + SM_STAGE + wg * PAGE;
    const uint32_t dstage = desc_lo(stage, 16);
    if (spare) {
      const uint32_t tag = ld_relaxed(epoch_ptr(P)) + 1;
      const int tid = threadIdx.x & 127;
#pragma unroll
      for (int i = 0; i < 4; i++) sts128(stage + (i * 128 + tid) * 16, 0x3f803f80u, 0x3f803f80u, 0x3f803f80u, 0x3f803f80u);
      fence_async_smem();
      bar_sync(2 + wg, 128);
      c.db0 = desc_lo(sb + wg * PAGE, 8192);
#pragma unroll 1
      for (int r = -1; r < 7; r++) {
        float acc[64];
#pragma unroll 1
        for (int k = 0; k < 16; k++) c.step_ab<128, 2>(acc, dstage, c.db0 + c.off, k);
        c.drain();
        acc_fence<64>(acc);
        {
          float v = 0;
#pragma unroll
          for (int i = 0; i < 32; i++) asm("{\n.reg .pred p;\nsetp.eq.u32 p, %2, %3;\nselp.f32 %0, %1, %0, p;\n}" : "+f"(v) : "f"(acc[4 * (i >> 1) + (i & 1)]), "r"(tid >> 2), "r"(i));
          st_b128(scratch<uint4>(P, G_CS + (uint32_t)((r < 0 ? j * 256 + wg * 128 : 3 * DM + wg * FF + ((r < 2 ? r : r == 2 ? 6 : r - 1) * 4 + j) * 128) + (tid >> 3) * 8 + quad * 2 + (gr & 1)) * 16u),
                  tagf(v, tag), tag & 15u, tag & 15u, tag & 15u);
        }
        __syncwarp();
      }
      if (wg == 0) {
        const uint32_t* p = scratch<uint32_t>(P, (tid >> 3) * G_BLOCK + G_STATS + (tid & 7) * 8u);
        uint32_t spins = 0;
        while (__any_sync(0xffffffffu, (ld_relaxed(p) ^ tag) & 15u)) spin_check(++spins);
      }
      bar_sync(1, 256);
      if (threadIdx.x == 0) *epoch_ptr(P) = tag;
    } else {
    c.da0 = desc_lo(sb + wg * 8192, 16); c.db0 = desc_lo(sb, 8192);
    uint32_t sphase = 1, sfull = sb + BAR_SFULL + 16 * wg;
    const uint32_t maddr = stage + ((warp & 3) * 16 + (lane & 15)) * 128 + (((lane >> 4) ^ (lane & 7)) << 4);
    const uint32_t csaddr = sb + SM_CS + quad * 16;
    float st[8] = {0, 0, 0, 0, 0, 0, 0, 0};
    float* const mean = st; float* const rstd = st + 2;
    SP(6);

    auto stage_wait = [&]() { mbar_wait_fast(sb + BAR_SEMPTY, sphase); sphase ^= 1; };
    auto stage_publish = [&]() { fence_async_smem(); __syncwarp(); if (lane == 0) mbar_arrive(sfull); sfull ^= 8; };
    auto cs_load = [&](uint32_t (&cs)[16], int grp) {
#pragma unroll
      for (int i = 0; i < 4; i++) lds128(csaddr + grp * 256 + i * 64, cs[4 * i], cs[4 * i + 1], cs[4 * i + 2], cs[4 * i + 3]);
    };
    auto cs_apply = [&](float* acc, uint32_t (&cs)[16]) {
      acc_fence<32>(acc);
#pragma unroll
      for (int b = 0; b < 8; b++) {
        acc[4 * b] -= mean[0] * __uint_as_float(cs[2 * b]); acc[4 * b + 1] -= mean[0] * __uint_as_float(cs[2 * b + 1]);
        acc[4 * b + 2] -= mean[1] * __uint_as_float(cs[2 * b]); acc[4 * b + 3] -= mean[1] * __uint_as_float(cs[2 * b + 1]);
      }
      acc_fence<32>(acc);
    };
    auto glu_pair = [&](float g0, float g1, float u0, float u1, int r) {
      const float nl = -LOG2E * rstd[r], r2 = rstd[r] * rstd[r];
      return pack_bf16(g0 * u0 * r2 * rcp(1.0f + ex2(g0 * nl)), g1 * u1 * r2 * rcp(1.0f + ex2(g1 * nl)));
    };
    auto glu_slice = [&](uint32_t (&pk)[64], int i) {
      uint32_t hp[4];
#pragma unroll
      for (int e = 0; e < 4; e++) {
        asm volatile("" : "+r"(pk[4 * i + e]), "+r"(pk[32 + 4 * i + e]));
        const uint32_t pg = pk[4 * i + e], pu = pk[32 + 4 * i + e];
        hp[e] = glu_pair(bf_lo(pg), bf_hi(pg), bf_lo(pu), bf_hi(pu), e & 1);
      }
      stsm4((maddr ^ ((i & 3) << 5)) + (i >> 2) * 8192, hp[0], hp[1], hp[2], hp[3]);
    };
    auto glu_slice_acc = [&](float (&acc)[128], int i) {
      uint32_t hp[4];
      acc_fence<8>(acc + 8 * i);
#pragma unroll
      for (int e = 0; e < 4; e++) hp[e] = glu_pair(acc[8 * i + 2 * e], acc[8 * i + 2 * e + 1], acc[64 + 8 * i + 2 * e], acc[64 + 8 * i + 2 * e + 1], e & 1);
      stsm4((maddr ^ ((i & 3) << 5)) + (i >> 2) * 8192, hp[0], hp[1], hp[2], hp[3]);
    };
    auto stage_x = [&](float (&x)[64], uint32_t (&r)[32], int hf) {
#pragma unroll
      for (int i = 4 * hf; i < 4 * hf + 4; i++) {
        uint32_t v[4];
#pragma unroll
        for (int e = 0; e < 4; e++) v[e] = add_bf16x2(r[4 * i + e], pack_bf16(x[8 * i + 2 * e], x[8 * i + 2 * e + 1]));
        stsm4((maddr ^ ((i & 3) << 5)) + hf * 8192, v[0], v[1], v[2], v[3]);
      }
      stage_publish();
    };

    float acc[128];
    mbar_wait_fast(sb + BAR_XIN, 0);
    SP(7);
    c.step_own<256>(acc, dstage, 0);
    mbar_wait_fast(sb + BAR_XIN + 8, 0);
    SP(8);
#pragma unroll 1
    for (int hl = 0;; hl++) {
      int t = hl & 1;
      float acc2[64];
      uint32_t res[32];
      c.step_own<256>(acc, dstage + 512, 1);
#pragma unroll
      for (int s = 0; s < 2; s++) c.step_own<128>(acc2, dstage + s * 512, s);
#pragma unroll 1
      for (int s = 2; s < 11; s++) {
        const uint32_t apage = (c.off << 4) - (SM_STAGE + wg * 8192);
        c.step<256>(acc);
        int act = s;
        asm volatile("" : "+r"(act));
        auto get_tag = [&]() { uint32_t tag; asm volatile("ld.shared.u32 %0, [%1];" : "=r"(tag) : "r"(sb + SM_TAG) : "memory"); return tag; };
        auto stat_ptr = [&]() { return scratch<uint2>(P, g * G_BLOCK + G_STATS + (hl * 128 + warp * 16 + (lane_now() >> 2)) * 64u); };
        auto stat_get = [&]() {
          const uint2* sp = ptr_add(stat_ptr(), (lane_now() & 3) * 16);
          const uint4 a = ld_relaxed4(sp), b = ld_relaxed4(sp + 64);
          st[0] = __uint_as_float(a.x); st[1] = __uint_as_float(a.y); st[2] = __uint_as_float(a.z); st[3] = __uint_as_float(a.w);
          st[4] = __uint_as_float(b.x); st[5] = __uint_as_float(b.y); st[6] = __uint_as_float(b.z); st[7] = __uint_as_float(b.w);
        };
        switch (act) {
          case 4: case 5: {
            const uint32_t ra = maddr + ((hl || j == 0) ? (s & 1) * 8192 : apage);
#pragma unroll
            for (int i = 0; i < 4; i++) {
              uint32_t v[4];
              ldsm4(ra ^ (i << 5), v[0], v[1], v[2], v[3]);
              if (i == 0 && s == 4) { st[0] = bf_lo(v[0]); st[1] = bf_lo(v[1]); st[2] = st[3] = st[4] = st[5] = 0; }
#pragma unroll
              for (int e = 0; e < 4; e++) {
                const float a = bf_lo(v[e]) - st[e & 1], b = bf_hi(v[e]) - st[e & 1];
                st[2 + (e & 1)] += a + b; st[4 + (e & 1)] += a * a; st[4 + (e & 1)] += b * b;
              }
            }
          } break;
          case 6: {
            mbar_wait_fast(sb + BAR_TAG, 0);
            const uint32_t tag = get_tag();
#pragma unroll
            for (int r = 0; r < 2; r++) {
              const float mt = st[r] + st[2 + r] * (1.0f / 32);
              float m = mt + __shfl_xor_sync(0xffffffffu, mt, 1); m += __shfl_xor_sync(0xffffffffu, m, 2); m *= 0.25f;
              float q = st[4 + r] - st[2 + r] * st[2 + r] * (1.0f / 32) + 32.0f * (mt - m) * (mt - m);
              q += __shfl_xor_sync(0xffffffffu, q, 1); q += __shfl_xor_sync(0xffffffffu, q, 2);
              if (quad == 0) st_relaxed2(ptr_add(stat_ptr(), r * 512 + j * 8), tagf(m, tag), tagf(q, tag));
            }
          } break;
          case 8: stat_get(); break;
          case 10: {
            const uint32_t tag = get_tag();
            uint32_t spins = 0;
            for (;;) {
              uint32_t bad = 0;
#pragma unroll
              for (int i = 0; i < 8; i++) bad |= __float_as_uint(st[i]) ^ tag;
              if (!__any_sync(0xffffffffu, bad & 15u)) break;
              stat_get(); spin_check(++spins);
            }
            float mr[4];
#pragma unroll
            for (int r = 0; r < 2; r++) {
              const float m0 = untag(__float_as_uint(st[4 * r])), m1 = untag(__float_as_uint(st[4 * r + 2]));
              float m = m0 + m1; m += __shfl_xor_sync(0xffffffffu, m, 1); m += __shfl_xor_sync(0xffffffffu, m, 2); m *= 0.125f;
              float q = untag(__float_as_uint(st[4 * r + 1])) + untag(__float_as_uint(st[4 * r + 3])) + 128.0f * ((m0 - m) * (m0 - m) + (m1 - m) * (m1 - m));
              q += __shfl_xor_sync(0xffffffffu, q, 1); q += __shfl_xor_sync(0xffffffffu, q, 2);
              mr[r] = m; mr[2 + r] = rsqrtf(fmaxf(q, 0.f) * (1.0f / DM) + LN_EPS);
            }
            st[0] = mr[0]; st[1] = mr[1]; st[2] = mr[2]; st[3] = mr[3];
          } break;
          default: break;
        }
      }
#pragma unroll 1
      for (;;) {
      const int it = (hl >> 1) * 4 + t;
#pragma unroll
      for (int s = 0; s < 4; s++) {
        uint32_t cs[16];
        c.step<256>(acc);
        if (!(s & 1)) mbar_wait_fast(sb + BAR_CSF + 4 * s, t & 1);
        if (s >= 2 && t <= 1) { cs_load(cs, 2 + s); cs_apply(acc2 + 32 * (s - 2), cs); }
        cs_load(cs, s);
        c.drain();
        cs_apply(acc + 32 * s, cs);
      }
      c.step<256>(acc);
      if (lane == 0) mbar_arrive(sb + BAR_CSE);
      c.drain();
      acc_fence<128>(acc);
      TLC(1 + it * 6);
      if (t != 2) c.off += 2 << 10;
      uint32_t pkB[64];
      if (t == 2) {
#pragma unroll
        for (int i = 0; i < 64; i++) pkB[i] = pack_bf16(acc[2 * i], acc[2 * i + 1]);
      } else if (t == 0) {
        uint32_t pkA[64];
        auto kv_pack = [&](int v, int r) {
#pragma unroll
          for (int i = 32 * v + r; i < 32 * v + 32; i += 2) { acc_fence<2>(acc + 2 * i); pkA[i] = pack_bf16(acc[2 * i] * rstd[r], acc[2 * i + 1] * rstd[r]); }
        };
        const uint32_t l16 = lane_now() * 16u;
        uint4* const xs = ptr_add((uint4*)smem_raw, SM_STAGE + l16);
        uint4* const hp = scratch<uint4>(P, G_HALO + (((hl >> 1) * 16 + g) * 8 + j) * 4096u + l16);
        {
          uint4* const dst = (warp == 7 && g < 14) ? hp : ptr_add(xs, warp * 4096u);
#pragma unroll
          for (int s = 0; s < 2; s++) {
            c.steps<128>(acc2, s ? 2 : 1 + wg);
            if (s == 0) stage_wait();
            kv_pack(s, 1);
#pragma unroll
            for (int i = 4 * s; i < 4 * s + 4; i++) { pkA[8 * i + 1] = pkt_head(pkA[8 * i + 1]); gen_store(dst + i * 32, pkA[8 * i + 1], pkA[8 * i + 3], pkA[8 * i + 5], pkA[8 * i + 7]); }
          }
        }
        __syncwarp();
        if (lane == 0) mbar_arrive(sb + BAR_XFULL);
#pragma unroll
        for (int s = 0; s < 2; s++) {
          c.steps<128>(acc2, 2);
#pragma unroll
          for (int i = 33 - s; i < 64; i += 2) pkA[i] = movm(pkA[i]);
          kv_pack(1 - s, 0);
        }
        uint32_t kvH[32];
        {
          const uint4* const src = (warp == 0 && g >= 2) ? hp - 2 * 8 * 256 : ptr_add(xs, (warp ? warp - 1 : 0) * 4096u);
          c.steps<128>(acc2, 2);
          mbar_wait_fast(sb + BAR_XFULL, hl >> 1);
#pragma unroll
          for (int i = 0; i < 8; i++) gen_load(src + i * 32, kvH + 4 * i);
          c.steps<128>(acc2, 3 - wg);
          uint32_t spins = 0;
          while (__any_sync(0xffffffffu, !(kvH[0] && kvH[4] && kvH[8] && kvH[12] && kvH[16] && kvH[20] && kvH[24] && kvH[28]))) {
#pragma unroll
            for (int i = 0; i < 8; i++) gen_load(src + i * 32, kvH + 4 * i);
            spin_check(++spins);
          }
        }
#pragma unroll
        for (int i = 16; i < 32; i++) kvH[i] = movm(kvH[i]);
        mbar_wait_fast(sb + BAR_CLR, hl >> 1);
        c.steps<128>(acc2, 2);
        AP(0);
        c.wait_full(0);
        AP(1);
        c.drain();
        AP(2);
        acc_fence<64>(acc2);
        TLC(2 + it * 6);
        uint32_t q[32];
#pragma unroll
        for (int i = 0; i < 32; i++) q[i] = pack_bf16(acc2[2 * i], acc2[2 * i + 1]);
        const uint32_t zm = bar_sync_zero(1, 256);
        AP(3);
        uint32_t ob[4][16];
        uint4* const omail = scratch<uint4>(P, g * G_BLOCK + G_O + warp * 2048u + l16);
        auto o_fetch = [&](uint32_t (&v0)[16], uint32_t (&v1)[16], const uint4* p0, const uint4* p1) {
#pragma unroll
          for (int i = 0; i < 4; i++) pkt_load(p0 + i * 32, v0 + 4 * i);
#pragma unroll
          for (int i = 0; i < 4; i++) pkt_load(p1 + i * 32, v1 + 4 * i);
        };
        {
          const float hv = (warp == 0 && g < 2) ? -INFINITY : 0.f;
          const float hinit[4] = {hv, hv, hv, hv};
          const bool c0 = (2 * quad <= gr), c1 = (2 * quad + 1 <= gr);
          const uint32_t lm = (c0 ? 0xffffu : 0u) | (c1 ? 0xffff0000u : 0u);
          const float sc[2] = {rstd[0] * (0.17677669529663687f * LOG2E), rstd[1] * (0.17677669529663687f * LOG2E)};
          float lg[4][4], mx[4][2];
#pragma unroll
          for (int h = 0; h < 4; h++) {
            const int b = h * 4;
            float sH[4], sL[4], sU[4];
            q[2 * b] |= zm;
            mma16816(sH, q[2 * b], q[2 * b + 1], q[2 * b + 2], q[2 * b + 3], kvH[b], kvH[b + 1], hinit);
            mma16816z(sL, q[2 * b], q[2 * b + 1], q[2 * b + 2], q[2 * b + 3], pkA[2 * b], pkA[2 * b + 2]);
            mma16816z(sU, q[2 * b], q[2 * b + 1], q[2 * b + 2], q[2 * b + 3], pkA[2 * b + 1], pkA[2 * b + 3]);
            mma16816(sH, q[2 * b + 4], q[2 * b + 5], q[2 * b + 6], q[2 * b + 7], kvH[b + 2], kvH[b + 3], sH);
            mma16816(sL, q[2 * b + 4], q[2 * b + 5], q[2 * b + 6], q[2 * b + 7], pkA[2 * b + 4], pkA[2 * b + 6], sL);
            mma16816(sU, q[2 * b + 4], q[2 * b + 5], q[2 * b + 6], q[2 * b + 7], pkA[2 * b + 5], pkA[2 * b + 7], sU);
            lg[h][0] = c0 ? sL[0] : sH[0]; lg[h][1] = c1 ? sL[1] : sH[1]; lg[h][2] = c0 ? sU[2] : sL[2]; lg[h][3] = c1 ? sU[3] : sL[3];
            mx[h][0] = fmaxf(lg[h][0], lg[h][1]); mx[h][1] = fmaxf(lg[h][2], lg[h][3]);
          }
#pragma unroll
          for (int o = 1; o < 4; o <<= 1) {
#pragma unroll
            for (int i = 0; i < 8; i++) mx[i >> 1][i & 1] = fmaxf(mx[i >> 1][i & 1], __shfl_xor_sync(0xffffffffu, mx[i >> 1][i & 1], o));
          }
          AP(4);
          uint32_t z = zm;
#pragma unroll
          for (int hf = 0; hf < 2; hf++) {
#pragma unroll
            for (int hh = 0; hh < 2; hh++) {
              const int h = hf * 2 + hh, b = h * 4;
              const uint32_t pa = pack_bf16(ex2((lg[h][0] - mx[h][0]) * sc[0]), ex2((lg[h][1] - mx[h][0]) * sc[0]));
              const uint32_t pb = pack_bf16(ex2((lg[h][2] - mx[h][1]) * sc[1]), ex2((lg[h][3] - mx[h][1]) * sc[1]));
              float sum[4];
              mma1688z(sum, pa, pb, 0x3f803f80u);
              const uint32_t p0 = pa & ~lm, p1 = pa & z, p2 = pa & lm, p3 = pb & ~lm, p4 = pb & z, p5 = pb & lm;
              const float ra = rcp(sum[0]), rb = rcp(sum[2]);
#pragma unroll
              for (int d = 0; d < 4; d++) {
                float o[4];
                mma16816z(o, p0, p1, p2, p3, kvH[16 + b + d], pkA[32 + 2 * (b + d)]);
                mma1688(o, p4, p5, pkA[32 + 2 * (b + d) + 1], o);
                ob[hf][(hh * 4 + d) * 2] = pack_bf16(o[0] * ra, o[1] * ra); ob[hf][(hh * 4 + d) * 2 + 1] = pack_bf16(o[2] * rb, o[3] * rb);
              }
            }
#pragma unroll
            for (int i = 0; i < 4; i++) ob[hf][4 * i] = pkt_head(ob[hf][4 * i]);
            if (hf == 0) {
              AP(5);
              uint4* op = ptr_add(omail, j * 32768u);
#pragma unroll
              for (int i = 0; i < 4; i++) st_b128(op + i * 32, ob[0][4 * i], ob[0][4 * i + 1], ob[0][4 * i + 2], ob[0][4 * i + 3]);
              z = late_zero(zm);
              AP(6);
            }
          }
#pragma unroll
          for (int i = 0; i < 4; i++) sts128(stage + (warp & 3) * 2048 + i * 512 + l16, ob[1][4 * i], ob[1][4 * i + 1], ob[1][4 * i + 2], ob[1][4 * i + 3]);
          AP(7);
          bar_sync(1, 256);
        }
        TLC(3 + it * 6);
        AP(8);
        uint64_t todo;
        { const uint32_t o7 = 0x6543210u | (7u << (4 * j) & 0xfffffffu); todo = (uint64_t)(o7 * 2) | (uint64_t)(o7 * 2 + 0x1111111u) << 28; }
        const uint4* p0 = ptr_add(omail, ((uint32_t)todo & 15u) << 14);
        const uint4* p1 = ptr_add(omail, ((uint32_t)todo & 240u) << 10);
        auto batch = [&](int b, bool first) {
          uint32_t (&y0)[16] = ob[b ^ 2], (&y1)[16] = ob[b ^ 3];
          o_fetch(y0, y1, p0, p1);
          c.issue_rs2(acc2, ob[b], ob[b + 1], !first);
          const uint32_t z = late_zero(zm);
          todo >>= 8;
          const uint4* n0 = ptr_add(omail, ((uint32_t)todo & 15u) << 14);
          const uint4* n1 = ptr_add(omail, ((uint32_t)todo & 240u) << 10);
          asm volatile("" : "+l"(n0), "+l"(n1));
          c.wait_full(0);
          uint32_t spins = 0;
          while (__builtin_expect(__any_sync(0xffffffffu, (y0[0] == z || y0[4] == z || y0[8] == z || y0[12] == z) | (y1[0] == z || y1[4] == z || y1[8] == z || y1[12] == z)), 0)) {
            o_fetch(y0, y1, p0, p1);
            spin_check(++spins);
          }
          if (first) {
            fence_async_smem();
            __syncwarp();
            if (elect_one()) {
              asm volatile("cp.async.bulk.global.shared::cta.bulk_group [%0], [%1], 2048;"
                           :: "l"(scratch<uint4>(P, g * G_BLOCK + G_O + (2 * j + 1) * 16384u + warp * 2048u)), "r"(stage + (warp & 3) * 2048) : "memory");
              bulk_commit();
            }
          }
          p0 = n0; p1 = n1;
          c.drain();
        };
        batch(0, true);
#pragma unroll 1
        for (int i = 0; i < 3; i++) { batch(2, false); batch(0, false); }
        c.issue_rs2(acc2, ob[2], ob[3], 1);
        if (elect_one()) bulk_wait<0>();
        __syncwarp();
        {
          c.wait_full(0);
          const uint32_t ra = maddr - (SM_STAGE + wg * 8192) + (c.off << 4);
#pragma unroll
          for (int i = 0; i < 8; i++) ldsm4((ra ^ ((i & 3) << 5)) + (i >> 2) * PAGE, res[4 * i], res[4 * i + 1], res[4 * i + 2], res[4 * i + 3]);
          if (lane < 2) mbar_arrive_cluster(c.ebar + 64 + ((c.n & 7) << 3));
          c.advance<2>();
          c.drain();
        }
        break;
      } else {
        c.steps<128>(acc2, 1 + wg);
        stage_wait();
        glu_slice_acc(acc, 0);
#pragma unroll
        for (int s = 1; s < 8; s++) { c.steps<128>(acc2, (s & 1) || t == 3 ? 2 : 1); if (s == 4) stage_publish(); glu_slice_acc(acc, s); }
        c.steps<128>(acc2, 2 - wg);
        stage_publish();
        if (t == 3) {
#pragma unroll
          for (int i = 0; i < 32; i++) { res[i] = 0x80008000u; asm volatile("" : "+r"(res[i])); }
          c.steps<128>(acc2, 39);
          stage_wait();
          c.drain();
          break;
        }
        c.drain();
        TLC(2 + it * 6);
        c.step<256>(acc, 0);
        acc_fence<64>(acc2);
#pragma unroll
        for (int i = 0; i < 16; i++) {
          pkB[16 + i] = pack_bf16(acc2[2 * i], acc2[2 * i + 1]); pkB[48 + i] = pack_bf16(acc2[32 + 2 * i], acc2[32 + 2 * i + 1]);
          pkB[i] = 0; pkB[32 + i] = 0;
        }
      }
      t++;
#pragma unroll 1
      for (int s = 3 - t; s < 8; s++) {
        c.step<256>(acc, s);
        int act = (t == 3 || s >= 4) ? s : 8;
        asm volatile("" : "+r"(act));
        if (act < 8) {
          if (!(act & 3)) { if (act && t == 3) stage_publish(); else stage_wait(); }
          auto f = [&](int i) { glu_slice(pkB, i); };
          SELECT8(act, f);
        }
      }
#pragma unroll
      for (int s = 0; s < 2; s++) {
        const uint32_t ra = maddr - (SM_STAGE + wg * 8192) + (c.off << 4);
        c.step<256>(acc);
        if (s == 0) stage_publish();
#pragma unroll
        for (int i = 0; i < 4; i++) {
          uint32_t v[4];
          ldsm4(ra ^ (i << 5), v[0], v[1], v[2], v[3]);
#pragma unroll
          for (int e = 0; e < 4; e++) { acc2[32 * s + 8 * i + 2 * e] = bf_lo(v[e]); acc2[32 * s + 8 * i + 2 * e + 1] = bf_hi(v[e]); }
        }
        acc_fence<32>(acc2 + 32 * s);
      }
      c.step<256>(acc);
      }
      const int it = (hl >> 1) * 4 + t;
      acc_fence<64>(acc2);
      TLC(4 + it * 6);
      stage_x(acc2, res, 0);
      if (hl == 3) { stage_x(acc2, res, 1); TLE(47); TLG(63); break; }
      bar_sync(2 + wg, 128);
      TLC(5 + it * 6);
      c.step_own<256>(acc, dstage, 0);
      acc_fence<32>(acc2 + 32);
      stage_x(acc2, res, 1);
      bar_sync(2 + wg, 128);
    }
    }
  }
}

typedef CUresult (*EncodeFn)(CUtensorMap*, CUtensorMapDataType, cuuint32_t, void*, const cuuint64_t*, const cuuint64_t*, const cuuint32_t*,
                             const cuuint32_t*, CUtensorMapInterleave, CUtensorMapSwizzle, CUtensorMapL2promotion, CUtensorMapFloatOOBfill);

void encode(EncodeFn fn, CUtensorMap* m, const void* ptr, int rank, const cuuint64_t* dims, const cuuint64_t* strides, const cuuint32_t* box) {
  cuuint32_t es[5] = {1, 1, 1, 1, 1};
  fn(m, CU_TENSOR_MAP_DATA_TYPE_BFLOAT16, rank, const_cast<void*>(ptr), dims, strides, box, es, CU_TENSOR_MAP_INTERLEAVE_NONE,
     CU_TENSOR_MAP_SWIZZLE_128B, CU_TENSOR_MAP_L2_PROMOTION_L2_128B, CU_TENSOR_MAP_FLOAT_OOB_FILL_NONE);
}

}

extern "C" void kernel_launch(void* const* d_in, const int* in_sizes, int n_in, void* d_out, int out_size) {
  const __nv_bfloat16* x = (const __nv_bfloat16*)d_in[0];
  const __nv_bfloat16* wqkv = (const __nv_bfloat16*)d_in[1];
  const __nv_bfloat16* wo = (const __nv_bfloat16*)d_in[2];
  const __nv_bfloat16* w1 = (const __nv_bfloat16*)d_in[4];
  const __nv_bfloat16* w3 = (const __nv_bfloat16*)d_in[5];
  const __nv_bfloat16* w2 = (const __nv_bfloat16*)d_in[6];

  void* fnp = nullptr; cudaDriverEntryPointQueryResult qr;
  cudaGetDriverEntryPoint("cuTensorMapEncodeTiled", &fnp, cudaEnableDefault, &qr);
  EncodeFn fn = (EncodeFn)fnp;
  void* sym;
  cudaGetSymbolAddress(&sym, g_scratch);
  uint8_t* scr = (uint8_t*)(((uintptr_t)sym + G_BLOCK - 1) / G_BLOCK * G_BLOCK);

  Params P = {};
  { cuuint64_t d[3] = {DM, 2, SEQ / 2}, s[2] = {DM * 2, DM * 4}; cuuint32_t b[3] = {64, 1, 128}, b2[3] = {64, 1, 64};
    encode(fn, &P.map[M_XIN], x, 3, d, s, b); encode(fn, &P.map[M_XIN64], x, 3, d, s, b2);
    encode(fn, &P.map[M_OUT_LD], d_out, 3, d, s, b); encode(fn, &P.map[M_OUT_ST], d_out, 3, d, s, b2); }
  { cuuint64_t d[3] = {FF, 16, 128}, s[2] = {G_BLOCK, FF * 2}; cuuint32_t b[3] = {64, 1, 128}, b2[3] = {64, 1, 64};
    encode(fn, &P.map[M_H_LD], scr + G_H, 3, d, s, b); encode(fn, &P.map[M_H_ST], scr + G_H, 3, d, s, b2); }
  { const cuuint32_t b2[3] = {64, 64, 2}, b1[3] = {64, 64, 1};
    { cuuint64_t d[3] = {64, DM, 48}, s[2] = {3 * DM * 2, 128}; encode(fn, &P.map[M_WKV], wqkv, 3, d, s, b2); encode(fn, &P.map[M_WQ], wqkv, 3, d, s, b1); }
    { cuuint64_t d[3] = {64, DM, 16}, s[2] = {DM * 2, 128}; encode(fn, &P.map[M_WO], wo, 3, d, s, b1); }
    { cuuint64_t d[3] = {64, FF, 16}, s[2] = {DM * 2, 128}; encode(fn, &P.map[M_W2], w2, 3, d, s, b1); }
    { cuuint64_t d[3] = {64, DM, FF / 64}, s[2] = {FF * 2, 128};
      encode(fn, &P.map[M_W1], w1, 3, d, s, b2); encode(fn, &P.map[M_W3], w3, 3, d, s, b2);
      encode(fn, &P.map[M_W1H], w1, 3, d, s, b1); encode(fn, &P.map[M_W3H], w3, 3, d, s, b1); }
  }
  P.scratch = scr; P.x = x; P.wqkv = wqkv; P.wo = wo; P.w2 = w2;
  int dev = 0, sms = 0;
  cudaGetDevice(&dev);
  cudaDeviceGetAttribute(&sms, cudaDevAttrMultiProcessorCount, dev);
  P.use_smid = (sms == 132);
  cudaFuncSetAttribute(fused_kernel, cudaFuncAttributeMaxDynamicSharedMemorySize, SM_ALLOC);
  fused_kernel<<<132, 384, SM_ALLOC>>>(P);
}
```

```cpp
#include <cuda_runtime.h>
#include <cuda_bf16.h>
#include <cuda.h>
#include <stdint.h>
#include <math.h>

namespace {

constexpr int SEQ = 2048, DM = 1024, FF = 3584;
constexpr float LN_EPS = 1e-5f;
constexpr float LOG2E = 1.4426950408889634f;

constexpr uint32_t G_BLOCK = 2u << 20;
constexpr uint32_t G_H = 0;
constexpr uint32_t G_O = G_H + 128 * FF * 2;
constexpr uint32_t G_STATS = G_O + 128 * DM * 2;
constexpr uint32_t G_FLAGS = G_STATS + 4 * 128 * 64;
static_assert(G_FLAGS + 4096 <= G_BLOCK, "");
constexpr uint32_t G_HALO = 16 * G_BLOCK;
constexpr uint32_t G_CS = G_HALO + 2 * 16 * 8 * 4096;
constexpr uint32_t G_EPOCH = G_CS + (3 * DM + 2 * FF) * 16;
__device__ __align__(1024) uint8_t g_scratch[18 * G_BLOCK];

enum { M_XIN, M_XIN64, M_H_LD, M_H_ST, M_OUT_LD, M_OUT_ST, M_WKV, M_WQ, M_WO, M_W1, M_W3, M_W1H, M_W3H, M_W2, M_COUNT };
struct alignas(64) Params {
  CUtensorMap map[M_COUNT];
  uint8_t* scratch;
  const __nv_bfloat16* x;
  const __nv_bfloat16* wqkv;
  const __nv_bfloat16* wo;
  const __nv_bfloat16* w2;
  int use_smid;
};

constexpr uint32_t PAGE = 16384, NPAGE = 12;
constexpr uint32_t SM_STAGE = NPAGE * PAGE;
constexpr uint32_t SM_BAR = SM_STAGE + 2 * PAGE;
constexpr uint32_t SM_CS = SM_BAR + 256;
constexpr uint32_t SM_TOTAL = SM_CS + 1536;
constexpr uint32_t SM_ALLOC = SM_TOTAL;
static_assert(SM_ALLOC <= 232448, "shared memory");
constexpr uint32_t BAR_FULL = SM_BAR, BAR_EMPTY = SM_BAR + 64, BAR_SFULL = SM_BAR + 128;
constexpr uint32_t BAR_XFULL = SM_BAR + 160, BAR_CSE = SM_BAR + 168;
constexpr uint32_t BAR_SEMPTY = SM_BAR + 176, BAR_CSF = SM_BAR + 184, BAR_XIN = SM_BAR + 200;
constexpr uint32_t BAR_CLR = SM_BAR + 240, BAR_TAG = SM_BAR + 216, SM_ROLE = SM_BAR + 224, SM_TAG = SM_BAR + 228, SM_SEEN = SM_BAR + 232;
enum { EV_XA, EV_XA2, EV_H0, EV_H3, EV_H1, EV_H2, EV_XB, EV_XB2, EV_N };

#define WO_HOLD 5
struct Sched { uint32_t pat[14]; uint32_t page0[14]; bool ok; };
constexpr int seg_steps(int seg) { return seg == 0 || seg == 3 ? 18 : seg == 1 || seg == 4 ? 14 : seg == 2 ? 9 : seg == 5 ? 32 : 56; }
constexpr int step_pages(int seg, int i) {
  return seg == 0 || seg == 3 ? (i < 2 ? 2 : i < 4 ? 1 : 3) : seg == 5 ? 3 : 2;
}
constexpr Sched make_sched() {
  Sched s = {};
  int owner[NPAGE] = {-1, -1, -1, -1, -1, -1, -1, -1, -1, -1, -1, -1};
  int n = 0, tail = 0, page = 0;
  s.ok = true;
  for (int sg = 0; sg < 14; sg++) {
    const int seg = sg % 7;
    if (seg == 1 || seg == 4 || seg == 6) page += 2;
    s.page0[sg] = page;
    for (int i = 0; i < seg_steps(seg); i++) {
      const int p = step_pages(seg, i);
      if (page + p > (int)NPAGE) { s.ok = false; return s; }
      int need = n - 8;
      for (int q = 0; q < p; q++) { if (owner[page + q] > need) need = owner[page + q]; owner[page + q] = n; }
      if (seg == 3 && i < 4 && need < n - i - WO_HOLD + (i > 2 ? 2 : i)) need = n - i - WO_HOLD + (i > 2 ? 2 : i);
      int nw = need + 1 - tail; if (nw < 0) nw = 0;
      tail += nw;
      if (i < 16) s.pat[sg] |= (uint32_t)nw << (2 * i); else if (nw != 1) s.ok = false;
      if (nw > 3) s.ok = false;
      page = (page + p) % NPAGE; n++;
    }
  }
  for (int sg = 0; sg < 7; sg++) if (s.page0[sg] != s.page0[sg + 7] || (sg && s.pat[sg] != s.pat[sg + 7])) s.ok = false;
  return s;
}
constexpr Sched SCHED = make_sched();
static_assert(SCHED.ok && SCHED.page0[0] == 0 && SCHED.page0[3] == 0 && SCHED.page0[5] == 6 && (SCHED.pat[0] & 0xfff) == 0, "ring schedule");
template <int SEG> struct Pat { static constexpr uint32_t v = SCHED.pat[SEG]; };

#define P_EARLY 1
#define TAIL_LAG 3
__device__ __forceinline__ uint32_t smem_u32(const void* p) { return (uint32_t)__cvta_generic_to_shared(p); }
__device__ __forceinline__ void mbar_init(uint32_t bar, uint32_t cnt) { asm volatile("mbarrier.init.shared::cta.b64 [%0], %1;" :: "r"(bar), "r"(cnt)); }
__device__ __forceinline__ void mbar_expect_tx(uint32_t bar, uint32_t bytes) { asm volatile("mbarrier.arrive.expect_tx.shared::cta.b64 _, [%0], %1;" :: "r"(bar), "r"(bytes) : "memory"); }
__device__ __forceinline__ void mbar_arrive(uint32_t bar) { asm volatile("mbarrier.arrive.shared::cta.b64 _, [%0];" :: "r"(bar) : "memory"); }
__device__ __forceinline__ void mbar_wait(uint32_t bar, uint32_t parity) {
  asm volatile("{\n.reg .pred p;\n.reg .u32 n;\nmov.u32 n, 0;\nLAB_WAIT:\n"
               "mbarrier.try_wait.parity.shared::cta.b64 p, [%0], %1;\n@p bra LAB_DONE;\n"
               "add.u32 n, n, 1;\nsetp.lt.u32 p, n, 4194304;\n@p bra LAB_WAIT;\ntrap;\nLAB_DONE:\n}" :: "r"(bar), "r"(parity) : "memory");
}
__device__ __forceinline__ void mbar_wait_fast(uint32_t bar, uint32_t parity) {
  asm volatile("{\n.reg .pred p;\nLAB_WAIT:\nmbarrier.try_wait.parity.shared::cta.b64 p, [%0], %1;\n@!p bra LAB_WAIT;\n}" :: "r"(bar), "r"(parity) : "memory");
}
__device__ __forceinline__ void spin_check(uint32_t n) { asm volatile("{\n.reg .pred p;\nsetp.ge.u32 p, %0, 4194304;\n@p st.volatile.global.u32 [%1], %0;\n}" :: "r"(n), "l"(0ull)); }
__device__ __forceinline__ void tma_ld3(uint32_t dst, const CUtensorMap* m, uint32_t bar, int c0, int c1, int c2) {
  asm volatile("cp.async.bulk.tensor.3d.shared::cluster.global.mbarrier::complete_tx::bytes [%0], [%1, {%3, %4, %5}], [%2];" :: "r"(dst), "l"(m), "r"(bar), "r"(c0), "r"(c1), "r"(c2) : "memory");
}
__device__ __forceinline__ void tma_ld3_mc(uint32_t dst, const CUtensorMap* m, uint32_t bar, int c0, int c1, int c2, uint16_t mask) {
  asm volatile("cp.async.bulk.tensor.3d.shared::cluster.global.mbarrier::complete_tx::bytes.multicast::cluster [%0], [%1, {%3, %4, %5}], [%2], %6;"
               :: "r"(dst), "l"(m), "r"(bar), "r"(c0), "r"(c1), "r"(c2), "h"(mask) : "memory");
}
__device__ __forceinline__ uint32_t mapa(uint32_t addr, uint32_t cta) { uint32_t r; asm("mapa.shared::cluster.u32 %0, %1, %2;" : "=r"(r) : "r"(addr), "r"(cta)); return r; }
__device__ __forceinline__ void mbar_arrive_cluster(uint32_t bar) { asm volatile("mbarrier.arrive.shared::cluster.b64 _, [%0];" :: "r"(bar) : "memory"); }
__device__ __forceinline__ void tma_st3(const CUtensorMap* m, uint32_t src, int c0, int c1, int c2) {
  asm volatile("cp.async.bulk.tensor.3d.global.shared::cta.bulk_group [%0, {%2, %3, %4}], [%1];" :: "l"(m), "r"(src), "r"(c0), "r"(c1), "r"(c2) : "memory");
}
__device__ __forceinline__ void bulk_commit() { asm volatile("cp.async.bulk.commit_group;" ::: "memory"); }
template <int N> __device__ __forceinline__ void bulk_wait() { asm volatile("cp.async.bulk.wait_group %0;" :: "n"(N) : "memory"); }
__device__ __forceinline__ void fence_async_smem() { asm volatile("fence.proxy.async.shared::cta;" ::: "memory"); }
__device__ __forceinline__ void fence_async_global() { asm volatile("fence.proxy.async.global;" ::: "memory"); }
__device__ __forceinline__ bool elect_one() { uint32_t p; asm volatile("{\n.reg .pred P;\nelect.sync _|P, 0xffffffff;\nselp.u32 %0, 1, 0, P;\n}" : "=r"(p)); return p; }
__device__ __forceinline__ void prefetch_map(const CUtensorMap* m) { asm volatile("prefetch.tensormap [%0];" :: "l"(m) : "memory"); }
__device__ __forceinline__ void prefetch_l2(const void* p, uint32_t bytes) { asm volatile("cp.async.bulk.prefetch.L2.global [%0], %1;" :: "l"(p), "r"(bytes) : "memory"); }
__device__ __forceinline__ void wgmma_fence() { asm volatile("wgmma.fence.sync.aligned;" ::: "memory"); }
__device__ __forceinline__ void wgmma_commit() { asm volatile("wgmma.commit_group.sync.aligned;" ::: "memory"); }
template <int N> __device__ __forceinline__ void wgmma_wait() { asm volatile("wgmma.wait_group.sync.aligned %0;" :: "n"(N) : "memory"); }
__device__ __forceinline__ uint32_t desc_lo(uint32_t addr, uint32_t lbo) { return ((addr & 0x3FFFF) >> 4) | ((lbo >> 4) << 16); }
__device__ __forceinline__ uint64_t desc64(uint32_t lo) { uint64_t r; asm("mov.b64 %0, {%1, %2};" : "=l"(r) : "r"(lo), "r"(0x40000040u)); return r; }
__device__ __forceinline__ void bar_sync(int id, int n) { asm volatile("bar.sync %0, %1;" :: "r"(id), "r"(n) : "memory"); }
__device__ __forceinline__ uint32_t pack_bf16(float lo, float hi) { uint32_t r; asm("cvt.rn.bf16x2.f32 %0, %1, %2;" : "=r"(r) : "f"(hi), "f"(lo)); return r; }
__device__ __forceinline__ float bf_lo(uint32_t v) { return __uint_as_float(v << 16); }
__device__ __forceinline__ float bf_hi(uint32_t v) { return __uint_as_float(v & 0xffff0000u); }
__device__ __forceinline__ float ex2(float x) { float r; asm("ex2.approx.ftz.f32 %0, %1;" : "=f"(r) : "f"(x)); return r; }
__device__ __forceinline__ float rcp(float x) { float r; asm("rcp.approx.ftz.f32 %0, %1;" : "=f"(r) : "f"(x)); return r; }
__device__ __forceinline__ void stsm4(uint32_t a, uint32_t r0, uint32_t r1, uint32_t r2, uint32_t r3) {
  asm volatile("stmatrix.sync.aligned.m8n8.x4.shared.b16 [%0], {%1, %2, %3, %4};" :: "r"(a), "r"(r0), "r"(r1), "r"(r2), "r"(r3) : "memory");
}
__device__ __forceinline__ void ldsm4(uint32_t a, uint32_t& r0, uint32_t& r1, uint32_t& r2, uint32_t& r3) {
  asm volatile("ldmatrix.sync.aligned.m8n8.x4.shared.b16 {%0, %1, %2, %3}, [%4];" : "=r"(r0), "=r"(r1), "=r"(r2), "=r"(r3) : "r"(a) : "memory");
}
__device__ __forceinline__ uint32_t movm(uint32_t v) { uint32_t r; asm volatile("movmatrix.sync.aligned.m8n8.trans.b16 %0, %1;" : "=r"(r) : "r"(v)); return r; }
__device__ __forceinline__ void sts128(uint32_t a, uint32_t r0, uint32_t r1, uint32_t r2, uint32_t r3) {
  asm volatile("st.shared.v4.b32 [%0], {%1, %2, %3, %4};" :: "r"(a), "r"(r0), "r"(r1), "r"(r2), "r"(r3) : "memory");
}
__device__ __forceinline__ void lds128(uint32_t a, uint32_t& r0, uint32_t& r1, uint32_t& r2, uint32_t& r3) {
  asm volatile("ld.shared.v4.b32 {%0, %1, %2, %3}, [%4];" : "=r"(r0), "=r"(r1), "=r"(r2), "=r"(r3) : "r"(a) : "memory");
}
__device__ __forceinline__ uint32_t add_bf16x2(uint32_t a, uint32_t b) { uint32_t r; asm("add.rn.bf16x2 %0, %1, %2;" : "=r"(r) : "r"(a), "r"(b)); return r; }
__device__ __forceinline__ void sts32f(uint32_t a, float v) { asm volatile("st.shared.f32 [%0], %1;" :: "r"(a), "f"(v) : "memory"); }
__device__ __forceinline__ void mma16816(float (&d)[4], uint32_t a0, uint32_t a1, uint32_t a2, uint32_t a3, uint32_t b0, uint32_t b1, const float (&c)[4]) {
  asm("mma.sync.aligned.m16n8k16.row.col.f32.bf16.bf16.f32 {%0, %1, %2, %3}, {%4, %5, %6, %7}, {%8, %9}, {%10, %11, %12, %13};"
      : "=f"(d[0]), "=f"(d[1]), "=f"(d[2]), "=f"(d[3]) : "r"(a0), "r"(a1), "r"(a2), "r"(a3), "r"(b0), "r"(b1), "f"(c[0]), "f"(c[1]), "f"(c[2]), "f"(c[3]));
}
__device__ __forceinline__ void mma1688(float (&d)[4], uint32_t a0, uint32_t a1, uint32_t b0, const float (&c)[4]) {
  asm("mma.sync.aligned.m16n8k8.row.col.f32.bf16.bf16.f32 {%0, %1, %2, %3}, {%4, %5}, {%6}, {%7, %8, %9, %10};"
      : "=f"(d[0]), "=f"(d[1]), "=f"(d[2]), "=f"(d[3]) : "r"(a0), "r"(a1), "r"(b0), "f"(c[0]), "f"(c[1]), "f"(c[2]), "f"(c[3]));
}
__device__ __forceinline__ void mma16816z(float (&d)[4], uint32_t a0, uint32_t a1, uint32_t a2, uint32_t a3, uint32_t b0, uint32_t b1) {
  asm("mma.sync.aligned.m16n8k16.row.col.f32.bf16.bf16.f32 {%0, %1, %2, %3}, {%4, %5, %6, %7}, {%8, %9}, {0f00000000, 0f00000000, 0f00000000, 0f00000000};"
      : "=f"(d[0]), "=f"(d[1]), "=f"(d[2]), "=f"(d[3]) : "r"(a0), "r"(a1), "r"(a2), "r"(a3), "r"(b0), "r"(b1));
}
__device__ __forceinline__ void mma1688z(float (&d)[4], uint32_t a0, uint32_t a1, uint32_t b0) {
  asm("mma.sync.aligned.m16n8k8.row.col.f32.bf16.bf16.f32 {%0, %1, %2, %3}, {%4, %5}, {%6}, {0f00000000, 0f00000000, 0f00000000, 0f00000000};"
      : "=f"(d[0]), "=f"(d[1]), "=f"(d[2]), "=f"(d[3]) : "r"(a0), "r"(a1), "r"(b0));
}
__device__ __forceinline__ uint32_t bar_sync_zero(int id, int n) {
  uint32_t r;
  asm volatile("{\n.reg .pred p;\nsetp.eq.u32 p, %1, 0;\nbarrier.cta.red.popc.aligned.u32 %0, %1, %2, p;\n}" : "=r"(r) : "r"(id), "r"(n) : "memory");
  return r;
}
__device__ __forceinline__ uint32_t late_zero(uint32_t zm) { uint32_t c; asm volatile("mov.u32 %0, %%clock;" : "=r"(c) :: "memory"); return c & zm; }
__device__ __forceinline__ void st_b128(uint4* p, uint32_t a, uint32_t b, uint32_t c, uint32_t d) {
  asm volatile("{\n.reg .b128 t;\n.reg .b64 lo, hi;\nmov.b64 lo, {%0, %1};\nmov.b64 hi, {%2, %3};\nmov.b128 t, {lo, hi};\nst.relaxed.gpu.global.b128 [%4], t;\n}"
               :: "r"(a), "r"(b), "r"(c), "r"(d), "l"(p) : "memory");
}
__device__ __forceinline__ uint32_t pkt_head(uint32_t a) { return a ? a : 0x8000u; }
__device__ __forceinline__ void gen_store(uint4* p, uint32_t a, uint32_t b, uint32_t c, uint32_t d) {
  asm volatile("{\n.reg .b128 t;\n.reg .b64 lo, hi;\nmov.b64 lo, {%0, %1};\nmov.b64 hi, {%2, %3};\nmov.b128 t, {lo, hi};\nst.relaxed.gpu.b128 [%4], t;\n}"
               :: "r"(a), "r"(b), "r"(c), "r"(d), "l"(p) : "memory");
}
__device__ __forceinline__ void gen_load(const uint4* p, uint32_t* v) {
  asm volatile("{\n.reg .b128 t;\n.reg .b64 lo, hi;\nld.relaxed.gpu.b128 t, [%4];\nmov.b128 {lo, hi}, t;\nmov.b64 {%0, %1}, lo;\nmov.b64 {%2, %3}, hi;\n}"
               : "=r"(v[0]), "=r"(v[1]), "=r"(v[2]), "=r"(v[3]) : "l"(p) : "memory");
}
__device__ __forceinline__ void pkt_load(const uint4* p, uint32_t* v) {
  asm volatile("{\n.reg .b128 t;\n.reg .b64 lo, hi;\nld.relaxed.gpu.global.b128 t, [%4];\nmov.b128 {lo, hi}, t;\nmov.b64 {%0, %1}, lo;\nmov.b64 {%2, %3}, hi;\n}"
               : "=r"(v[0]), "=r"(v[1]), "=r"(v[2]), "=r"(v[3]) : "l"(p) : "memory");
}
__device__ __forceinline__ uint32_t ld_relaxed(const uint32_t* p) { uint32_t v; asm volatile("ld.relaxed.gpu.global.u32 %0, [%1];" : "=r"(v) : "l"(p) : "memory"); return v; }
__device__ __forceinline__ uint4 ld_relaxed4(const void* p) { uint4 v; asm volatile("ld.relaxed.gpu.global.v4.u32 {%0, %1, %2, %3}, [%4];" : "=r"(v.x), "=r"(v.y), "=r"(v.z), "=r"(v.w) : "l"(p) : "memory"); return v; }
__device__ __forceinline__ void st_relaxed(uint32_t* p, uint32_t v) { asm volatile("st.relaxed.gpu.global.u32 [%0], %1;" :: "l"(p), "r"(v) : "memory"); }
__device__ __forceinline__ void st_relaxed2(void* p, uint32_t a, uint32_t b) { asm volatile("st.relaxed.gpu.global.v2.u32 [%0], {%1, %2};" :: "l"(p), "r"(a), "r"(b) : "memory"); }
__device__ __forceinline__ void red_release(uint32_t* p, uint32_t v) { asm volatile("red.release.gpu.global.add.u32 [%0], %1;" :: "l"(p), "r"(v) : "memory"); }
__device__ __forceinline__ uint32_t tagf(float v, uint32_t tag) { return (__float_as_uint(v) & ~15u) | (tag & 15u); }
__device__ __forceinline__ bool tag_ok4(const uint4& v, uint32_t tag) { return (((v.x ^ tag) | (v.y ^ tag) | (v.z ^ tag) | (v.w ^ tag)) & 15u) == 0; }
__device__ __forceinline__ float untag(uint32_t v) { return __uint_as_float(v & ~15u); }
template <typename T> __device__ __forceinline__ T* ptr_add(T* p, uint32_t bytes) {
  uint64_t r;
  asm("{\n.reg .u32 lo, hi;\nmov.b64 {lo, hi}, %1;\nadd.cc.u32 lo, lo, %2;\naddc.u32 hi, hi, 0;\nmov.b64 %0, {lo, hi};\n}" : "=l"(r) : "l"(p), "r"(bytes));
  return (T*)r;
}
#define TL(who, slot) do {} while (0)
#define TLC(slot) do {} while (0)
#define TLE(slot) do {} while (0)
#define ST(who, n) do {} while (0)
#define AP(i) do {} while (0)
#define SP(v) do {} while (0)
#define TLG(slot) do {} while (0)
#define STA() do {} while (0)
#define STB(n) do {} while (0)

__device__ __forceinline__ void wgmma_n128(float (&d)[64], uint64_t da, uint64_t db, int scale_d) {
  asm volatile("{\n.reg .pred p;\nsetp.ne.b32 p, %66, 0;\n"
    "wgmma.mma_async.sync.aligned.m64n128k16.f32.bf16.bf16 "
    "{%0, %1, %2, %3, %4, %5, %6, %7, %8, %9, %10, %11, %12, %13, %14, %15, "
    "%16, %17, %18, %19, %20, %21, %22, %23, %24, %25, %26, %27, %28, %29, %30, %31, "
    "%32, %33, %34, %35, %36, %37, %38, %39, %40, %41, %42, %43, %44, %45, %46, %47, "
    "%48, %49, %50, %51, %52, %53, %54, %55, %56, %57, %58, %59, %60, %61, %62, %63}, "
    "%64, %65, p, 1, 1, 0, 1;\n}\n"
    : "+f"(d[0]), "+f"(d[1]), "+f"(d[2]), "+f"(d[3]), "+f"(d[4]), "+f"(d[5]), "+f"(d[6]), "+f"(d[7]),
      "+f"(d[8]), "+f"(d[9]), "+f"(d[10]), "+f"(d[11]), "+f"(d[12]), "+f"(d[13]), "+f"(d[14]), "+f"(d[15]),
      "+f"(d[16]), "+f"(d[17]), "+f"(d[18]), "+f"(d[19]), "+f"(d[20]), "+f"(d[21]), "+f"(d[22]), "+f"(d[23]),
      "+f"(d[24]), "+f"(d[25]), "+f"(d[26]), "+f"(d[27]), "+f"(d[28]), "+f"(d[29]), "+f"(d[30]), "+f"(d[31]),
      "+f"(d[32]), "+f"(d[33]), "+f"(d[34]), "+f"(d[35]), "+f"(d[36]), "+f"(d[37]), "+f"(d[38]), "+f"(d[39]),
      "+f"(d[40]), "+f"(d[41]), "+f"(d[42]), "+f"(d[43]), "+f"(d[44]), "+f"(d[45]), "+f"(d[46]), "+f"(d[47]),
      "+f"(d[48]), "+f"(d[49]), "+f"(d[50]), "+f"(d[51]), "+f"(d[52]), "+f"(d[53]), "+f"(d[54]), "+f"(d[55]),
      "+f"(d[56]), "+f"(d[57]), "+f"(d[58]), "+f"(d[59]), "+f"(d[60]), "+f"(d[61]), "+f"(d[62]), "+f"(d[63])
    : "l"(da), "l"(db), "r"(scale_d));
}
__device__ __forceinline__ void wgmma_n256(float (&d)[128], uint64_t da, uint64_t db, int scale_d) {
  asm volatile("{\n.reg .pred p;\nsetp.ne.b32 p, %130, 0;\n"
    "wgmma.mma_async.sync.aligned.m64n256k16.f32.bf16.bf16 "
    "{%0, %1, %2, %3, %4, %5, %6, %7, %8, %9, %10, %11, %12, %13, %14, %15, "
    "%16, %17, %18, %19, %20, %21, %22, %23, %24, %25, %26, %27, %28, %29, %30, %31, "
    "%32, %33, %34, %35, %36, %37, %38, %39, %40, %41, %42, %43, %44, %45, %46, %47, "
    "%48, %49, %50, %51, %52, %53, %54, %55, %56, %57, %58, %59, %60, %61, %62, %63, "
    "%64, %65, %66, %67, %68, %69, %70, %71, %72, %73, %74, %75, %76, %77, %78, %79, "
    "%80, %81, %82, %83, %84, %85, %86, %87, %88, %89, %90, %91, %92, %93, %94, %95, "
    "%96, %97, %98, %99, %100, %101, %102, %103, %104, %105, %106, %107, %108, %109, %110, %111, "
    "%112, %113, %114, %115, %116, %117, %118, %119, %120, %121, %122, %123, %124, %125, %126, %127}, "
    "%128, %129, p, 1, 1, 0, 1;\n}\n"
    : "+f"(d[0]), "+f"(d[1]), "+f"(d[2]), "+f"(d[3]), "+f"(d[4]), "+f"(d[5]), "+f"(d[6]), "+f"(d[7]),
      "+f"(d[8]), "+f"(d[9]), "+f"(d[10]), "+f"(d[11]), "+f"(d[12]), "+f"(d[13]), "+f"(d[14]), "+f"(d[15]),
      "+f"(d[16]), "+f"(d[17]), "+f"(d[18]), "+f"(d[19]), "+f"(d[20]), "+f"(d[21]), "+f"(d[22]), "+f"(d[23]),
      "+f"(d[24]), "+f"(d[25]), "+f"(d[26]), "+f"(d[27]), "+f"(d[28]), "+f"(d[29]), "+f"(d[30]), "+f"(d[31]),
      "+f"(d[32]), "+f"(d[33]), "+f"(d[34]), "+f"(d[35]), "+f"(d[36]), "+f"(d[37]), "+f"(d[38]), "+f"(d[39]),
      "+f"(d[40]), "+f"(d[41]), "+f"(d[42]), "+f"(d[43]), "+f"(d[44]), "+f"(d[45]), "+f"(d[46]), "+f"(d[47]),
      "+f"(d[48]), "+f"(d[49]), "+f"(d[50]), "+f"(d[51]), "+f"(d[52]), "+f"(d[53]), "+f"(d[54]), "+f"(d[55]),
      "+f"(d[56]), "+f"(d[57]), "+f"(d[58]), "+f"(d[59]), "+f"(d[60]), "+f"(d[61]), "+f"(d[62]), "+f"(d[63]),
      "+f"(d[64]), "+f"(d[65]), "+f"(d[66]), "+f"(d[67]), "+f"(d[68]), "+f"(d[69]), "+f"(d[70]), "+f"(d[71]),
      "+f"(d[72]), "+f"(d[73]), "+f"(d[74]), "+f"(d[75]), "+f"(d[76]), "+f"(d[77]), "+f"(d[78]), "+f"(d[79]),
      "+f"(d[80]), "+f"(d[81]), "+f"(d[82]), "+f"(d[83]), "+f"(d[84]), "+f"(d[85]), "+f"(d[86]), "+f"(d[87]),
      "+f"(d[88]), "+f"(d[89]), "+f"(d[90]), "+f"(d[91]), "+f"(d[92]), "+f"(d[93]), "+f"(d[94]), "+f"(d[95]),
      "+f"(d[96]), "+f"(d[97]), "+f"(d[98]), "+f"(d[99]), "+f"(d[100]), "+f"(d[101]), "+f"(d[102]), "+f"(d[103]),
      "+f"(d[104]), "+f"(d[105]), "+f"(d[106]), "+f"(d[107]), "+f"(d[108]), "+f"(d[109]), "+f"(d[110]), "+f"(d[111]),
      "+f"(d[112]), "+f"(d[113]), "+f"(d[114]), "+f"(d[115]), "+f"(d[116]), "+f"(d[117]), "+f"(d[118]), "+f"(d[119]),
      "+f"(d[120]), "+f"(d[121]), "+f"(d[122]), "+f"(d[123]), "+f"(d[124]), "+f"(d[125]), "+f"(d[126]), "+f"(d[127])
    : "l"(da), "l"(db), "r"(scale_d));
}
__device__ __forceinline__ void wgmma_rs_n128(float (&d)[64], const uint32_t* a, uint64_t db, int scale_d) {
  asm volatile("{\n.reg .pred p;\nsetp.ne.b32 p, %69, 0;\n"
    "wgmma.mma_async.sync.aligned.m64n128k16.f32.bf16.bf16 "
    "{%0, %1, %2, %3, %4, %5, %6, %7, %8, %9, %10, %11, %12, %13, %14, %15, "
    "%16, %17, %18, %19, %20, %21, %22, %23, %24, %25, %26, %27, %28, %29, %30, %31, "
    "%32, %33, %34, %35, %36, %37, %38, %39, %40, %41, %42, %43, %44, %45, %46, %47, "
    "%48, %49, %50, %51, %52, %53, %54, %55, %56, %57, %58, %59, %60, %61, %62, %63}, "
    "{%64, %65, %66, %67}, %68, p, 1, 1, 1;\n}\n"
    : "+f"(d[0]), "+f"(d[1]), "+f"(d[2]), "+f"(d[3]), "+f"(d[4]), "+f"(d[5]), "+f"(d[6]), "+f"(d[7]),
      "+f"(d[8]), "+f"(d[9]), "+f"(d[10]), "+f"(d[11]), "+f"(d[12]), "+f"(d[13]), "+f"(d[14]), "+f"(d[15]),
      "+f"(d[16]), "+f"(d[17]), "+f"(d[18]), "+f"(d[19]), "+f"(d[20]), "+f"(d[21]), "+f"(d[22]), "+f"(d[23]),
      "+f"(d[24]), "+f"(d[25]), "+f"(d[26]), "+f"(d[27]), "+f"(d[28]), "+f"(d[29]), "+f"(d[30]), "+f"(d[31]),
      "+f"(d[32]), "+f"(d[33]), "+f"(d[34]), "+f"(d[35]), "+f"(d[36]), "+f"(d[37]), "+f"(d[38]), "+f"(d[39]),
      "+f"(d[40]), "+f"(d[41]), "+f"(d[42]), "+f"(d[43]), "+f"(d[44]), "+f"(d[45]), "+f"(d[46]), "+f"(d[47]),
      "+f"(d[48]), "+f"(d[49]), "+f"(d[50]), "+f"(d[51]), "+f"(d[52]), "+f"(d[53]), "+f"(d[54]), "+f"(d[55]),
      "+f"(d[56]), "+f"(d[57]), "+f"(d[58]), "+f"(d[59]), "+f"(d[60]), "+f"(d[61]), "+f"(d[62]), "+f"(d[63])
    : "r"(a[0]), "r"(a[1]), "r"(a[2]), "r"(a[3]), "l"(db), "r"(scale_d));
}

template <int BN> __device__ __forceinline__ void wgmma(float (&d)[BN / 2], uint64_t a, uint64_t b, int s) {
  if constexpr (BN == 128) wgmma_n128(d, a, b, s);
  else wgmma_n256(d, a, b, s);
}

template <int N> __device__ __forceinline__ void acc_fence(float* a) {
#pragma unroll
  for (int i = 0; i < N; i++) asm volatile("" : "+f"(a[i]) :: "memory");
}

#define SELECT8(a, f) do { \
  if ((a) & 4) { if ((a) & 2) { if ((a) & 1) f(7); else f(6); } else { if ((a) & 1) f(5); else f(4); } } \
  else { if ((a) & 2) { if ((a) & 1) f(3); else f(2); } else { if ((a) & 1) f(1); else f(0); } } } while (0)
__device__ __forceinline__ uint32_t lane_now() { uint32_t l; asm volatile("mov.u32 %0, %%laneid;" : "=r"(l)); return l; }

struct Prod {
  uint32_t sb, n, tail, addr, pat, ready;
  uint32_t rank, flip; uint16_t mask;
  __device__ __forceinline__ void load_b(uint32_t dst, uint32_t half, const CUtensorMap* m, uint32_t mstep, uint32_t fb, int k, int ch, int cstep) {
    uint32_t h = rank;
    do { tma_ld3_mc(dst + h * half, ptr_add(m, h * mstep), fb, 0, k * 64, ch + h * cstep, mask); h ^= flip; } while (h != rank);
  }
  __device__ __forceinline__ void load_wide(const Params& P, int ffn, uint32_t dst, uint32_t fb, int k, int ch) {
    load_b(dst, PAGE, &P.map[ffn ? M_W1 : M_WKV], ffn ? 128 : 0, fb, k, ffn ? ch : ch + 16, ffn ? 0 : 16);
  }
  __device__ __forceinline__ void load_narrow(const Params& P, int ffn, uint32_t dst, uint32_t fb, int k, int j) {
    load_b(dst, 8192, &P.map[ffn ? M_W1H : M_WQ], ffn ? 128 : 0, fb, k, ffn ? 48 + j : 2 * j, ffn ? 0 : 1);
  }
  __device__ __forceinline__ void finish() {
#pragma unroll 1
    for (; tail < n; tail++) mbar_wait(sb + BAR_EMPTY + ((tail & 7) << 3), (tail >> 3) & 1);
  }
  template <int PAGES> __device__ __forceinline__ uint32_t acquire(uint32_t& fb) {
    uint32_t nw = pat & 3; pat = (pat >> 2) | 0x40000000u;
#pragma unroll 1
    for (; nw; nw--) { mbar_wait(sb + BAR_EMPTY + ((tail & 7) << 3), (tail >> 3) & 1); tail++; }
    ST(4, n);
    fb = sb + BAR_FULL + ((n & 7) << 3);
    mbar_expect_tx(fb, PAGES * PAGE);
    const uint32_t a = sb + addr;
    addr += PAGES * PAGE; if (addr >= NPAGE * PAGE) addr = 0;
    n++;
    return a;
  }
  const uint32_t* flag; uint32_t base, seen;
  __device__ __forceinline__ void acquire_fence() { asm volatile("fence.acquire.gpu;" ::: "memory"); fence_async_global(); }
  __device__ __forceinline__ void next() {
    uint32_t v, spins = 0;
    seen++;
    do { asm volatile("ld.acquire.cta.shared.u32 %0, [%1];" : "=r"(v) : "r"(sb + SM_SEEN) : "memory"); spin_check(++spins >> 4); } while (v < seen);
    fence_async_global();
  }
  __device__ __forceinline__ void need(uint32_t mask) {
    if ((ready & mask) != mask) {
      uint32_t spins = 0;
      do { ready = ld_relaxed(flag) - base; spin_check(++spins); } while ((ready & mask) != mask);
      acquire_fence();
    }
    ST(5, n - 1);
  }
};

struct Cons {
  uint32_t sb, n, off, prev;
  uint32_t ebar;
  uint32_t da0, db0;
  int lane;
  template <int PAGES> __device__ __forceinline__ void advance() {
    n++; off += PAGES << 10; if (off >= (NPAGE << 10)) off = 0;
    asm volatile("" : "+r"(n), "+r"(off));
  }
  template <int BN, int PAGES> __device__ __forceinline__ void step_ab(float (&acc)[BN / 2], uint32_t da, uint32_t db, int accumulate) {
    STA();
    mbar_wait_fast(sb + BAR_FULL + ((n & 7) << 3), (n >> 3) & 1);
    STB(n);
    const uint64_t da64 = desc64(da), db64 = desc64(db);
    wgmma_fence();
#pragma unroll
    for (int k = 0; k < 4; k++) wgmma<BN>(acc, da64 + 2 * k, db64 + 128 * k, k ? 1 : accumulate);
    wgmma_commit();
    wgmma_wait<1>();
    if (prev && lane < 2) mbar_arrive_cluster(ebar + prev);
    prev = 64 + ((n & 7) << 3);
    advance<PAGES>();
  }
  template <int BN> __device__ __forceinline__ void step(float (&acc)[BN / 2], int accumulate = 1) { step_ab<BN, BN / 128 + 1>(acc, da0 + off, db0 + 1024 + off, accumulate); }
  template <int BN> __device__ __forceinline__ void step_own(float (&acc)[BN / 2], uint32_t da, int accumulate) { step_ab<BN, BN / 128>(acc, da, db0 + off, accumulate); }
  __device__ __forceinline__ void wait_full(uint32_t i) { mbar_wait_fast(sb + BAR_FULL + (((n + i) & 7) << 3), ((n + i) >> 3) & 1); }
  __device__ __forceinline__ void issue_rs(float (&acc)[64], uint32_t (&a)[16], int second, int accumulate) {
    if (!second) { STA(); STB(n); }
    const uint64_t db64 = desc64(db0 + off) + 1024 * second;
    wgmma_fence();
#pragma unroll
    for (int k = 0; k < 4; k++) wgmma_rs_n128(acc, a + 4 * k, db64 + 128 * k, k ? 1 : accumulate);
    if (second) {
      wgmma_commit();
      prev = 64 + ((n & 7) << 3);
      advance<2>();
    }
  }
  template <int BN> __device__ __forceinline__ void steps(float (&acc)[BN / 2], int cnt) {
#pragma unroll 1
    do { step<BN>(acc); } while (--cnt > 0);
  }
  __device__ __forceinline__ void drain() {
    wgmma_wait<0>();
    if (lane < 2) mbar_arrive_cluster(ebar + prev);
    prev = 0;
  }
};

#define MAPPING 2
__device__ __forceinline__ uint32_t role_of_sm(uint32_t smid) {
  const uint32_t t = smid >> 1;
  uint32_t q, i;
  if (t < 32) { q = t & 7; i = t >> 3; }
  else if (t < 60) { const uint32_t u = t - 32, d = (u * 37) >> 8; q = 1 + u - d * 7; i = 4 + d; }
  else if (t < 62) return 128 + smid - 120;
  else { q = 0; i = t - 58; }
  return (q * 2 + (smid & 1)) * 8 + i;
}

template <typename T> __device__ __forceinline__ T* scratch(const Params& P, uint32_t off) { return (T*)ptr_add(P.scratch, off); }
__device__ __forceinline__ uint32_t* epoch_ptr(const Params& P) { uint32_t b; asm volatile("mov.u32 %0, %%ctaid.x;" : "=r"(b)); return scratch<uint32_t>(P, G_EPOCH + b * 4u); }

__device__ __forceinline__ int o_chunk(int s, int j) { const int hf = s >= 9, m = s - 2 - 7 * hf; return s < 2 ? 2 * j + s : 2 * (m == j ? 7 : m) + hf; }

__global__ void __cluster_dims__(2, 1, 1) __launch_bounds__(384, 1) fused_kernel(const __grid_constant__ Params P) {
  extern __shared__ __align__(1024) uint8_t smem_raw[];
  SP(0);
  const uint32_t sb = __shfl_sync(0xffffffffu, smem_u32(smem_raw), 0);
  const int warp = __shfl_sync(0xffffffffu, threadIdx.x >> 5, 0);
  const int lane = threadIdx.x & 31;
  if (warp == 7 && elect_one()) { prefetch_map(&P.map[M_XIN64]); prefetch_map(&P.map[M_WKV]); prefetch_map(&P.map[M_XIN]); }
  uint32_t role = blockIdx.x < 128 ? ((blockIdx.x >> 4) * 2 + (blockIdx.x & 1)) * 8 + ((blockIdx.x >> 1) & 7) : blockIdx.x;
  if (P.use_smid) { uint32_t smid; asm volatile("mov.u32 %0, %%smid;" : "=r"(smid)); role = role_of_sm(smid); }
  const bool spare = role >= 128;
  const int g = role >> 3, j = role & 7;
  uint32_t rank; asm("mov.u32 %0, %%cluster_ctarank;" : "=r"(rank));
  auto shared_b = [&]() {
    uint32_t peer;
    asm volatile("ld.shared::cluster.u32 %0, [%1];" : "=r"(peer) : "r"(mapa(sb + SM_ROLE, rank ^ 1)) : "memory");
    return !spare && peer < 128 && (peer & 7) == (uint32_t)j;
  };
  SP(1);

  if (warp >= 8) {
    asm volatile("setmaxnreg.dec.sync.aligned.u32 40;");
    if (elect_one()) {
      if (warp == 8) {
#pragma unroll
        for (int i = 0; i < 6; i++) mbar_init(sb + BAR_FULL + 8 * i, 1);
        mbar_init(sb + BAR_XIN, 1); mbar_init(sb + BAR_XIN + 8, 1);
      } else if (warp == 9) {
#pragma unroll
        for (int i = 0; i < 8; i++) mbar_init(sb + BAR_EMPTY + 8 * i, 16);
      } else if (warp == 10) {
#pragma unroll
        for (int i = 0; i < 4; i++) mbar_init(sb + BAR_SFULL + 8 * i, 4);
        mbar_init(sb + BAR_CLR, 1); mbar_init(sb + BAR_FULL + 48, 1); mbar_init(sb + BAR_FULL + 56, 1);
      } else {
        sts128(sb + SM_ROLE, role, 0, 0, 0);
        mbar_init(sb + BAR_TAG, 1); mbar_init(sb + BAR_XFULL, 8); mbar_init(sb + BAR_CSE, 8);
        mbar_init(sb + BAR_SEMPTY, 1); mbar_init(sb + BAR_CSF, 1); mbar_init(sb + BAR_CSF + 8, 2);
      }
      asm volatile("fence.mbarrier_init.release.cluster;\nfence.release.sync_restrict::shared::cta.cluster;" ::: "memory");
      fence_async_smem();
    }
    __syncwarp();
    SP(2);
    asm volatile("barrier.cluster.arrive.relaxed.aligned;" ::: "memory");
    if (warp == 8 && !spare) {
      if (elect_one()) {
        const int par = g & 1, row = (g >> 1) * 128;
#pragma unroll 1
        for (int s = 0; s < 2; s++) {
          const uint32_t xb = sb + BAR_XIN + 8 * s, fb = sb + BAR_FULL + 8 * s;
          mbar_expect_tx(xb, PAGE); mbar_expect_tx(fb, 2 * PAGE);
#pragma unroll
          for (int h = 0; h < 2; h++) tma_ld3(sb + SM_STAGE + h * PAGE + s * 8192, &P.map[M_XIN64], xb, s * 64, par, row + h * 64);
#pragma unroll
          for (int h = 0; h < 2; h++) tma_ld3(sb + (2 * s + h) * PAGE, &P.map[M_WKV], fb, 0, s * 64, 16 + 16 * h + 2 * j);
        }
#pragma unroll 1
        for (int s = 0; s < 2; s++) {
          const uint32_t fb = sb + BAR_FULL + 16 + 8 * s;
          mbar_expect_tx(fb, PAGE);
          tma_ld3(sb + (4 + s) * PAGE, &P.map[M_WKV], fb, 0, s * 64, 2 * j);
        }
#pragma unroll 1
        for (int s = 0; s < 2; s++) {
          const uint32_t fb = sb + BAR_FULL + 32 + 8 * s, a = sb + (6 + 3 * s) * PAGE;
          const int k = (j == 1 ? 4 : 2) + s;
          mbar_expect_tx(fb, 3 * PAGE);
          tma_ld3(a, &P.map[M_XIN], fb, k * 64, par, row);
#pragma unroll
          for (int h = 0; h < 2; h++) tma_ld3(a + PAGE + h * PAGE, &P.map[M_WKV], fb, 0, k * 64, 16 + 16 * h + 2 * j);
        }
        spin_check((sb & 1023) << 22);
      }
      __syncwarp();
    }
    SP(3);
    asm volatile("barrier.cluster.wait.acquire.aligned;" ::: "memory");
    SP(4);
    if (warp == 8) {
      if (elect_one()) {
        Prod p; p.sb = sb; p.n = 0; p.tail = 0; p.ready = 0; p.addr = 0;
        { const bool mc = shared_b(); p.rank = rank; p.flip = !mc; p.mask = mc ? 3 : 1 << rank; }
        uint32_t fb;
        if (spare) {
          p.pat = 0x55555000u;
#pragma unroll 1
          for (int r = -1; r < 7; r++) {
            const int ch = r < 0 ? 4 * j : ((r < 2 ? r : r == 2 ? 6 : r - 1) * 4 + j) * 2;
#pragma unroll 1
            for (int k = 0; k < 16; k++) { const uint32_t a = p.acquire<2>(fb); p.load_b(a, PAGE, &P.map[r < 0 ? M_WKV : M_W1], r < 0 ? 0 : 128, fb, k, ch, r < 0 ? 2 : 0); }
          }
        } else {
          p.seen = 0;
          const int xpar = g & 1, xrow = (g >> 1) * 128;
          SP(5);
#pragma unroll 1
          for (int hl = 0; hl < 4; hl++) {
            const int ffn = hl & 1;
            const CUtensorMap* xmap = &P.map[hl ? M_OUT_LD : M_XIN];
            if (hl) {
              p.pat = ffn ? Pat<3>::v : Pat<7>::v;
#pragma unroll 1
              for (int s = 0; s < 2; s++) { const uint32_t a = p.acquire<2>(fb); p.load_wide(P, ffn, a, fb, 2 * j + s, 2 * j); }
#pragma unroll 1
              for (int s = 0; s < 2; s++) { const uint32_t a = p.acquire<1>(fb); p.load_narrow(P, ffn, a, fb, 2 * j + s, j); }
            } else { p.pat = (Pat<0>::v >> 12) | 0x55500000u; p.addr = 0; p.n = 6; }
            if (hl == 0) SP(6);
            uint32_t fb0 = 0;
#pragma unroll 1
            for (int m = hl ? 0 : 2; m < 14; m++) {
              const int hf = m >= 7, mm = m - 7 * hf, jj = mm == j ? 7 : mm;
              int k = 2 * jj + hf;
              if (hl == 0) {
                const int pr = (m >> 1) + 1;
                k = 2 * (j && pr == 2 ? j : pr == j ? 2 : pr) + (m & 1);
              }
              const uint32_t a = p.acquire<3>(fb);
              p.load_wide(P, ffn, a + PAGE, fb, k, 2 * j);
              if (hl) {
                if (m == 0) { fb0 = fb; continue; }
                if (m == 1) {
                  const int j0 = j ? 0 : 7;
                  p.flag = scratch<uint32_t>(P, g * G_BLOCK + G_FLAGS + (ffn ? (hl >> 1) * EV_N + EV_XA : EV_XB) * 128);
                  p.ready = 0; p.need((1u << j0) | (1u << j));
                  tma_ld3(a - 3 * PAGE, xmap, fb0, j0 * 128, xpar, xrow);
                }
                if (m < 7) p.need(1u << jj); else if (m == 7) p.next();
              }
              tma_ld3(a, xmap, fb, k * 64, xpar, xrow);
            }
            if (hl == 0) { mbar_wait(sb + BAR_TAG, 0); asm volatile("ld.shared.u32 %0, [%1];" : "=r"(p.base) : "r"(sb + SM_TAG) : "memory"); p.base = (p.base - 1) * 255; }
            static_assert(Pat<1>::v == Pat<4>::v, "");
            p.pat = Pat<1>::v; p.addr += 2 * PAGE;
#pragma unroll 1
            for (int m = 0; m < 14; m++) {
              const int k = (m >> 1) == (hl ? j : 0) ? 14 + (m & 1) : m;
              const uint32_t a = p.acquire<2>(fb);
              p.load_narrow(P, ffn, a + PAGE, fb, k, j);
              tma_ld3(a, xmap, fb, k * 64, xpar, xrow);
            }
            if (!ffn) {
              p.pat = Pat<2>::v;
              uint32_t a = 0;
#pragma unroll 1
              for (int s = 0; s < 16; s++) {
                if (!(s & 1)) a = p.acquire<2>(fb); else a += PAGE;
                p.load_b(a, 8192, &P.map[M_WO], 0, fb, o_chunk(s, j), 2 * j, 1);
              }
              a = p.acquire<2>(fb);
              tma_ld3(a, xmap, fb, j * 128, xpar, xrow); tma_ld3(a + PAGE, xmap, fb, j * 128 + 64, xpar, xrow);
            } else {
              p.pat = Pat<5>::v;
#pragma unroll 1
              for (int s = 16; s < 48; s++) {
                const int pi = (s >> 1) & 7;
                const int k = (s < 32 ? pi : pi == 4 ? j : pi == j ? 4 : pi) * 2 + (s & 1);
                const uint32_t a = p.acquire<3>(fb);
                p.load_wide(P, 1, a + PAGE, fb, k, (s & 48) + 2 * j);
                tma_ld3(a, xmap, fb, k * 64, xpar, xrow);
              }
              p.pat = Pat<6>::v; p.addr += 2 * PAGE;
#pragma unroll 1
              for (int q = 0; q < 4; q++) {
                p.next();
                const int k0 = q == 0 ? 0 : q == 1 ? 48 : q * 16 - 16, k1 = k0 + (q == 1 ? 8 : 16);
#pragma unroll 1
                for (int k = k0; k < k1; k++) {
                  const uint32_t a = p.acquire<2>(fb);
                  p.load_b(a + PAGE, 8192, &P.map[M_W2], 0, fb, k, 2 * j, 1);
                  tma_ld3(a, &P.map[M_H_LD], fb, k * 64, g, 0);
                }
              }
            }
            TL(2, 1 + hl);
          }
        }
        p.finish();
      }
    } else if (!spare) {
      mbar_wait(sb + BAR_XIN, 0);
      if (elect_one()) {
#pragma unroll 1
        for (int i = warp - 9; i < 8; i += 3) prefetch_l2(ptr_add(P.wqkv, (i * 128 + role) * 6144u + 2048u), 4096);
      }
      uint32_t tag;
      {
        const uint32_t part = warp - 9, col = DM + role * 16 + (lane & 1) * 8;
        const int cnt = part ? 21 : 22;
        const uint4* wp = ptr_add((const uint4*)P.wqkv, ((part ? 16 + part * 336 : 0) + (lane >> 1)) * 6144u + col * 2);
        float s[8] = {0, 0, 0, 0, 0, 0, 0, 0};
        uint4 v[4];
#pragma unroll
        for (int i = 0; i < 4; i++) v[i] = ld_relaxed4(wp + i * (16 * 6144 / 16));
        tag = ld_relaxed(epoch_ptr(P)) + 1;
        if (warp == 10 && lane == 0) { asm volatile("st.shared.u32 [%0], %1;" :: "r"(sb + SM_TAG), "r"(tag) : "memory"); mbar_arrive(sb + BAR_TAG); }
#pragma unroll 1
        for (int b = 4; b < 28; b += 4) {
          wp += 64 * 6144 / 16;
#pragma unroll
          for (int i = 0; i < 4; i++) {
            s[0] += bf_lo(v[i].x); s[1] += bf_hi(v[i].x); s[2] += bf_lo(v[i].y); s[3] += bf_hi(v[i].y);
            s[4] += bf_lo(v[i].z); s[5] += bf_hi(v[i].z); s[6] += bf_lo(v[i].w); s[7] += bf_hi(v[i].w);
            v[i] = make_uint4(0, 0, 0, 0);
            if (b + i < cnt) v[i] = __ldcg(wp + i * (16 * 6144 / 16));
          }
        }
#pragma unroll
        for (int e = 0; e < 4; e++) { const bool h = lane & 16; const float t = __shfl_xor_sync(0xffffffffu, h ? s[e] : s[e + 4], 16); s[e] = (h ? s[e + 4] : s[e]) + t; }
#pragma unroll
        for (int e = 0; e < 2; e++) { const bool h = lane & 8; const float t = __shfl_xor_sync(0xffffffffu, h ? s[e] : s[e + 2], 8); s[e] = (h ? s[e + 2] : s[e]) + t; }
        { const bool h = lane & 4; const float t = __shfl_xor_sync(0xffffffffu, h ? s[0] : s[1], 4); s[0] = (h ? s[1] : s[0]) + t; }
        s[0] += __shfl_xor_sync(0xffffffffu, s[0], 2);
        if (!(lane & 2) || part == 0) st_relaxed(scratch<uint32_t>(P, G_CS + (col + (lane >> 2)) * 16 + ((lane & 2) ? 3 : part) * 4), tagf((lane & 2) ? 0.f : s[0], tag));
        __syncwarp();
      }
      if (warp == 11 && lane == 0) TL(2, 30);
      {
        const uint32_t cspos = sb + SM_CS + ((lane & 16) + ((lane >> 1) & 3) * 4 + ((lane >> 3) & 1) * 2 + (lane & 1)) * 4;
#pragma unroll 1
        for (int it = 0; it < (warp == 10 ? 8 : 1); it++) {
          const int t = it & 3;
          if (it) mbar_wait(sb + BAR_CSE, (it - 1) & 1);
          if (t == 1) mbar_wait(sb + BAR_SEMPTY, 0);
#pragma unroll 1
          for (int b = it ? 0 : warp - 9; b < (it == 0 ? warp - 8 : t < 2 ? 3 : 2); b++) {
            uint32_t c0, c1;
            if (b < 2) { c0 = (t ? 2048 + t * 1024 + b * FF : 1024 + b * 1024) + j * 128; c1 = c0 + 64; }
            else if (t) { c0 = 6144 + j * 64; c1 = c0 + FF; }
            else { c0 = j * 128; c1 = c0 + 64; }
            const uint4* p0 = scratch<uint4>(P, G_CS + (c0 + lane) * 16u);
            const uint4* p1 = scratch<uint4>(P, G_CS + (c1 + lane) * 16u);
            uint4 v[4]; uint32_t spins = 0; bool ok;
            do {
              if (spins) __nanosleep(200);
              v[0] = ld_relaxed4(p0); v[1] = ld_relaxed4(p0 + 32); v[2] = ld_relaxed4(p1); v[3] = ld_relaxed4(p1 + 32);
              ok = tag_ok4(v[0], tag) && tag_ok4(v[1], tag) && tag_ok4(v[2], tag) && tag_ok4(v[3], tag);
              spin_check(++spins);
            } while (__any_sync(0xffffffffu, !ok));
#pragma unroll
            for (int m = 0; m < 4; m++) sts32f(cspos + b * 512 + m * 128, (untag(v[m].x) + untag(v[m].y)) + (untag(v[m].z) + untag(v[m].w)));
            __syncwarp();
            if (lane == 0) mbar_arrive(sb + BAR_CSF + (b ? 8 : 0));
          }
          if (lane == 0) { if (t >= 2) mbar_arrive(sb + BAR_CSF + 8); TL(2, 16 + it + (warp == 11 ? 8 : warp == 9 ? 9 : 0)); }
          if (t == 3) {
            if (g >= 2) {
              uint4* op = scratch<uint4>(P, G_HALO + (((it >> 2) * 16 + g - 2) * 8 + j) * 4096u + lane * 16u);
#pragma unroll 1
              for (int i = 0; i < 8; i++) { st_b128(op, 0, 0, 0, 0); op += 32; }
            }
          }
        }
      }
      if (warp == 11) {
        if (elect_one()) prefetch_l2(ptr_add(P.wo, role * 16384u), 16384);
        uint32_t* const fl = scratch<uint32_t>(P, g * G_BLOCK + G_FLAGS);
        uint32_t seen = 0;
#pragma unroll 1
        for (int e = EV_XA; e < EV_N + EV_XB; e++) {
          if (e == EV_XB) continue;
          const bool clr = (e & 7) == EV_XA;
          uint32_t* const f = ptr_add(fl, (clr ? 16 + e : e) * 128u);
          if (clr) {
            uint4* op = scratch<uint4>(P, g * G_BLOCK + G_O + j * 32768u + lane * 16u);
#pragma unroll 1
            for (int i = 0; i < 64; i++) { st_b128(op, 0, 0, 0, 0); op += 32; if (e || (i & 1)) __nanosleep(10); }
            __syncwarp();
            if (lane == 0) red_release(f, 1u << j);
          }
          uint32_t spins = 0, m;
          while ((m = ld_relaxed(f) - (tag - 1) * 255) != 255) { __nanosleep(m ? 50 : 500); spin_check(++spins); }
          asm volatile("fence.acquire.gpu;" ::: "memory");
          if (lane == 0) {
            if (clr) mbar_arrive(sb + BAR_CLR);
            else asm volatile("st.release.cta.shared.u32 [%0], %1;" :: "r"(sb + SM_SEEN), "r"(++seen) : "memory");
          }
          if (e == EV_H3) {
#pragma unroll 1
            for (int i = 0; i < 7; i++) { if (elect_one()) prefetch_l2(ptr_add(P.w2, (i * 128 + role) * 8192u), 8192); __nanosleep(500); }
          }
          __syncwarp();
        }
      } else if (warp == 9) {
        if (elect_one()) {
          prefetch_map(&P.map[M_WQ]); prefetch_map(&P.map[M_OUT_LD]); prefetch_map(&P.map[M_WO]); prefetch_map(&P.map[M_W1 + rank]);
          prefetch_map(&P.map[M_H_ST]); prefetch_map(&P.map[M_H_LD]); prefetch_map(&P.map[M_W1H + rank]); prefetch_map(&P.map[M_W2]); prefetch_map(&P.map[M_OUT_ST]);
          uint32_t* fl = scratch<uint32_t>(P, g * G_BLOCK + G_FLAGS);
          int pe = 0;
#pragma unroll 1
          for (int e = 0; e < 2 * EV_N; e++) {
            const int q = e & 7;
            const bool is_h = q >= EV_H0 && q < EV_XB, last = e >= EV_N + EV_XB;
            const CUtensorMap* map = &P.map[is_h ? M_H_ST : M_OUT_ST];
            const int col = q == EV_H3 ? 3072 - 64 + j * 64 : (q == EV_H1 ? 1024 : q == EV_H2 ? 2048 : 0) + j * 128;
            const int row = is_h ? 0 : (g >> 1) * 128, par = is_h ? g : g & 1;
#pragma unroll 1
            for (int hb = is_h ? q == EV_H3 : q & 1; hb <= (is_h ? 1 : q & 1); hb++) {
#pragma unroll
              for (int w = 0; w < 2; w++) {
                const bool sw = TAIL_LAG && last;
                const int wg = sw ? hb : w, h = sw ? w : hb, p = sw ? pe - hb + w : pe;
                mbar_wait(sb + BAR_SFULL + 16 * wg + 8 * (p & 1), (p >> 1) & 1);
                if (w == 0) TL(3, 20 + e);
                tma_st3(map, sb + SM_STAGE + wg * PAGE + h * 8192, col + h * 64, par, row + wg * 64);
              }
              pe++;
            }
            bulk_commit();
            if (e != EV_N + EV_XB) bulk_wait<0>();
            TL(3, 40 + e);
            if (is_h || (q & 1)) mbar_arrive(sb + BAR_SEMPTY);
            if (!last) red_release(fl, 1u << j);
            TL(3, e);
            fl += 32;
          }
          *epoch_ptr(P) = tag;
        }
      }
    }
  } else {
    if (!spare) {
      if (warp == 0) asm volatile("prefetch.global.L2 [%0];" :: "l"(ptr_add(P.x, (2 * ((g >> 1) * 128 + j * 16 + (lane >> 1)) + (g & 1)) * 2048u + (lane & 1) * 128u)));
      else if (warp < 3 && (warp == 1 || lane < 16)) asm volatile("prefetch.global.L2 [%0];" :: "l"(ptr_add(P.wqkv, role * 6144u + (warp - 1) * 4096u + lane * 128u)));
      __syncwarp();
    }
    asm volatile("barrier.cluster.arrive.relaxed.aligned;" ::: "memory");
    asm volatile("setmaxnreg.inc.sync.aligned.u32 232;");
    SP(4);
    asm volatile("barrier.cluster.wait.acquire.aligned;" ::: "memory");
    SP(5);
    const int wg = warp >> 2;
    const int quad = lane & 3, gr = lane >> 2;
    Cons c; c.sb = sb; c.n = 0; c.off = 0; c.prev = 0; c.lane = lane;
    c.ebar = mapa(sb + BAR_EMPTY - 64, shared_b() ? lane & 1 : rank);
    const uint32_t stage = sb + SM_STAGE + wg * PAGE;
    const uint32_t dstage = desc_lo(stage, 16);
    if (spare) {
      const uint32_t tag = ld_relaxed(epoch_ptr(P)) + 1;
      const int tid = threadIdx.x & 127;
#pragma unroll
      for (int i = 0; i < 4; i++) sts128(stage + (i * 128 + tid) * 16, 0x3f803f80u, 0x3f803f80u, 0x3f803f80u, 0x3f803f80u);
      fence_async_smem();
      bar_sync(2 + wg, 128);
      c.db0 = desc_lo(sb + wg * PAGE, 8192);
#pragma unroll 1
      for (int r = -1; r < 7; r++) {
        float acc[64];
#pragma unroll 1
        for (int k = 0; k < 16; k++) c.step_ab<128, 2>(acc, dstage, c.db0 + c.off, k);
        c.drain();
        acc_fence<64>(acc);
        {
          float v = 0;
#pragma unroll
          for (int i = 0; i < 32; i++) asm("{\n.reg .pred p;\nsetp.eq.u32 p, %2, %3;\nselp.f32 %0, %1, %0, p;\n}" : "+f"(v) : "f"(acc[4 * (i >> 1) + (i & 1)]), "r"(tid >> 2), "r"(i));
          st_b128(scratch<uint4>(P, G_CS + (uint32_t)((r < 0 ? j * 256 + wg * 128 : 3 * DM + wg * FF + ((r < 2 ? r : r == 2 ? 6 : r - 1) * 4 + j) * 128) + (tid >> 3) * 8 + quad * 2 + (gr & 1)) * 16u),
                  tagf(v, tag), tag & 15u, tag & 15u, tag & 15u);
        }
        __syncwarp();
      }
      if (wg == 0) {
        const uint32_t* p = scratch<uint32_t>(P, (tid >> 3) * G_BLOCK + G_STATS + (tid & 7) * 8u);
        uint32_t spins = 0;
        while (__any_sync(0xffffffffu, (ld_relaxed(p) ^ tag) & 15u)) spin_check(++spins);
      }
      bar_sync(1, 256);
      if (threadIdx.x == 0) *epoch_ptr(P) = tag;
    } else {
    c.da0 = desc_lo(sb + wg * 8192, 16); c.db0 = desc_lo(sb, 8192);
    uint32_t sphase = 1, sfull = sb + BAR_SFULL + 16 * wg;
    const uint32_t maddr = stage + ((warp & 3) * 16 + (lane & 15)) * 128 + (((lane >> 4) ^ (lane & 7)) << 4);
    const uint32_t csaddr = sb + SM_CS + quad * 16;
    float st[8] = {0, 0, 0, 0, 0, 0, 0, 0};
    float* const mean = st; float* const rstd = st + 2;
    SP(6);

    auto stage_wait = [&]() { mbar_wait_fast(sb + BAR_SEMPTY, sphase); sphase ^= 1; };
    auto stage_publish = [&]() { fence_async_smem(); __syncwarp(); if (lane == 0) mbar_arrive(sfull); sfull ^= 8; };
    auto cs_load = [&](uint32_t (&cs)[16], int grp) {
#pragma unroll
      for (int i = 0; i < 4; i++) lds128(csaddr + grp * 256 + i * 64, cs[4 * i], cs[4 * i + 1], cs[4 * i + 2], cs[4 * i + 3]);
    };
    auto cs_apply = [&](float* acc, uint32_t (&cs)[16]) {
      acc_fence<32>(acc);
#pragma unroll
      for (int b = 0; b < 8; b++) {
        acc[4 * b] -= mean[0] * __uint_as_float(cs[2 * b]); acc[4 * b + 1] -= mean[0] * __uint_as_float(cs[2 * b + 1]);
        acc[4 * b + 2] -= mean[1] * __uint_as_float(cs[2 * b]); acc[4 * b + 3] -= mean[1] * __uint_as_float(cs[2 * b + 1]);
      }
      acc_fence<32>(acc);
    };
    auto glu_pair = [&](float g0, float g1, float u0, float u1, int r) {
      const float nl = -LOG2E * rstd[r], r2 = rstd[r] * rstd[r];
      return pack_bf16(g0 * u0 * r2 * rcp(1.0f + ex2(g0 * nl)), g1 * u1 * r2 * rcp(1.0f + ex2(g1 * nl)));
    };
    auto glu_slice = [&](uint32_t (&pk)[64], int i) {
      uint32_t hp[4];
#pragma unroll
      for (int e = 0; e < 4; e++) {
        asm volatile("" : "+r"(pk[4 * i + e]), "+r"(pk[32 + 4 * i + e]));
        const uint32_t pg = pk[4 * i + e], pu = pk[32 + 4 * i + e];
        hp[e] = glu_pair(bf_lo(pg), bf_hi(pg), bf_lo(pu), bf_hi(pu), e & 1);
      }
      stsm4((maddr ^ ((i & 3) << 5)) + (i >> 2) * 8192, hp[0], hp[1], hp[2], hp[3]);
    };
    auto glu_slice_acc = [&](float (&acc)[128], int i) {
      uint32_t hp[4];
      acc_fence<8>(acc + 8 * i);
#pragma unroll
      for (int e = 0; e < 4; e++) hp[e] = glu_pair(acc[8 * i + 2 * e], acc[8 * i + 2 * e + 1], acc[64 + 8 * i + 2 * e], acc[64 + 8 * i + 2 * e + 1], e & 1);
      stsm4((maddr ^ ((i & 3) << 5)) + (i >> 2) * 8192, hp[0], hp[1], hp[2], hp[3]);
    };
    auto stage_x = [&](float (&x)[64], uint32_t (&r)[32], int hf) {
#pragma unroll
      for (int i = 4 * hf; i < 4 * hf + 4; i++) {
        uint32_t v[4];
#pragma unroll
        for (int e = 0; e < 4; e++) v[e] = add_bf16x2(r[4 * i + e], pack_bf16(x[8 * i + 2 * e], x[8 * i + 2 * e + 1]));
        stsm4((maddr ^ ((i & 3) << 5)) + hf * 8192, v[0], v[1], v[2], v[3]);
      }
      stage_publish();
    };

    float acc[128];
    mbar_wait_fast(sb + BAR_XIN, 0);
    SP(7);
    c.step_own<256>(acc, dstage, 0);
    mbar_wait_fast(sb + BAR_XIN + 8, 0);
    SP(8);
#pragma unroll 1
    for (int hl = 0;; hl++) {
      int t = hl & 1;
      float acc2[64];
      uint32_t res[32];
      c.step_own<256>(acc, dstage + 512, 1);
#pragma unroll
      for (int s = 0; s < 2; s++) c.step_own<128>(acc2, dstage + s * 512, s);
#pragma unroll 1
      for (int s = 2; s < 11; s++) {
        const uint32_t apage = (c.off << 4) - (SM_STAGE + wg * 8192);
        c.step<256>(acc);
        int act = s;
        asm volatile("" : "+r"(act));
        auto get_tag = [&]() { uint32_t tag; asm volatile("ld.shared.u32 %0, [%1];" : "=r"(tag) : "r"(sb + SM_TAG) : "memory"); return tag; };
        auto stat_ptr = [&]() { return scratch<uint2>(P, g * G_BLOCK + G_STATS + (hl * 128 + warp * 16 + (lane_now() >> 2)) * 64u); };
        auto stat_get = [&]() {
          const uint2* sp = ptr_add(stat_ptr(), (lane_now() & 3) * 16);
          const uint4 a = ld_relaxed4(sp), b = ld_relaxed4(sp + 64);
          st[0] = __uint_as_float(a.x); st[1] = __uint_as_float(a.y); st[2] = __uint_as_float(a.z); st[3] = __uint_as_float(a.w);
          st[4] = __uint_as_float(b.x); st[5] = __uint_as_float(b.y); st[6] = __uint_as_float(b.z); st[7] = __uint_as_float(b.w);
        };
        switch (act) {
          case 4: case 5: {
            const uint32_t ra = maddr + ((hl || j == 0) ? (s & 1) * 8192 : apage);
#pragma unroll
            for (int i = 0; i < 4; i++) {
              uint32_t v[4];
              ldsm4(ra ^ (i << 5), v[0], v[1], v[2], v[3]);
              if (i == 0 && s == 4) { st[0] = bf_lo(v[0]); st[1] = bf_lo(v[1]); st[2] = st[3] = st[4] = st[5] = 0; }
#pragma unroll
              for (int e = 0; e < 4; e++) {
                const float a = bf_lo(v[e]) - st[e & 1], b = bf_hi(v[e]) - st[e & 1];
                st[2 + (e & 1)] += a + b; st[4 + (e & 1)] += a * a; st[4 + (e & 1)] += b * b;
              }
            }
          } break;
          case 6: {
            mbar_wait_fast(sb + BAR_TAG, 0);
            const uint32_t tag = get_tag();
#pragma unroll
            for (int r = 0; r < 2; r++) {
              const float mt = st[r] + st[2 + r] * (1.0f / 32);
              float m = mt + __shfl_xor_sync(0xffffffffu, mt, 1); m += __shfl_xor_sync(0xffffffffu, m, 2); m *= 0.25f;
              float q = st[4 + r] - st[2 + r] * st[2 + r] * (1.0f / 32) + 32.0f * (mt - m) * (mt - m);
              q += __shfl_xor_sync(0xffffffffu, q, 1); q += __shfl_xor_sync(0xffffffffu, q, 2);
              if (quad == 0) st_relaxed2(ptr_add(stat_ptr(), r * 512 + j * 8), tagf(m, tag), tagf(q, tag));
            }
          } break;
          case 8: stat_get(); break;
          case 10: {
            const uint32_t tag = get_tag();
            uint32_t spins = 0;
            for (;;) {
              uint32_t bad = 0;
#pragma unroll
              for (int i = 0; i < 8; i++) bad |= __float_as_uint(st[i]) ^ tag;
              if (!__any_sync(0xffffffffu, bad & 15u)) break;
              stat_get(); spin_check(++spins);
            }
            float mr[4];
#pragma unroll
            for (int r = 0; r < 2; r++) {
              const float m0 = untag(__float_as_uint(st[4 * r])), m1 = untag(__float_as_uint(st[4 * r + 2]));
              float m = m0 + m1; m += __shfl_xor_sync(0xffffffffu, m, 1); m += __shfl_xor_sync(0xffffffffu, m, 2); m *= 0.125f;
              float q = untag(__float_as_uint(st[4 * r + 1])) + untag(__float_as_uint(st[4 * r + 3])) + 128.0f * ((m0 - m) * (m0 - m) + (m1 - m) * (m1 - m));
              q += __shfl_xor_sync(0xffffffffu, q, 1); q += __shfl_xor_sync(0xffffffffu, q, 2);
              mr[r] = m; mr[2 + r] = rsqrtf(fmaxf(q, 0.f) * (1.0f / DM) + LN_EPS);
            }
            st[0] = mr[0]; st[1] = mr[1]; st[2] = mr[2]; st[3] = mr[3];
          } break;
          default: break;
        }
      }
#pragma unroll 1
      for (;;) {
      const int it = (hl >> 1) * 4 + t;
#pragma unroll
      for (int s = 0; s < 4; s++) {
        uint32_t cs[16];
        c.step<256>(acc);
        if (!(s & 1)) mbar_wait_fast(sb + BAR_CSF + 4 * s, t & 1);
        if (s >= 2 && t <= 1) { cs_load(cs, 2 + s); cs_apply(acc2 + 32 * (s - 2), cs); }
        cs_load(cs, s);
        c.drain();
        cs_apply(acc + 32 * s, cs);
      }
      c.step<256>(acc);
      if (lane == 0) mbar_arrive(sb + BAR_CSE);
      c.drain();
      acc_fence<128>(acc);
      TLC(1 + it * 6);
      if (t != 2) c.off += 2 << 10;
      uint32_t pkB[64];
      if (t == 2) {
#pragma unroll
        for (int i = 0; i < 64; i++) pkB[i] = pack_bf16(acc[2 * i], acc[2 * i + 1]);
      } else if (t == 0) {
        uint32_t pkA[64];
        auto kv_pack = [&](int v, int r) {
#pragma unroll
          for (int i = 32 * v + r; i < 32 * v + 32; i += 2) { acc_fence<2>(acc + 2 * i); pkA[i] = pack_bf16(acc[2 * i] * rstd[r], acc[2 * i + 1] * rstd[r]); }
        };
        const uint32_t l16 = lane_now() * 16u;
        uint4* const xs = ptr_add((uint4*)smem_raw, SM_STAGE + l16);
        uint4* const hp = scratch<uint4>(P, G_HALO + (((hl >> 1) * 16 + g) * 8 + j) * 4096u + l16);
        {
          uint4* const dst = (warp == 7 && g < 14) ? hp : ptr_add(xs, warp * 4096u);
#pragma unroll
          for (int s = 0; s < 2; s++) {
            c.steps<128>(acc2, s ? 2 : 1 + wg);
            if (s == 0) stage_wait();
            kv_pack(s, 1);
#pragma unroll
            for (int i = 4 * s; i < 4 * s + 4; i++) { pkA[8 * i + 1] = pkt_head(pkA[8 * i + 1]); gen_store(dst + i * 32, pkA[8 * i + 1], pkA[8 * i + 3], pkA[8 * i + 5], pkA[8 * i + 7]); }
          }
        }
        __syncwarp();
        if (lane == 0) mbar_arrive(sb + BAR_XFULL);
#pragma unroll
        for (int s = 0; s < 2; s++) {
          c.steps<128>(acc2, 2);
#pragma unroll
          for (int i = 33 - s; i < 64; i += 2) pkA[i] = movm(pkA[i]);
          kv_pack(1 - s, 0);
        }
        uint32_t kvH[32];
        {
          const uint4* const src = (warp == 0 && g >= 2) ? hp - 2 * 8 * 256 : ptr_add(xs, (warp ? warp - 1 : 0) * 4096u);
          c.steps<128>(acc2, 2);
          mbar_wait_fast(sb + BAR_XFULL, hl >> 1);
#pragma unroll
          for (int i = 0; i < 8; i++) gen_load(src + i * 32, kvH + 4 * i);
          c.steps<128>(acc2, 3 - wg);
          uint32_t spins = 0;
          while (__any_sync(0xffffffffu, !(kvH[0] && kvH[4] && kvH[8] && kvH[12] && kvH[16] && kvH[20] && kvH[24] && kvH[28]))) {
#pragma unroll
            for (int i = 0; i < 8; i++) gen_load(src + i * 32, kvH + 4 * i);
            spin_check(++spins);
          }
        }
#pragma unroll
        for (int i = 16; i < 32; i++) kvH[i] = movm(kvH[i]);
        mbar_wait_fast(sb + BAR_CLR, hl >> 1);
        c.steps<128>(acc2, 2);
        AP(0);
        c.wait_full(0);
        AP(1);
        c.drain();
        AP(2);
        acc_fence<64>(acc2);
        TLC(2 + it * 6);
        uint32_t q[32];
#pragma unroll
        for (int i = 0; i < 32; i++) q[i] = pack_bf16(acc2[2 * i], acc2[2 * i + 1]);
        const uint32_t zm = bar_sync_zero(1, 256);
        AP(3);
        uint32_t ob[4][16];
        uint4* const omail = scratch<uint4>(P, g * G_BLOCK + G_O + warp * 2048u + l16);
        auto o_fetch = [&](uint32_t (&v0)[16], uint32_t (&v1)[16], const uint4* p0, const uint4* p1) {
#pragma unroll
          for (int i = 0; i < 4; i++) pkt_load(p0 + i * 32, v0 + 4 * i);
#pragma unroll
          for (int i = 0; i < 4; i++) pkt_load(p1 + i * 32, v1 + 4 * i);
        };
        float o2[8][4], r2[4];
        {
          const float hv = (warp == 0 && g < 2) ? -INFINITY : 0.f;
          const float hinit[4] = {hv, hv, hv, hv};
          const bool c0 = (2 * quad <= gr), c1 = (2 * quad + 1 <= gr);
          const uint32_t lm = (c0 ? 0xffffu : 0u) | (c1 ? 0xffff0000u : 0u);
          const float sc[2] = {rstd[0] * (0.17677669529663687f * LOG2E), rstd[1] * (0.17677669529663687f * LOG2E)};
          float lg[4][4], mx[4][2];
#pragma unroll
          for (int h = 0; h < 4; h++) {
            const int b = h * 4;
            float sH[4], sL[4], sU[4];
            q[2 * b] |= zm;
            mma16816(sH, q[2 * b], q[2 * b + 1], q[2 * b + 2], q[2 * b + 3], kvH[b], kvH[b + 1], hinit);
            mma16816z(sL, q[2 * b], q[2 * b + 1], q[2 * b + 2], q[2 * b + 3], pkA[2 * b], pkA[2 * b + 2]);
            mma16816z(sU, q[2 * b], q[2 * b + 1], q[2 * b + 2], q[2 * b + 3], pkA[2 * b + 1], pkA[2 * b + 3]);
            mma16816(sH, q[2 * b + 4], q[2 * b + 5], q[2 * b + 6], q[2 * b + 7], kvH[b + 2], kvH[b + 3], sH);
            mma16816(sL, q[2 * b + 4], q[2 * b + 5], q[2 * b + 6], q[2 * b + 7], pkA[2 * b + 4], pkA[2 * b + 6], sL);
            mma16816(sU, q[2 * b + 4], q[2 * b + 5], q[2 * b + 6], q[2 * b + 7], pkA[2 * b + 5], pkA[2 * b + 7], sU);
            lg[h][0] = c0 ? sL[0] : sH[0]; lg[h][1] = c1 ? sL[1] : sH[1]; lg[h][2] = c0 ? sU[2] : sL[2]; lg[h][3] = c1 ? sU[3] : sL[3];
            mx[h][0] = fmaxf(lg[h][0], lg[h][1]); mx[h][1] = fmaxf(lg[h][2], lg[h][3]);
          }
#pragma unroll
          for (int o = 1; o < 4; o <<= 1) {
#pragma unroll
            for (int i = 0; i < 8; i++) mx[i >> 1][i & 1] = fmaxf(mx[i >> 1][i & 1], __shfl_xor_sync(0xffffffffu, mx[i >> 1][i & 1], o));
          }
          AP(4);
          uint32_t z = zm, pp[4][2];
          float rs[4][2];
          auto probs = [&](int h) {
            pp[h][0] = pack_bf16(ex2((lg[h][0] - mx[h][0]) * sc[0]), ex2((lg[h][1] - mx[h][0]) * sc[0]));
            pp[h][1] = pack_bf16(ex2((lg[h][2] - mx[h][1]) * sc[1]), ex2((lg[h][3] - mx[h][1]) * sc[1]));
            float sum[4];
            mma1688z(sum, pp[h][0], pp[h][1], 0x3f803f80u);
            rs[h][0] = rcp(sum[0]); rs[h][1] = rcp(sum[2]);
            if (P_EARLY) asm volatile("" : "+f"(rs[h][0]), "+f"(rs[h][1]));
          };
          if (P_EARLY) { probs(0); probs(1); probs(2); probs(3); }
#pragma unroll
          for (int hf = 0; hf < 2; hf++) {
#pragma unroll
            for (int hh = 0; hh < 2; hh++) {
              const int h = hf * 2 + hh, b = h * 4;
              if (!P_EARLY) probs(h);
              const uint32_t pa = pp[h][0], pb = pp[h][1];
              const uint32_t p0 = pa & ~lm, p1 = pa & z, p2 = pa & lm, p3 = pb & ~lm, p4 = pb & z, p5 = pb & lm;
              const float ra = rs[h][0], rb = rs[h][1];
#pragma unroll
              for (int d = 0; d < 4; d++) {
                float o[4];
                mma16816z(o, p0, p1, p2, p3, kvH[16 + b + d], pkA[32 + 2 * (b + d)]);
                mma1688(o, p4, p5, pkA[32 + 2 * (b + d) + 1], o);
                if (hf == 0) { ob[0][(hh * 4 + d) * 2] = pack_bf16(o[0] * ra, o[1] * ra); ob[0][(hh * 4 + d) * 2 + 1] = pack_bf16(o[2] * rb, o[3] * rb); }
                else { o2[hh * 4 + d][0] = o[0]; o2[hh * 4 + d][1] = o[1]; o2[hh * 4 + d][2] = o[2]; o2[hh * 4 + d][3] = o[3]; }
              }
              if (hf) { r2[2 * hh] = ra; r2[2 * hh + 1] = rb; }
            }
            if (hf == 0) {
#pragma unroll
              for (int i = 0; i < 4; i++) ob[0][4 * i] = pkt_head(ob[0][4 * i]);
              AP(5);
              uint4* op = ptr_add(omail, j * 32768u);
#pragma unroll
              for (int i = 0; i < 4; i++) st_b128(op + i * 32, ob[0][4 * i], ob[0][4 * i + 1], ob[0][4 * i + 2], ob[0][4 * i + 3]);
              z = late_zero(zm);
              AP(6);
            }
          }
        }
        auto finish_o2 = [&](uint32_t z) {
#pragma unroll
          for (int i = 0; i < 4; i++) r2[i] = __uint_as_float(__float_as_uint(r2[i]) | z);
#pragma unroll
          for (int i = 0; i < 8; i++) {
            ob[1][2 * i] = pack_bf16(o2[i][0] * r2[(i >> 2) * 2], o2[i][1] * r2[(i >> 2) * 2]);
            ob[1][2 * i + 1] = pack_bf16(o2[i][2] * r2[(i >> 2) * 2 + 1], o2[i][3] * r2[(i >> 2) * 2 + 1]);
          }
#pragma unroll
          for (int i = 0; i < 4; i++) { ob[1][4 * i] = pkt_head(ob[1][4 * i]); sts128(stage + (warp & 3) * 2048 + i * 512 + l16, ob[1][4 * i], ob[1][4 * i + 1], ob[1][4 * i + 2], ob[1][4 * i + 3]); }
        };
        {
          uint32_t dep = __float_as_uint(r2[0]) | __float_as_uint(r2[2]);
#pragma unroll
          for (int i = 0; i < 8; i++) dep |= __float_as_uint(o2[i][3]);
          const uint32_t cnt = 256 | (dep & zm);
          AP(7);
          if (wg) { asm volatile("bar.arrive 1, %0;" :: "r"(cnt) : "memory"); bar_sync(6, 256); } else bar_sync(1, cnt);
        }
        TLC(3 + it * 6);
        AP(8);
        uint64_t todo;
        { const uint32_t o7 = 0x6543210u | (7u << (4 * j) & 0xfffffffu); todo = (uint64_t)(o7 * 2) | (uint64_t)(o7 * 2 + 0x1111111u) << 28; }
        const uint4* p0 = ptr_add(omail, ((uint32_t)todo & 15u) << 14);
        const uint4* p1 = ptr_add(omail, ((uint32_t)todo & 240u) << 10);
        auto batch = [&](int b, bool first) {
          uint32_t (&y0)[16] = ob[b ^ 2], (&y1)[16] = ob[b ^ 3];
          if (first) {
            c.issue_rs(acc2, ob[0], 0, 0);
            finish_o2(late_zero(zm));
            o_fetch(y0, y1, p0, p1);
          } else {
            o_fetch(y0, y1, p0, p1);
            c.issue_rs(acc2, ob[b], 0, 1);
          }
          c.issue_rs(acc2, ob[b + 1], 1, 1);
          if (first && !wg) asm volatile("bar.arrive 6, 256;" ::: "memory");
          const uint32_t z = late_zero(zm);
          todo >>= 8;
          const uint4* n0 = ptr_add(omail, ((uint32_t)todo & 15u) << 14);
          const uint4* n1 = ptr_add(omail, ((uint32_t)todo & 240u) << 10);
          asm volatile("" : "+l"(n0), "+l"(n1));
          c.wait_full(0);
          uint32_t spins = 0;
          while (__builtin_expect(__any_sync(0xffffffffu, (y0[0] == z || y0[4] == z || y0[8] == z || y0[12] == z) | (y1[0] == z || y1[4] == z || y1[8] == z || y1[12] == z)), 0)) {
            o_fetch(y0, y1, p0, p1);
            spin_check(++spins);
          }
          if (first) {
            fence_async_smem();
            __syncwarp();
            if (elect_one()) {
              asm volatile("cp.async.bulk.global.shared::cta.bulk_group [%0], [%1], 2048;"
                           :: "l"(scratch<uint4>(P, g * G_BLOCK + G_O + (2 * j + 1) * 16384u + warp * 2048u)), "r"(stage + (warp & 3) * 2048) : "memory");
              bulk_commit();
            }
          }
          p0 = n0; p1 = n1;
          c.drain();
        };
        batch(0, true);
#pragma unroll 1
        for (int i = 0; i < 3; i++) { batch(2, false); batch(0, false); }
        c.issue_rs(acc2, ob[2], 0, 1); c.issue_rs(acc2, ob[3], 1, 1);
        if (elect_one()) bulk_wait<0>();
        __syncwarp();
        {
          c.wait_full(0);
          const uint32_t ra = maddr - (SM_STAGE + wg * 8192) + (c.off << 4);
#pragma unroll
          for (int i = 0; i < 8; i++) ldsm4((ra ^ ((i & 3) << 5)) + (i >> 2) * PAGE, res[4 * i], res[4 * i + 1], res[4 * i + 2], res[4 * i + 3]);
          if (lane < 2) mbar_arrive_cluster(c.ebar + 64 + ((c.n & 7) << 3));
          c.advance<2>();
          c.drain();
        }
        break;
      } else {
        c.steps<128>(acc2, 1 + wg);
        stage_wait();
        glu_slice_acc(acc, 0);
#pragma unroll
        for (int s = 1; s < 8; s++) { c.steps<128>(acc2, (s & 1) || t == 3 ? 2 : 1); if (s == 4) stage_publish(); glu_slice_acc(acc, s); }
        c.steps<128>(acc2, 2 - wg);
        stage_publish();
        if (t == 3) {
#pragma unroll
          for (int i = 0; i < 32; i++) { res[i] = 0x80008000u; asm volatile("" : "+r"(res[i])); }
          if (TAIL_LAG) {
#pragma unroll 1
            for (int i = 0; i < 2; i++) {
              c.steps<128>(acc2, i ? TAIL_LAG : 39 - TAIL_LAG);
              if (hl == 3) { if (wg == 1 && i == 0) { c.drain(); bar_sync(5, 256); } else if (wg == 0 && i == 1) asm volatile("bar.arrive 5, 256;" ::: "memory"); }
            }
          } else c.steps<128>(acc2, 39);
          stage_wait();
          c.drain();
          break;
        }
        c.drain();
        TLC(2 + it * 6);
        c.step<256>(acc, 0);
        acc_fence<64>(acc2);
#pragma unroll
        for (int i = 0; i < 16; i++) {
          pkB[16 + i] = pack_bf16(acc2[2 * i], acc2[2 * i + 1]); pkB[48 + i] = pack_bf16(acc2[32 + 2 * i], acc2[32 + 2 * i + 1]);
          pkB[i] = 0; pkB[32 + i] = 0;
        }
      }
      t++;
#pragma unroll 1
      for (int s = 3 - t; s < 8; s++) {
        c.step<256>(acc, s);
        int act = (t == 3 || s >= 4) ? s : 8;
        asm volatile("" : "+r"(act));
        if (act < 8) {
          if (!(act & 3)) { if (act && t == 3) stage_publish(); else stage_wait(); }
          auto f = [&](int i) { glu_slice(pkB, i); };
          SELECT8(act, f);
        }
      }
#pragma unroll
      for (int s = 0; s < 2; s++) {
        const uint32_t ra = maddr - (SM_STAGE + wg * 8192) + (c.off << 4);
        c.step<256>(acc);
        if (s == 0) stage_publish();
#pragma unroll
        for (int i = 0; i < 4; i++) {
          uint32_t v[4];
          ldsm4(ra ^ (i << 5), v[0], v[1], v[2], v[3]);
#pragma unroll
          for (int e = 0; e < 4; e++) { acc2[32 * s + 8 * i + 2 * e] = bf_lo(v[e]); acc2[32 * s + 8 * i + 2 * e + 1] = bf_hi(v[e]); }
        }
        acc_fence<32>(acc2 + 32 * s);
      }
      c.step<256>(acc);
      }
      const int it = (hl >> 1) * 4 + t;
      acc_fence<64>(acc2);
      TLC(4 + it * 6);
      stage_x(acc2, res, 0);
      if (hl == 3) { stage_x(acc2, res, 1); TLE(47); TLG(63); break; }
      bar_sync(2 + wg, 128);
      TLC(5 + it * 6);
      c.step_own<256>(acc, dstage, 0);
      acc_fence<32>(acc2 + 32);
      stage_x(acc2, res, 1);
      bar_sync(2 + wg, 128);
    }
    }
  }
}

typedef CUresult (*EncodeFn)(CUtensorMap*, CUtensorMapDataType, cuuint32_t, void*, const cuuint64_t*, const cuuint64_t*, const cuuint32_t*,
                             const cuuint32_t*, CUtensorMapInterleave, CUtensorMapSwizzle, CUtensorMapL2promotion, CUtensorMapFloatOOBfill);

void encode(EncodeFn fn, CUtensorMap* m, const void* ptr, int rank, const cuuint64_t* dims, const cuuint64_t* strides, const cuuint32_t* box) {
  cuuint32_t es[5] = {1, 1, 1, 1, 1};
  fn(m, CU_TENSOR_MAP_DATA_TYPE_BFLOAT16, rank, const_cast<void*>(ptr), dims, strides, box, es, CU_TENSOR_MAP_INTERLEAVE_NONE,
     CU_TENSOR_MAP_SWIZZLE_128B, CU_TENSOR_MAP_L2_PROMOTION_L2_128B, CU_TENSOR_MAP_FLOAT_OOB_FILL_NONE);
}

}

extern "C" void kernel_launch(void* const* d_in, const int* in_sizes, int n_in, void* d_out, int out_size) {
  const __nv_bfloat16* x = (const __nv_bfloat16*)d_in[0];
  const __nv_bfloat16* wqkv = (const __nv_bfloat16*)d_in[1];
  const __nv_bfloat16* wo = (const __nv_bfloat16*)d_in[2];
  const __nv_bfloat16* w1 = (const __nv_bfloat16*)d_in[4];
  const __nv_bfloat16* w3 = (const __nv_bfloat16*)d_in[5];
  const __nv_bfloat16* w2 = (const __nv_bfloat16*)d_in[6];

  void* fnp = nullptr; cudaDriverEntryPointQueryResult qr;
  cudaGetDriverEntryPoint("cuTensorMapEncodeTiled", &fnp, cudaEnableDefault, &qr);
  EncodeFn fn = (EncodeFn)fnp;
  void* sym;
  cudaGetSymbolAddress(&sym, g_scratch);
  uint8_t* scr = (uint8_t*)(((uintptr_t)sym + G_BLOCK - 1) / G_BLOCK * G_BLOCK);

  Params P = {};
  { cuuint64_t d[3] = {DM, 2, SEQ / 2}, s[2] = {DM * 2, DM * 4}; cuuint32_t b[3] = {64, 1, 128}, b2[3] = {64, 1, 64};
    encode(fn, &P.map[M_XIN], x, 3, d, s, b); encode(fn, &P.map[M_XIN64], x, 3, d, s, b2);
    encode(fn, &P.map[M_OUT_LD], d_out, 3, d, s, b); encode(fn, &P.map[M_OUT_ST], d_out, 3, d, s, b2); }
  { cuuint64_t d[3] = {FF, 16, 128}, s[2] = {G_BLOCK, FF * 2}; cuuint32_t b[3] = {64, 1, 128}, b2[3] = {64, 1, 64};
    encode(fn, &P.map[M_H_LD], scr + G_H, 3, d, s, b); encode(fn, &P.map[M_H_ST], scr + G_H, 3, d, s, b2); }
  { const cuuint32_t b2[3] = {64, 64, 2}, b1[3] = {64, 64, 1};
    { cuuint64_t d[3] = {64, DM, 48}, s[2] = {3 * DM * 2, 128}; encode(fn, &P.map[M_WKV], wqkv, 3, d, s, b2); encode(fn, &P.map[M_WQ], wqkv, 3, d, s, b1); }
    { cuuint64_t d[3] = {64, DM, 16}, s[2] = {DM * 2, 128}; encode(fn, &P.map[M_WO], wo, 3, d, s, b1); }
    { cuuint64_t d[3] = {64, FF, 16}, s[2] = {DM * 2, 128}; encode(fn, &P.map[M_W2], w2, 3, d, s, b1); }
    { cuuint64_t d[3] = {64, DM, FF / 64}, s[2] = {FF * 2, 128};
      encode(fn, &P.map[M_W1], w1, 3, d, s, b2); encode(fn, &P.map[M_W3], w3, 3, d, s, b2);
      encode(fn, &P.map[M_W1H], w1, 3, d, s, b1); encode(fn, &P.map[M_W3H], w3, 3, d, s, b1); }
  }
  P.scratch = scr; P.x = x; P.wqkv = wqkv; P.wo = wo; P.w2 = w2;
  int dev = 0, sms = 0;
  cudaGetDevice(&dev);
  cudaDeviceGetAttribute(&sms, cudaDevAttrMultiProcessorCount, dev);
  P.use_smid = (sms == 132);
  cudaFuncSetAttribute(fused_kernel, cudaFuncAttributeMaxDynamicSharedMemorySize, SM_ALLOC);
  fused_kernel<<<132, 384, SM_ALLOC>>>(P);
}
```

```cpp
#include <cuda_runtime.h>
#include <cuda_bf16.h>
#include <cuda.h>
#include <stdint.h>
#include <math.h>

namespace {

constexpr int SEQ = 2048, DM = 1024, FF = 3584;
constexpr float LN_EPS = 1e-5f;
constexpr float LOG2E = 1.4426950408889634f;

#define G_SKEW 4096
constexpr uint32_t G_PAGE = 2u << 20, G_BLOCK = G_PAGE + G_SKEW;
constexpr uint32_t G_H = 0;
constexpr uint32_t G_O = G_H + 128 * FF * 2;
constexpr uint32_t G_STATS = G_O + 128 * DM * 2;
constexpr uint32_t G_FLAGS = G_STATS + 4 * 128 * 64;
static_assert(G_FLAGS + 4096 + 15 * G_SKEW <= G_PAGE, "");
constexpr uint32_t G_HALO = 16 * G_PAGE;
constexpr uint32_t G_CS = G_HALO + 2 * 16 * 8 * 4096;
constexpr uint32_t G_EPOCH = G_CS + (3 * DM + 2 * FF) * 16;
__device__ __align__(1024) uint8_t g_scratch[18 * G_PAGE];

enum { M_XIN, M_XIN64, M_H_LD, M_H_ST, M_OUT_LD, M_OUT_ST, M_WKV, M_WQ, M_WO, M_W1, M_W3, M_W1H, M_W3H, M_W2, M_COUNT };
struct alignas(64) Params {
  CUtensorMap map[M_COUNT];
  uint8_t* scratch;
  const __nv_bfloat16* x;
  const __nv_bfloat16* wqkv;
  const __nv_bfloat16* wo;
  const __nv_bfloat16* w2;
  int use_smid;
};

constexpr uint32_t PAGE = 16384, NPAGE = 12;
constexpr uint32_t SM_STAGE = NPAGE * PAGE;
constexpr uint32_t SM_BAR = SM_STAGE + 2 * PAGE;
constexpr uint32_t SM_CS = SM_BAR + 256;
constexpr uint32_t SM_TOTAL = SM_CS + 1536;
constexpr uint32_t SM_ALLOC = SM_TOTAL;
static_assert(SM_ALLOC <= 232448, "shared memory");
constexpr uint32_t BAR_FULL = SM_BAR, BAR_EMPTY = SM_BAR + 64, BAR_SFULL = SM_BAR + 128;
constexpr uint32_t BAR_XFULL = SM_BAR + 160, BAR_CSE = SM_BAR + 168;
constexpr uint32_t BAR_SEMPTY = SM_BAR + 176, BAR_CSF = SM_BAR + 184, BAR_XIN = SM_BAR + 200;
constexpr uint32_t BAR_CLR = SM_BAR + 240, BAR_TAG = SM_BAR + 216, SM_ROLE = SM_BAR + 224, SM_TAG = SM_BAR + 228, SM_SEEN = SM_BAR + 232;
enum { EV_XA, EV_XA2, EV_H0, EV_H3, EV_H1, EV_H2, EV_XB, EV_XB2, EV_N };

#define WO_HOLD 5
struct Sched { uint32_t pat[16]; uint32_t page0[16]; bool ok; };
constexpr int seg_steps(int seg) { return seg == 0 || seg == 3 ? 18 : seg == 1 || seg == 4 ? 14 : seg == 2 ? 9 : seg == 7 ? 24 : 32; }
constexpr int step_pages(int seg, int i) {
  return seg == 0 || seg == 3 ? (i < 2 ? 2 : i < 4 ? 1 : 3) : seg == 5 ? 3 : 2;
}
constexpr Sched make_sched() {
  Sched s = {};
  int owner[NPAGE] = {-1, -1, -1, -1, -1, -1, -1, -1, -1, -1, -1, -1};
  int n = 0, tail = 0, page = 0;
  s.ok = true;
  for (int sg = 0; sg < 16; sg++) {
    const int seg = sg % 8;
    s.page0[sg] = page;
    for (int i = 0; i < seg_steps(seg); i++) {
      const int p = step_pages(seg, i);
      if ((seg == 2 && i == 8) || (seg == 4 && i == 8) || (seg == 7 && i == 0)) page = (page + 2) % NPAGE;
      if (page + p > (int)NPAGE) { s.ok = false; return s; }
      int need = n - 8;
      for (int q = 0; q < p; q++) { if (owner[page + q] > need) need = owner[page + q]; owner[page + q] = n; }
      if (seg == 3 && i < 4 && need < n - i - WO_HOLD + (i > 2 ? 2 : i)) need = n - i - WO_HOLD + (i > 2 ? 2 : i);
      int nw = need + 1 - tail; if (nw < 0) nw = 0;
      tail += nw;
      if (i < 16) s.pat[sg] |= (uint32_t)nw << (2 * i); else if (nw != 1) s.ok = false;
      if (nw > 3) s.ok = false;
      page = (page + p) % NPAGE; n++;
    }
  }
  for (int sg = 0; sg < 8; sg++) if (s.page0[sg] != s.page0[sg + 8] || (sg && s.pat[sg] != s.pat[sg + 8])) s.ok = false;
  return s;
}
constexpr Sched SCHED = make_sched();
static_assert(SCHED.ok && SCHED.page0[0] == 0 && SCHED.page0[3] == 0 && SCHED.page0[5] == 6 && SCHED.page0[2] == 4 && SCHED.page0[7] == 10 && (SCHED.pat[0] & 0xfff) == 0, "ring schedule");
template <int SEG> struct Pat { static constexpr uint32_t v = SCHED.pat[SEG]; };

#define TAIL_LAG 3
__device__ __forceinline__ uint32_t smem_u32(const void* p) { return (uint32_t)__cvta_generic_to_shared(p); }
__device__ __forceinline__ void mbar_init(uint32_t bar, uint32_t cnt) { asm volatile("mbarrier.init.shared::cta.b64 [%0], %1;" :: "r"(bar), "r"(cnt)); }
__device__ __forceinline__ void mbar_expect_tx(uint32_t bar, uint32_t bytes) { asm volatile("mbarrier.arrive.expect_tx.shared::cta.b64 _, [%0], %1;" :: "r"(bar), "r"(bytes) : "memory"); }
__device__ __forceinline__ void mbar_arrive(uint32_t bar) { asm volatile("mbarrier.arrive.shared::cta.b64 _, [%0];" :: "r"(bar) : "memory"); }
__device__ __forceinline__ void mbar_wait(uint32_t bar, uint32_t parity) {
  asm volatile("{\n.reg .pred p;\n.reg .u32 n;\nmov.u32 n, 0;\nLAB_WAIT:\n"
               "mbarrier.try_wait.parity.shared::cta.b64 p, [%0], %1;\n@p bra LAB_DONE;\n"
               "add.u32 n, n, 1;\nsetp.lt.u32 p, n, 4194304;\n@p bra LAB_WAIT;\ntrap;\nLAB_DONE:\n}" :: "r"(bar), "r"(parity) : "memory");
}
__device__ __forceinline__ void mbar_wait_fast(uint32_t bar, uint32_t parity) {
  asm volatile("{\n.reg .pred p;\nLAB_WAIT:\nmbarrier.try_wait.parity.shared::cta.b64 p, [%0], %1;\n@!p bra LAB_WAIT;\n}" :: "r"(bar), "r"(parity) : "memory");
}
__device__ __forceinline__ void spin_check(uint32_t n) { asm volatile("{\n.reg .pred p;\nsetp.ge.u32 p, %0, 4194304;\n@p st.volatile.global.u32 [%1], %0;\n}" :: "r"(n), "l"(0ull)); }
__device__ __forceinline__ void tma_ld3(uint32_t dst, const CUtensorMap* m, uint32_t bar, int c0, int c1, int c2) {
  asm volatile("cp.async.bulk.tensor.3d.shared::cluster.global.mbarrier::complete_tx::bytes [%0], [%1, {%3, %4, %5}], [%2];" :: "r"(dst), "l"(m), "r"(bar), "r"(c0), "r"(c1), "r"(c2) : "memory");
}
__device__ __forceinline__ void tma_ld3_mc(uint32_t dst, const CUtensorMap* m, uint32_t bar, int c0, int c1, int c2, uint16_t mask) {
  asm volatile("cp.async.bulk.tensor.3d.shared::cluster.global.mbarrier::complete_tx::bytes.multicast::cluster [%0], [%1, {%3, %4, %5}], [%2], %6;"
               :: "r"(dst), "l"(m), "r"(bar), "r"(c0), "r"(c1), "r"(c2), "h"(mask) : "memory");
}
__device__ __forceinline__ uint32_t mapa(uint32_t addr, uint32_t cta) { uint32_t r; asm("mapa.shared::cluster.u32 %0, %1, %2;" : "=r"(r) : "r"(addr), "r"(cta)); return r; }
__device__ __forceinline__ void mbar_arrive_cluster(uint32_t bar) { asm volatile("mbarrier.arrive.shared::cluster.b64 _, [%0];" :: "r"(bar) : "memory"); }
__device__ __forceinline__ void tma_st3(const CUtensorMap* m, uint32_t src, int c0, int c1, int c2) {
  asm volatile("cp.async.bulk.tensor.3d.global.shared::cta.bulk_group [%0, {%2, %3, %4}], [%1];" :: "l"(m), "r"(src), "r"(c0), "r"(c1), "r"(c2) : "memory");
}
__device__ __forceinline__ void bulk_commit() { asm volatile("cp.async.bulk.commit_group;" ::: "memory"); }
template <int N> __device__ __forceinline__ void bulk_wait() { asm volatile("cp.async.bulk.wait_group %0;" :: "n"(N) : "memory"); }
__device__ __forceinline__ void fence_async_smem() { asm volatile("fence.proxy.async.shared::cta;" ::: "memory"); }
__device__ __forceinline__ void fence_async_global() { asm volatile("fence.proxy.async.global;" ::: "memory"); }
__device__ __forceinline__ bool elect_one() { uint32_t p; asm volatile("{\n.reg .pred P;\nelect.sync _|P, 0xffffffff;\nselp.u32 %0, 1, 0, P;\n}" : "=r"(p)); return p; }
__device__ __forceinline__ void prefetch_map(const CUtensorMap* m) { asm volatile("prefetch.tensormap [%0];" :: "l"(m) : "memory"); }
__device__ __forceinline__ void prefetch_l2(const void* p, uint32_t bytes) { asm volatile("cp.async.bulk.prefetch.L2.global [%0], %1;" :: "l"(p), "r"(bytes) : "memory"); }
__device__ __forceinline__ void wgmma_fence() { asm volatile("wgmma.fence.sync.aligned;" ::: "memory"); }
__device__ __forceinline__ void wgmma_commit() { asm volatile("wgmma.commit_group.sync.aligned;" ::: "memory"); }
template <int N> __device__ __forceinline__ void wgmma_wait() { asm volatile("wgmma.wait_group.sync.aligned %0;" :: "n"(N) : "memory"); }
__device__ __forceinline__ uint32_t desc_lo(uint32_t addr, uint32_t lbo) { return ((addr & 0x3FFFF) >> 4) | ((lbo >> 4) << 16); }
__device__ __forceinline__ uint64_t desc64(uint32_t lo) { uint64_t r; asm("mov.b64 %0, {%1, %2};" : "=l"(r) : "r"(lo), "r"(0x40000040u)); return r; }
__device__ __forceinline__ void bar_sync(int id, int n) { asm volatile("bar.sync %0, %1;" :: "r"(id), "r"(n) : "memory"); }
__device__ __forceinline__ uint32_t pack_bf16(float lo, float hi) { uint32_t r; asm("cvt.rn.bf16x2.f32 %0, %1, %2;" : "=r"(r) : "f"(hi), "f"(lo)); return r; }
__device__ __forceinline__ float bf_lo(uint32_t v) { return __uint_as_float(v << 16); }
__device__ __forceinline__ float bf_hi(uint32_t v) { return __uint_as_float(v & 0xffff0000u); }
__device__ __forceinline__ float ex2(float x) { float r; asm("ex2.approx.ftz.f32 %0, %1;" : "=f"(r) : "f"(x)); return r; }
__device__ __forceinline__ float rcp(float x) { float r; asm("rcp.approx.ftz.f32 %0, %1;" : "=f"(r) : "f"(x)); return r; }
__device__ __forceinline__ void stsm4(uint32_t a, uint32_t r0, uint32_t r1, uint32_t r2, uint32_t r3) {
  asm volatile("stmatrix.sync.aligned.m8n8.x4.shared.b16 [%0], {%1, %2, %3, %4};" :: "r"(a), "r"(r0), "r"(r1), "r"(r2), "r"(r3) : "memory");
}
__device__ __forceinline__ void ldsm4(uint32_t a, uint32_t& r0, uint32_t& r1, uint32_t& r2, uint32_t& r3) {
  asm volatile("ldmatrix.sync.aligned.m8n8.x4.shared.b16 {%0, %1, %2, %3}, [%4];" : "=r"(r0), "=r"(r1), "=r"(r2), "=r"(r3) : "r"(a) : "memory");
}
__device__ __forceinline__ uint32_t movm(uint32_t v) { uint32_t r; asm volatile("movmatrix.sync.aligned.m8n8.trans.b16 %0, %1;" : "=r"(r) : "r"(v)); return r; }
__device__ __forceinline__ void sts128(uint32_t a, uint32_t r0, uint32_t r1, uint32_t r2, uint32_t r3) {
  asm volatile("st.shared.v4.b32 [%0], {%1, %2, %3, %4};" :: "r"(a), "r"(r0), "r"(r1), "r"(r2), "r"(r3) : "memory");
}
__device__ __forceinline__ void lds128(uint32_t a, uint32_t& r0, uint32_t& r1, uint32_t& r2, uint32_t& r3) {
  asm volatile("ld.shared.v4.b32 {%0, %1, %2, %3}, [%4];" : "=r"(r0), "=r"(r1), "=r"(r2), "=r"(r3) : "r"(a) : "memory");
}
__device__ __forceinline__ uint32_t add_bf16x2(uint32_t a, uint32_t b) { uint32_t r; asm("add.rn.bf16x2 %0, %1, %2;" : "=r"(r) : "r"(a), "r"(b)); return r; }
__device__ __forceinline__ void sts32f(uint32_t a, float v) { asm volatile("st.shared.f32 [%0], %1;" :: "r"(a), "f"(v) : "memory"); }
__device__ __forceinline__ void mma16816(float (&d)[4], uint32_t a0, uint32_t a1, uint32_t a2, uint32_t a3, uint32_t b0, uint32_t b1, const float (&c)[4]) {
  asm("mma.sync.aligned.m16n8k16.row.col.f32.bf16.bf16.f32 {%0, %1, %2, %3}, {%4, %5, %6, %7}, {%8, %9}, {%10, %11, %12, %13};"
      : "=f"(d[0]), "=f"(d[1]), "=f"(d[2]), "=f"(d[3]) : "r"(a0), "r"(a1), "r"(a2), "r"(a3), "r"(b0), "r"(b1), "f"(c[0]), "f"(c[1]), "f"(c[2]), "f"(c[3]));
}
__device__ __forceinline__ void mma1688(float (&d)[4], uint32_t a0, uint32_t a1, uint32_t b0, const float (&c)[4]) {
  asm("mma.sync.aligned.m16n8k8.row.col.f32.bf16.bf16.f32 {%0, %1, %2, %3}, {%4, %5}, {%6}, {%7, %8, %9, %10};"
      : "=f"(d[0]), "=f"(d[1]), "=f"(d[2]), "=f"(d[3]) : "r"(a0), "r"(a1), "r"(b0), "f"(c[0]), "f"(c[1]), "f"(c[2]), "f"(c[3]));
}
__device__ __forceinline__ void mma16816z(float (&d)[4], uint32_t a0, uint32_t a1, uint32_t a2, uint32_t a3, uint32_t b0, uint32_t b1) {
  asm("mma.sync.aligned.m16n8k16.row.col.f32.bf16.bf16.f32 {%0, %1, %2, %3}, {%4, %5, %6, %7}, {%8, %9}, {0f00000000, 0f00000000, 0f00000000, 0f00000000};"
      : "=f"(d[0]), "=f"(d[1]), "=f"(d[2]), "=f"(d[3]) : "r"(a0), "r"(a1), "r"(a2), "r"(a3), "r"(b0), "r"(b1));
}
__device__ __forceinline__ void mma1688z(float (&d)[4], uint32_t a0, uint32_t a1, uint32_t b0) {
  asm("mma.sync.aligned.m16n8k8.row.col.f32.bf16.bf16.f32 {%0, %1, %2, %3}, {%4, %5}, {%6}, {0f00000000, 0f00000000, 0f00000000, 0f00000000};"
      : "=f"(d[0]), "=f"(d[1]), "=f"(d[2]), "=f"(d[3]) : "r"(a0), "r"(a1), "r"(b0));
}
__device__ __forceinline__ uint32_t bar_sync_zero(int id, int n) {
  uint32_t r;
  asm volatile("{\n.reg .pred p;\nsetp.eq.u32 p, %1, 0;\nbarrier.cta.red.popc.aligned.u32 %0, %1, %2, p;\n}" : "=r"(r) : "r"(id), "r"(n) : "memory");
  return r;
}
__device__ __forceinline__ uint32_t late_zero(uint32_t zm) { uint32_t c; asm volatile("mov.u32 %0, %%clock;" : "=r"(c) :: "memory"); return c & zm; }
__device__ __forceinline__ void st_b128(uint4* p, uint32_t a, uint32_t b, uint32_t c, uint32_t d) {
  asm volatile("{\n.reg .b128 t;\n.reg .b64 lo, hi;\nmov.b64 lo, {%0, %1};\nmov.b64 hi, {%2, %3};\nmov.b128 t, {lo, hi};\nst.relaxed.gpu.global.b128 [%4], t;\n}"
               :: "r"(a), "r"(b), "r"(c), "r"(d), "l"(p) : "memory");
}
__device__ __forceinline__ uint32_t pkt_head(uint32_t a) { return a ? a : 0x8000u; }
__device__ __forceinline__ void gen_store(uint4* p, uint32_t a, uint32_t b, uint32_t c, uint32_t d) {
  asm volatile("{\n.reg .b128 t;\n.reg .b64 lo, hi;\nmov.b64 lo, {%0, %1};\nmov.b64 hi, {%2, %3};\nmov.b128 t, {lo, hi};\nst.relaxed.gpu.b128 [%4], t;\n}"
               :: "r"(a), "r"(b), "r"(c), "r"(d), "l"(p) : "memory");
}
__device__ __forceinline__ void gen_load(const uint4* p, uint32_t* v) {
  asm volatile("{\n.reg .b128 t;\n.reg .b64 lo, hi;\nld.relaxed.gpu.b128 t, [%4];\nmov.b128 {lo, hi}, t;\nmov.b64 {%0, %1}, lo;\nmov.b64 {%2, %3}, hi;\n}"
               : "=r"(v[0]), "=r"(v[1]), "=r"(v[2]), "=r"(v[3]) : "l"(p) : "memory");
}
__device__ __forceinline__ void pkt_load(const uint4* p, uint32_t* v) {
  asm volatile("{\n.reg .b128 t;\n.reg .b64 lo, hi;\nld.relaxed.gpu.global.b128 t, [%4];\nmov.b128 {lo, hi}, t;\nmov.b64 {%0, %1}, lo;\nmov.b64 {%2, %3}, hi;\n}"
               : "=r"(v[0]), "=r"(v[1]), "=r"(v[2]), "=r"(v[3]) : "l"(p) : "memory");
}
__device__ __forceinline__ uint32_t ld_relaxed(const uint32_t* p) { uint32_t v; asm volatile("ld.relaxed.gpu.global.u32 %0, [%1];" : "=r"(v) : "l"(p) : "memory"); return v; }
__device__ __forceinline__ uint4 ld_relaxed4(const void* p) { uint4 v; asm volatile("ld.relaxed.gpu.global.v4.u32 {%0, %1, %2, %3}, [%4];" : "=r"(v.x), "=r"(v.y), "=r"(v.z), "=r"(v.w) : "l"(p) : "memory"); return v; }
__device__ __forceinline__ void st_relaxed(uint32_t* p, uint32_t v) { asm volatile("st.relaxed.gpu.global.u32 [%0], %1;" :: "l"(p), "r"(v) : "memory"); }
__device__ __forceinline__ void st_relaxed2(void* p, uint32_t a, uint32_t b) { asm volatile("st.relaxed.gpu.global.v2.u32 [%0], {%1, %2};" :: "l"(p), "r"(a), "r"(b) : "memory"); }
__device__ __forceinline__ void red_release(uint32_t* p, uint32_t v) { asm volatile("red.release.gpu.global.add.u32 [%0], %1;" :: "l"(p), "r"(v) : "memory"); }
__device__ __forceinline__ uint32_t tagf(float v, uint32_t tag) { return (__float_as_uint(v) & ~15u) | (tag & 15u); }
__device__ __forceinline__ bool tag_ok4(const uint4& v, uint32_t tag) { return (((v.x ^ tag) | (v.y ^ tag) | (v.z ^ tag) | (v.w ^ tag)) & 15u) == 0; }
__device__ __forceinline__ float untag(uint32_t v) { return __uint_as_float(v & ~15u); }
template <typename T> __device__ __forceinline__ T* ptr_add(T* p, uint32_t bytes) {
  uint64_t r;
  asm("{\n.reg .u32 lo, hi;\nmov.b64 {lo, hi}, %1;\nadd.cc.u32 lo, lo, %2;\naddc.u32 hi, hi, 0;\nmov.b64 %0, {lo, hi};\n}" : "=l"(r) : "l"(p), "r"(bytes));
  return (T*)r;
}
#define TL(who, slot) do {} while (0)
#define TLC(slot) do {} while (0)
#define TLE(slot) do {} while (0)
#define ST(who, n) do {} while (0)
#define AP(i) do {} while (0)
#define SP(v) do {} while (0)
#define TLG(slot) do {} while (0)
#define STA() do {} while (0)
#define STB(n) do {} while (0)

__device__ __forceinline__ void wgmma_n128(float (&d)[64], uint64_t da, uint64_t db, int scale_d) {
  asm volatile("{\n.reg .pred p;\nsetp.ne.b32 p, %66, 0;\n"
    "wgmma.mma_async.sync.aligned.m64n128k16.f32.bf16.bf16 "
    "{%0, %1, %2, %3, %4, %5, %6, %7, %8, %9, %10, %11, %12, %13, %14, %15, "
    "%16, %17, %18, %19, %20, %21, %22, %23, %24, %25, %26, %27, %28, %29, %30, %31, "
    "%32, %33, %34, %35, %36, %37, %38, %39, %40, %41, %42, %43, %44, %45, %46, %47, "
    "%48, %49, %50, %51, %52, %53, %54, %55, %56, %57, %58, %59, %60, %61, %62, %63}, "
    "%64, %65, p, 1, 1, 0, 1;\n}\n"
    : "+f"(d[0]), "+f"(d[1]), "+f"(d[2]), "+f"(d[3]), "+f"(d[4]), "+f"(d[5]), "+f"(d[6]), "+f"(d[7]),
      "+f"(d[8]), "+f"(d[9]), "+f"(d[10]), "+f"(d[11]), "+f"(d[12]), "+f"(d[13]), "+f"(d[14]), "+f"(d[15]),
      "+f"(d[16]), "+f"(d[17]), "+f"(d[18]), "+f"(d[19]), "+f"(d[20]), "+f"(d[21]), "+f"(d[22]), "+f"(d[23]),
      "+f"(d[24]), "+f"(d[25]), "+f"(d[26]), "+f"(d[27]), "+f"(d[28]), "+f"(d[29]), "+f"(d[30]), "+f"(d[31]),
      "+f"(d[32]), "+f"(d[33]), "+f"(d[34]), "+f"(d[35]), "+f"(d[36]), "+f"(d[37]), "+f"(d[38]), "+f"(d[39]),
      "+f"(d[40]), "+f"(d[41]), "+f"(d[42]), "+f"(d[43]), "+f"(d[44]), "+f"(d[45]), "+f"(d[46]), "+f"(d[47]),
      "+f"(d[48]), "+f"(d[49]), "+f"(d[50]), "+f"(d[51]), "+f"(d[52]), "+f"(d[53]), "+f"(d[54]), "+f"(d[55]),
      "+f"(d[56]), "+f"(d[57]), "+f"(d[58]), "+f"(d[59]), "+f"(d[60]), "+f"(d[61]), "+f"(d[62]), "+f"(d[63])
    : "l"(da), "l"(db), "r"(scale_d));
}
__device__ __forceinline__ void wgmma_n256(float (&d)[128], uint64_t da, uint64_t db, int scale_d) {
  asm volatile("{\n.reg .pred p;\nsetp.ne.b32 p, %130, 0;\n"
    "wgmma.mma_async.sync.aligned.m64n256k16.f32.bf16.bf16 "
    "{%0, %1, %2, %3, %4, %5, %6, %7, %8, %9, %10, %11, %12, %13, %14, %15, "
    "%16, %17, %18, %19, %20, %21, %22, %23, %24, %25, %26, %27, %28, %29, %30, %31, "
    "%32, %33, %34, %35, %36, %37, %38, %39, %40, %41, %42, %43, %44, %45, %46, %47, "
    "%48, %49, %50, %51, %52, %53, %54, %55, %56, %57, %58, %59, %60, %61, %62, %63, "
    "%64, %65, %66, %67, %68, %69, %70, %71, %72, %73, %74, %75, %76, %77, %78, %79, "
    "%80, %81, %82, %83, %84, %85, %86, %87, %88, %89, %90, %91, %92, %93, %94, %95, "
    "%96, %97, %98, %99, %100, %101, %102, %103, %104, %105, %106, %107, %108, %109, %110, %111, "
    "%112, %113, %114, %115, %116, %117, %118, %119, %120, %121, %122, %123, %124, %125, %126, %127}, "
    "%128, %129, p, 1, 1, 0, 1;\n}\n"
    : "+f"(d[0]), "+f"(d[1]), "+f"(d[2]), "+f"(d[3]), "+f"(d[4]), "+f"(d[5]), "+f"(d[6]), "+f"(d[7]),
      "+f"(d[8]), "+f"(d[9]), "+f"(d[10]), "+f"(d[11]), "+f"(d[12]), "+f"(d[13]), "+f"(d[14]), "+f"(d[15]),
      "+f"(d[16]), "+f"(d[17]), "+f"(d[18]), "+f"(d[19]), "+f"(d[20]), "+f"(d[21]), "+f"(d[22]), "+f"(d[23]),
      "+f"(d[24]), "+f"(d[25]), "+f"(d[26]), "+f"(d[27]), "+f"(d[28]), "+f"(d[29]), "+f"(d[30]), "+f"(d[31]),
      "+f"(d[32]), "+f"(d[33]), "+f"(d[34]), "+f"(d[35]), "+f"(d[36]), "+f"(d[37]), "+f"(d[38]), "+f"(d[39]),
      "+f"(d[40]), "+f"(d[41]), "+f"(d[42]), "+f"(d[43]), "+f"(d[44]), "+f"(d[45]), "+f"(d[46]), "+f"(d[47]),
      "+f"(d[48]), "+f"(d[49]), "+f"(d[50]), "+f"(d[51]), "+f"(d[52]), "+f"(d[53]), "+f"(d[54]), "+f"(d[55]),
      "+f"(d[56]), "+f"(d[57]), "+f"(d[58]), "+f"(d[59]), "+f"(d[60]), "+f"(d[61]), "+f"(d[62]), "+f"(d[63]),
      "+f"(d[64]), "+f"(d[65]), "+f"(d[66]), "+f"(d[67]), "+f"(d[68]), "+f"(d[69]), "+f"(d[70]), "+f"(d[71]),
      "+f"(d[72]), "+f"(d[73]), "+f"(d[74]), "+f"(d[75]), "+f"(d[76]), "+f"(d[77]), "+f"(d[78]), "+f"(d[79]),
      "+f"(d[80]), "+f"(d[81]), "+f"(d[82]), "+f"(d[83]), "+f"(d[84]), "+f"(d[85]), "+f"(d[86]), "+f"(d[87]),
      "+f"(d[88]), "+f"(d[89]), "+f"(d[90]), "+f"(d[91]), "+f"(d[92]), "+f"(d[93]), "+f"(d[94]), "+f"(d[95]),
      "+f"(d[96]), "+f"(d[97]), "+f"(d[98]), "+f"(d[99]), "+f"(d[100]), "+f"(d[101]), "+f"(d[102]), "+f"(d[103]),
      "+f"(d[104]), "+f"(d[105]), "+f"(d[106]), "+f"(d[107]), "+f"(d[108]), "+f"(d[109]), "+f"(d[110]), "+f"(d[111]),
      "+f"(d[112]), "+f"(d[113]), "+f"(d[114]), "+f"(d[115]), "+f"(d[116]), "+f"(d[117]), "+f"(d[118]), "+f"(d[119]),
      "+f"(d[120]), "+f"(d[121]), "+f"(d[122]), "+f"(d[123]), "+f"(d[124]), "+f"(d[125]), "+f"(d[126]), "+f"(d[127])
    : "l"(da), "l"(db), "r"(scale_d));
}
__device__ __forceinline__ void wgmma_rs_n128(float (&d)[64], const uint32_t* a, uint64_t db, int scale_d) {
  asm volatile("{\n.reg .pred p;\nsetp.ne.b32 p, %69, 0;\n"
    "wgmma.mma_async.sync.aligned.m64n128k16.f32.bf16.bf16 "
    "{%0, %1, %2, %3, %4, %5, %6, %7, %8, %9, %10, %11, %12, %13, %14, %15, "
    "%16, %17, %18, %19, %20, %21, %22, %23, %24, %25, %26, %27, %28, %29, %30, %31, "
    "%32, %33, %34, %35, %36, %37, %38, %39, %40, %41, %42, %43, %44, %45, %46, %47, "
    "%48, %49, %50, %51, %52, %53, %54, %55, %56, %57, %58, %59, %60, %61, %62, %63}, "
    "{%64, %65, %66, %67}, %68, p, 1, 1, 1;\n}\n"
    : "+f"(d[0]), "+f"(d[1]), "+f"(d[2]), "+f"(d[3]), "+f"(d[4]), "+f"(d[5]), "+f"(d[6]), "+f"(d[7]),
      "+f"(d[8]), "+f"(d[9]), "+f"(d[10]), "+f"(d[11]), "+f"(d[12]), "+f"(d[13]), "+f"(d[14]), "+f"(d[15]),
      "+f"(d[16]), "+f"(d[17]), "+f"(d[18]), "+f"(d[19]), "+f"(d[20]), "+f"(d[21]), "+f"(d[22]), "+f"(d[23]),
      "+f"(d[24]), "+f"(d[25]), "+f"(d[26]), "+f"(d[27]), "+f"(d[28]), "+f"(d[29]), "+f"(d[30]), "+f"(d[31]),
      "+f"(d[32]), "+f"(d[33]), "+f"(d[34]), "+f"(d[35]), "+f"(d[36]), "+f"(d[37]), "+f"(d[38]), "+f"(d[39]),
      "+f"(d[40]), "+f"(d[41]), "+f"(d[42]), "+f"(d[43]), "+f"(d[44]), "+f"(d[45]), "+f"(d[46]), "+f"(d[47]),
      "+f"(d[48]), "+f"(d[49]), "+f"(d[50]), "+f"(d[51]), "+f"(d[52]), "+f"(d[53]), "+f"(d[54]), "+f"(d[55]),
      "+f"(d[56]), "+f"(d[57]), "+f"(d[58]), "+f"(d[59]), "+f"(d[60]), "+f"(d[61]), "+f"(d[62]), "+f"(d[63])
    : "r"(a[0]), "r"(a[1]), "r"(a[2]), "r"(a[3]), "l"(db), "r"(scale_d));
}

template <int BN> __device__ __forceinline__ void wgmma(float (&d)[BN / 2], uint64_t a, uint64_t b, int s) {
  if constexpr (BN == 128) wgmma_n128(d, a, b, s);
  else wgmma_n256(d, a, b, s);
}

template <int N> __device__ __forceinline__ void acc_fence(float* a) {
#pragma unroll
  for (int i = 0; i < N; i++) asm volatile("" : "+f"(a[i]) :: "memory");
}

#define SELECT8(a, f) do { \
  if ((a) & 4) { if ((a) & 2) { if ((a) & 1) f(7); else f(6); } else { if ((a) & 1) f(5); else f(4); } } \
  else { if ((a) & 2) { if ((a) & 1) f(3); else f(2); } else { if ((a) & 1) f(1); else f(0); } } } while (0)
__device__ __forceinline__ uint32_t lane_now() { uint32_t l; asm volatile("mov.u32 %0, %%laneid;" : "=r"(l)); return l; }

struct Prod {
  uint32_t sb, n, tail, addr, pat, ready;
  uint32_t rank, flip; uint16_t mask;
  __device__ __forceinline__ void load_b(uint32_t dst, uint32_t half, const CUtensorMap* m, uint32_t mstep, uint32_t fb, int k, int ch, int cstep) {
    uint32_t h = rank;
    do { tma_ld3_mc(dst + h * half, ptr_add(m, h * mstep), fb, 0, k * 64, ch + h * cstep, mask); h ^= flip; } while (h != rank);
  }
  __device__ __forceinline__ void load_wide(const Params& P, int ffn, uint32_t dst, uint32_t fb, int k, int ch) {
    load_b(dst, PAGE, &P.map[ffn ? M_W1 : M_WKV], ffn ? 128 : 0, fb, k, ffn ? ch : ch + 16, ffn ? 0 : 16);
  }
  __device__ __forceinline__ void load_narrow(const Params& P, int ffn, uint32_t dst, uint32_t fb, int k, int j) {
    load_b(dst, 8192, &P.map[ffn ? M_W1H : M_WQ], ffn ? 128 : 0, fb, k, ffn ? 48 + j : 2 * j, ffn ? 0 : 1);
  }
  __device__ __forceinline__ void finish() {
#pragma unroll 1
    for (; tail < n; tail++) mbar_wait(sb + BAR_EMPTY + ((tail & 7) << 3), (tail >> 3) & 1);
  }
  template <int PAGES> __device__ __forceinline__ uint32_t acquire(uint32_t& fb) {
    uint32_t nw = pat & 3; pat = (pat >> 2) | 0x40000000u;
#pragma unroll 1
    for (; nw; nw--) { mbar_wait(sb + BAR_EMPTY + ((tail & 7) << 3), (tail >> 3) & 1); tail++; }
    ST(4, n);
    fb = sb + BAR_FULL + ((n & 7) << 3);
    mbar_expect_tx(fb, PAGES * PAGE);
    const uint32_t a = sb + addr;
    addr += PAGES * PAGE; if (addr >= NPAGE * PAGE) addr = 0;
    n++;
    return a;
  }
  const uint32_t* flag; uint32_t base, seen;
  __device__ __forceinline__ void acquire_fence() { asm volatile("fence.acquire.gpu;" ::: "memory"); fence_async_global(); }
  __device__ __forceinline__ void next() {
    uint32_t v, spins = 0;
    seen++;
    do { asm volatile("ld.acquire.cta.shared.u32 %0, [%1];" : "=r"(v) : "r"(sb + SM_SEEN) : "memory"); spin_check(++spins >> 4); } while (v < seen);
    fence_async_global();
  }
  __device__ __forceinline__ void need(uint32_t mask) {
    if ((ready & mask) != mask) {
      uint32_t spins = 0;
      do { ready = ld_relaxed(flag) - base; spin_check(++spins); } while ((ready & mask) != mask);
      acquire_fence();
    }
    ST(5, n - 1);
  }
};

struct Cons {
  uint32_t sb, n, off, prev;
  uint32_t ebar;
  uint32_t da0, db0;
  int lane;
  template <int PAGES> __device__ __forceinline__ void advance() {
    n++; off += PAGES << 10; if (off >= (NPAGE << 10)) off = 0;
    asm volatile("" : "+r"(n), "+r"(off));
  }
  template <int BN, int PAGES> __device__ __forceinline__ void step_ab(float (&acc)[BN / 2], uint32_t da, uint32_t db, int accumulate) {
    STA();
    mbar_wait_fast(sb + BAR_FULL + ((n & 7) << 3), (n >> 3) & 1);
    STB(n);
    const uint64_t da64 = desc64(da), db64 = desc64(db);
    wgmma_fence();
#pragma unroll
    for (int k = 0; k < 4; k++) wgmma<BN>(acc, da64 + 2 * k, db64 + 128 * k, k ? 1 : accumulate);
    wgmma_commit();
    wgmma_wait<1>();
    if (prev && lane < 2) mbar_arrive_cluster(ebar + prev);
    prev = 64 + ((n & 7) << 3);
    advance<PAGES>();
  }
  template <int BN> __device__ __forceinline__ void step(float (&acc)[BN / 2], int accumulate = 1) { step_ab<BN, BN / 128 + 1>(acc, da0 + off, db0 + 1024 + off, accumulate); }
  template <int BN> __device__ __forceinline__ void step_own(float (&acc)[BN / 2], uint32_t da, int accumulate) { step_ab<BN, BN / 128>(acc, da, db0 + off, accumulate); }
  __device__ __forceinline__ void wait_full(uint32_t i) { mbar_wait_fast(sb + BAR_FULL + (((n + i) & 7) << 3), ((n + i) >> 3) & 1); }
  __device__ __forceinline__ void issue_rs(float (&acc)[64], uint32_t (&a)[16], int second, int accumulate) {
    if (!second) { STA(); STB(n); }
    const uint64_t db64 = desc64(db0 + off) + 1024 * second;
    wgmma_fence();
#pragma unroll
    for (int k = 0; k < 4; k++) wgmma_rs_n128(acc, a + 4 * k, db64 + 128 * k, k ? 1 : accumulate);
    if (second) {
      wgmma_commit();
      prev = 64 + ((n & 7) << 3);
      advance<2>();
    }
  }
  template <int BN> __device__ __forceinline__ void steps(float (&acc)[BN / 2], int cnt) {
#pragma unroll 1
    do { step<BN>(acc); } while (--cnt > 0);
  }
  __device__ __forceinline__ void steps_skip(float (&acc)[64], int at) {
    int i = 0;
#pragma unroll 1
    do { if (i == at) off += 2 << 10; step<128>(acc); } while (++i < 2);
  }
  __device__ __forceinline__ void drain() {
    wgmma_wait<0>();
    if (lane < 2) mbar_arrive_cluster(ebar + prev);
    prev = 0;
  }
};

#define MAPPING 2
__device__ __forceinline__ uint32_t role_of_sm(uint32_t smid) {
  const uint32_t t = smid >> 1;
  uint32_t q, i;
  if (t < 32) { q = t & 7; i = t >> 3; }
  else if (t < 60) { const uint32_t u = t - 32, d = (u * 37) >> 8; q = 1 + u - d * 7; i = 4 + d; }
  else if (t < 62) return 128 + smid - 120;
  else { q = 0; i = t - 58; }
  return (q * 2 + (smid & 1)) * 8 + i;
}

template <typename T> __device__ __forceinline__ T* scratch(const Params& P, uint32_t off) { return (T*)ptr_add(P.scratch, off); }
__device__ __forceinline__ uint32_t* epoch_ptr(const Params& P) { uint32_t b; asm volatile("mov.u32 %0, %%ctaid.x;" : "=r"(b)); return scratch<uint32_t>(P, G_EPOCH + b * 4u); }

__device__ __forceinline__ int o_chunk(int s, int j) { const int hf = s >= 9, m = s - 2 - 7 * hf; return s < 2 ? 2 * j + s : 2 * (m == j ? 7 : m) + hf; }

__global__ void __cluster_dims__(2, 1, 1) __launch_bounds__(384, 1) fused_kernel(const __grid_constant__ Params P) {
  extern __shared__ __align__(1024) uint8_t smem_raw[];
  SP(0);
  const uint32_t sb = __shfl_sync(0xffffffffu, smem_u32(smem_raw), 0);
  const int warp = __shfl_sync(0xffffffffu, threadIdx.x >> 5, 0);
  const int lane = threadIdx.x & 31;
  if (warp == 7 && elect_one()) { prefetch_map(&P.map[M_XIN64]); prefetch_map(&P.map[M_WKV]); prefetch_map(&P.map[M_XIN]); }
  uint32_t role = blockIdx.x < 128 ? ((blockIdx.x >> 4) * 2 + (blockIdx.x & 1)) * 8 + ((blockIdx.x >> 1) & 7) : blockIdx.x;
  if (P.use_smid) { uint32_t smid; asm volatile("mov.u32 %0, %%smid;" : "=r"(smid)); role = role_of_sm(smid); }
  const bool spare = role >= 128;
  const int g = role >> 3, j = role & 7;
  uint32_t rank; asm("mov.u32 %0, %%cluster_ctarank;" : "=r"(rank));
  auto shared_b = [&]() {
    uint32_t peer;
    asm volatile("ld.shared::cluster.u32 %0, [%1];" : "=r"(peer) : "r"(mapa(sb + SM_ROLE, rank ^ 1)) : "memory");
    return !spare && peer < 128 && (peer & 7) == (uint32_t)j;
  };
  SP(1);

  if (warp >= 8) {
    asm volatile("setmaxnreg.dec.sync.aligned.u32 40;");
    if (elect_one()) {
      if (warp == 8) {
#pragma unroll
        for (int i = 0; i < 6; i++) mbar_init(sb + BAR_FULL + 8 * i, 1);
        mbar_init(sb + BAR_XIN, 1); mbar_init(sb + BAR_XIN + 8, 1);
      } else if (warp == 9) {
#pragma unroll
        for (int i = 0; i < 8; i++) mbar_init(sb + BAR_EMPTY + 8 * i, 16);
      } else if (warp == 10) {
#pragma unroll
        for (int i = 0; i < 4; i++) mbar_init(sb + BAR_SFULL + 8 * i, 4);
        mbar_init(sb + BAR_CLR, 1); mbar_init(sb + BAR_FULL + 48, 1); mbar_init(sb + BAR_FULL + 56, 1);
      } else {
        sts128(sb + SM_ROLE, role, 0, 0, 0);
        mbar_init(sb + BAR_TAG, 1); mbar_init(sb + BAR_XFULL, 8); mbar_init(sb + BAR_CSE, 8);
        mbar_init(sb + BAR_SEMPTY, 1); mbar_init(sb + BAR_CSF, 1); mbar_init(sb + BAR_CSF + 8, 2);
      }
      asm volatile("fence.mbarrier_init.release.cluster;\nfence.release.sync_restrict::shared::cta.cluster;" ::: "memory");
      fence_async_smem();
    }
    __syncwarp();
    SP(2);
    asm volatile("barrier.cluster.arrive.relaxed.aligned;" ::: "memory");
    if (warp == 8 && !spare) {
      if (elect_one()) {
        const int par = g & 1, row = (g >> 1) * 128;
#pragma unroll 1
        for (int s = 0; s < 2; s++) {
          const uint32_t xb = sb + BAR_XIN + 8 * s, fb = sb + BAR_FULL + 8 * s;
          mbar_expect_tx(xb, PAGE); mbar_expect_tx(fb, 2 * PAGE);
#pragma unroll
          for (int h = 0; h < 2; h++) tma_ld3(sb + SM_STAGE + h * PAGE + s * 8192, &P.map[M_XIN64], xb, s * 64, par, row + h * 64);
#pragma unroll
          for (int h = 0; h < 2; h++) tma_ld3(sb + (2 * s + h) * PAGE, &P.map[M_WKV], fb, 0, s * 64, 16 + 16 * h + 2 * j);
        }
#pragma unroll 1
        for (int s = 0; s < 2; s++) {
          const uint32_t fb = sb + BAR_FULL + 16 + 8 * s;
          mbar_expect_tx(fb, PAGE);
          tma_ld3(sb + (4 + s) * PAGE, &P.map[M_WKV], fb, 0, s * 64, 2 * j);
        }
#pragma unroll 1
        for (int s = 0; s < 2; s++) {
          const uint32_t fb = sb + BAR_FULL + 32 + 8 * s, a = sb + (6 + 3 * s) * PAGE;
          const int k = (j == 1 ? 4 : 2) + s;
          mbar_expect_tx(fb, 3 * PAGE);
          tma_ld3(a, &P.map[M_XIN], fb, k * 64, par, row);
#pragma unroll
          for (int h = 0; h < 2; h++) tma_ld3(a + PAGE + h * PAGE, &P.map[M_WKV], fb, 0, k * 64, 16 + 16 * h + 2 * j);
        }
        spin_check((sb & 1023) << 22);
      }
      __syncwarp();
    }
    SP(3);
    asm volatile("barrier.cluster.wait.acquire.aligned;" ::: "memory");
    SP(4);
    if (warp == 8) {
      if (elect_one()) {
        Prod p; p.sb = sb; p.n = 0; p.tail = 0; p.ready = 0; p.addr = 0;
        { const bool mc = shared_b(); p.rank = rank; p.flip = !mc; p.mask = mc ? 3 : 1 << rank; }
        uint32_t fb;
        if (spare) {
          p.pat = 0x55555000u;
#pragma unroll 1
          for (int r = -1; r < 7; r++) {
            const int ch = r < 0 ? 4 * j : ((r < 2 ? r : r == 2 ? 6 : r - 1) * 4 + j) * 2;
#pragma unroll 1
            for (int k = 0; k < 16; k++) { const uint32_t a = p.acquire<2>(fb); p.load_b(a, PAGE, &P.map[r < 0 ? M_WKV : M_W1], r < 0 ? 0 : 128, fb, k, ch, r < 0 ? 2 : 0); }
          }
        } else {
          p.seen = 0;
          const int xpar = g & 1, xrow = (g >> 1) * 128;
          SP(5);
#pragma unroll 1
          for (int hl = 0; hl < 4; hl++) {
            const int ffn = hl & 1;
            const CUtensorMap* xmap = &P.map[hl ? M_OUT_LD : M_XIN];
            if (hl) {
              p.pat = ffn ? Pat<3>::v : Pat<8>::v;
#pragma unroll 1
              for (int s = 0; s < 2; s++) { const uint32_t a = p.acquire<2>(fb); p.load_wide(P, ffn, a, fb, 2 * j + s, 2 * j); }
#pragma unroll 1
              for (int s = 0; s < 2; s++) { const uint32_t a = p.acquire<1>(fb); p.load_narrow(P, ffn, a, fb, 2 * j + s, j); }
            } else { p.pat = (Pat<0>::v >> 12) | 0x55500000u; p.addr = 0; p.n = 6; }
            if (hl == 0) SP(6);
            uint32_t fb0 = 0;
#pragma unroll 1
            for (int m = hl ? 0 : 2; m < 14; m++) {
              const int hf = m >= 7, mm = m - 7 * hf, jj = mm == j ? 7 : mm;
              int k = 2 * jj + hf;
              if (hl == 0) {
                const int pr = (m >> 1) + 1;
                k = 2 * (j && pr == 2 ? j : pr == j ? 2 : pr) + (m & 1);
              }
              const uint32_t a = p.acquire<3>(fb);
              p.load_wide(P, ffn, a + PAGE, fb, k, 2 * j);
              if (hl) {
                if (m == 0) { fb0 = fb; continue; }
                if (m == 1) {
                  const int j0 = j ? 0 : 7;
                  p.flag = scratch<uint32_t>(P, g * G_BLOCK + G_FLAGS + (ffn ? (hl >> 1) * EV_N + EV_XA : EV_XB) * 128);
                  p.ready = 0; p.need((1u << j0) | (1u << j));
                  tma_ld3(a - 3 * PAGE, xmap, fb0, j0 * 128, xpar, xrow);
                }
                if (m < 7) p.need(1u << jj); else if (m == 7) p.next();
              }
              tma_ld3(a, xmap, fb, k * 64, xpar, xrow);
            }
            if (hl == 0) { mbar_wait(sb + BAR_TAG, 0); asm volatile("ld.shared.u32 %0, [%1];" : "=r"(p.base) : "r"(sb + SM_TAG) : "memory"); p.base = (p.base - 1) * 255; }
            p.pat = ffn ? Pat<4>::v : Pat<1>::v;
#pragma unroll 1
            for (int m = 0; m < 14; m++) {
              const int k = (m >> 1) == (hl ? j : 0) ? 14 + (m & 1) : m;
              if (ffn && m == 8) p.addr += 2 * PAGE;
              const uint32_t a = p.acquire<2>(fb);
              p.load_narrow(P, ffn, a + PAGE, fb, k, j);
              tma_ld3(a, xmap, fb, k * 64, xpar, xrow);
            }
            if (!ffn) {
              p.pat = Pat<2>::v;
              uint32_t a = 0;
#pragma unroll 1
              for (int s = 0; s < 16; s++) {
                if (!(s & 1)) a = p.acquire<2>(fb); else a += PAGE;
                p.load_b(a, 8192, &P.map[M_WO], 0, fb, o_chunk(s, j), 2 * j, 1);
              }
              p.addr += 2 * PAGE;
              a = p.acquire<2>(fb);
              tma_ld3(a, xmap, fb, j * 128, xpar, xrow); tma_ld3(a + PAGE, xmap, fb, j * 128 + 64, xpar, xrow);
            } else {
              p.pat = Pat<5>::v;
#pragma unroll 1
              for (int s = 16; s < 48; s++) {
                const int pi = (s >> 1) & 7;
                const int k = (s < 32 ? pi : pi == 4 ? j : pi == j ? 4 : pi) * 2 + (s & 1);
                const uint32_t a = p.acquire<3>(fb);
                p.load_wide(P, 1, a + PAGE, fb, k, (s & 48) + 2 * j);
                tma_ld3(a, xmap, fb, k * 64, xpar, xrow);
              }
              p.pat = Pat<6>::v;
#pragma unroll 1
              for (int q = 0; q < 4; q++) {
                p.next();
                const int k0 = q == 0 ? 0 : q == 1 ? 48 : q * 16 - 16, k1 = k0 + (q == 1 ? 8 : 16);
#pragma unroll 1
                for (int k = k0; k < k1; k++) {
                  if (k == 24) { p.addr = 0; p.pat = Pat<7>::v; }
                  const uint32_t a = p.acquire<2>(fb);
                  p.load_b(a + PAGE, 8192, &P.map[M_W2], 0, fb, k, 2 * j, 1);
                  tma_ld3(a, &P.map[M_H_LD], fb, k * 64, g, 0);
                }
              }
            }
            TL(2, 1 + hl);
          }
        }
        p.finish();
      }
    } else if (!spare) {
      mbar_wait(sb + BAR_XIN, 0);
      if (elect_one()) {
#pragma unroll 1
        for (int i = warp - 9; i < 8; i += 3) prefetch_l2(ptr_add(P.wqkv, (i * 128 + role) * 6144u + 2048u), 4096);
      }
      uint32_t tag;
      {
        const uint32_t part = warp - 9, col = DM + role * 16 + (lane & 1) * 8;
        const int cnt = part ? 21 : 22;
        const uint4* wp = ptr_add((const uint4*)P.wqkv, ((part ? 16 + part * 336 : 0) + (lane >> 1)) * 6144u + col * 2);
        float s[8] = {0, 0, 0, 0, 0, 0, 0, 0};
        uint4 v[4];
#pragma unroll
        for (int i = 0; i < 4; i++) v[i] = ld_relaxed4(wp + i * (16 * 6144 / 16));
        tag = ld_relaxed(epoch_ptr(P)) + 1;
        if (warp == 10 && lane == 0) { asm volatile("st.shared.u32 [%0], %1;" :: "r"(sb + SM_TAG), "r"(tag) : "memory"); mbar_arrive(sb + BAR_TAG); }
#pragma unroll 1
        for (int b = 4; b < 28; b += 4) {
          wp += 64 * 6144 / 16;
#pragma unroll
          for (int i = 0; i < 4; i++) {
            s[0] += bf_lo(v[i].x); s[1] += bf_hi(v[i].x); s[2] += bf_lo(v[i].y); s[3] += bf_hi(v[i].y);
            s[4] += bf_lo(v[i].z); s[5] += bf_hi(v[i].z); s[6] += bf_lo(v[i].w); s[7] += bf_hi(v[i].w);
            v[i] = make_uint4(0, 0, 0, 0);
            if (b + i < cnt) v[i] = __ldcg(wp + i * (16 * 6144 / 16));
          }
        }
#pragma unroll
        for (int e = 0; e < 4; e++) { const bool h = lane & 16; const float t = __shfl_xor_sync(0xffffffffu, h ? s[e] : s[e + 4], 16); s[e] = (h ? s[e + 4] : s[e]) + t; }
#pragma unroll
        for (int e = 0; e < 2; e++) { const bool h = lane & 8; const float t = __shfl_xor_sync(0xffffffffu, h ? s[e] : s[e + 2], 8); s[e] = (h ? s[e + 2] : s[e]) + t; }
        { const bool h = lane & 4; const float t = __shfl_xor_sync(0xffffffffu, h ? s[0] : s[1], 4); s[0] = (h ? s[1] : s[0]) + t; }
        s[0] += __shfl_xor_sync(0xffffffffu, s[0], 2);
        if (!(lane & 2) || part == 0) st_relaxed(scratch<uint32_t>(P, G_CS + (col + (lane >> 2)) * 16 + ((lane & 2) ? 3 : part) * 4), tagf((lane & 2) ? 0.f : s[0], tag));
        __syncwarp();
      }
      if (warp == 11 && lane == 0) TL(2, 30);
      {
        const uint32_t cspos = sb + SM_CS + ((lane & 16) + ((lane >> 1) & 3) * 4 + ((lane >> 3) & 1) * 2 + (lane & 1)) * 4;
#pragma unroll 1
        for (int it = 0; it < (warp == 10 ? 8 : 1); it++) {
          const int t = it & 3;
          if (it) mbar_wait(sb + BAR_CSE, (it - 1) & 1);
          if (t == 1) mbar_wait(sb + BAR_SEMPTY, 0);
#pragma unroll 1
          for (int b = it ? 0 : warp - 9; b < (it == 0 ? warp - 8 : t < 2 ? 3 : 2); b++) {
            uint32_t c0, c1;
            if (b < 2) { c0 = (t ? 2048 + t * 1024 + b * FF : 1024 + b * 1024) + j * 128; c1 = c0 + 64; }
            else if (t) { c0 = 6144 + j * 64; c1 = c0 + FF; }
            else { c0 = j * 128; c1 = c0 + 64; }
            const uint4* p0 = scratch<uint4>(P, G_CS + (c0 + lane) * 16u);
            const uint4* p1 = scratch<uint4>(P, G_CS + (c1 + lane) * 16u);
            uint4 v[4]; uint32_t spins = 0; bool ok;
            do {
              if (spins) __nanosleep(200);
              v[0] = ld_relaxed4(p0); v[1] = ld_relaxed4(p0 + 32); v[2] = ld_relaxed4(p1); v[3] = ld_relaxed4(p1 + 32);
              ok = tag_ok4(v[0], tag) && tag_ok4(v[1], tag) && tag_ok4(v[2], tag) && tag_ok4(v[3], tag);
              spin_check(++spins);
            } while (__any_sync(0xffffffffu, !ok));
#pragma unroll
            for (int m = 0; m < 4; m++) sts32f(cspos + b * 512 + m * 128, (untag(v[m].x) + untag(v[m].y)) + (untag(v[m].z) + untag(v[m].w)));
            __syncwarp();
            if (lane == 0) mbar_arrive(sb + BAR_CSF + (b ? 8 : 0));
          }
          if (lane == 0) { if (t >= 2) mbar_arrive(sb + BAR_CSF + 8); TL(2, 16 + it + (warp == 11 ? 8 : warp == 9 ? 9 : 0)); }
          if (t == 3) {
            if (g >= 2) {
              uint4* op = scratch<uint4>(P, G_HALO + (((it >> 2) * 16 + g - 2) * 8 + j) * 4096u + lane * 16u);
#pragma unroll 1
              for (int i = 0; i < 8; i++) { st_b128(op, 0, 0, 0, 0); op += 32; }
            }
          }
        }
      }
      if (warp == 11) {
        if (elect_one()) prefetch_l2(ptr_add(P.wo, role * 16384u), 16384);
        uint32_t* const fl = scratch<uint32_t>(P, g * G_BLOCK + G_FLAGS);
        uint32_t seen = 0;
#pragma unroll 1
        for (int e = EV_XA; e < EV_N + EV_XB; e++) {
          if (e == EV_XB) continue;
          const bool clr = (e & 7) == EV_XA;
          uint32_t* const f = ptr_add(fl, (clr ? 16 + e : e) * 128u);
          if (clr) {
            uint4* op = scratch<uint4>(P, g * G_BLOCK + G_O + j * 32768u + lane * 16u);
#pragma unroll 1
            for (int i = 0; i < 64; i++) { st_b128(op, 0, 0, 0, 0); op += 32; if (e || (i & 1)) __nanosleep(10); }
            __syncwarp();
            if (lane == 0) red_release(f, 1u << j);
          }
          uint32_t spins = 0, m;
          while ((m = ld_relaxed(f) - (tag - 1) * 255) != 255) { __nanosleep(m ? 50 : 500); spin_check(++spins); }
          asm volatile("fence.acquire.gpu;" ::: "memory");
          if (lane == 0) {
            if (clr) mbar_arrive(sb + BAR_CLR);
            else asm volatile("st.release.cta.shared.u32 [%0], %1;" :: "r"(sb + SM_SEEN), "r"(++seen) : "memory");
          }
          if (e == EV_H3) {
#pragma unroll 1
            for (int i = 0; i < 7; i++) { if (elect_one()) prefetch_l2(ptr_add(P.w2, (i * 128 + role) * 8192u), 8192); __nanosleep(500); }
          }
          __syncwarp();
        }
      } else if (warp == 9) {
        if (elect_one()) {
          prefetch_map(&P.map[M_WQ]); prefetch_map(&P.map[M_OUT_LD]); prefetch_map(&P.map[M_WO]); prefetch_map(&P.map[M_W1 + rank]);
          prefetch_map(&P.map[M_H_ST]); prefetch_map(&P.map[M_H_LD]); prefetch_map(&P.map[M_W1H + rank]); prefetch_map(&P.map[M_W2]); prefetch_map(&P.map[M_OUT_ST]);
          uint32_t* fl = scratch<uint32_t>(P, g * G_BLOCK + G_FLAGS);
          int pe = 0;
#pragma unroll 1
          for (int e = 0; e < 2 * EV_N; e++) {
            const int q = e & 7;
            const bool is_h = q >= EV_H0 && q < EV_XB, last = e >= EV_N + EV_XB;
            const CUtensorMap* map = &P.map[is_h ? M_H_ST : M_OUT_ST];
            const int col = q == EV_H3 ? 3072 - 64 + j * 64 : (q == EV_H1 ? 1024 : q == EV_H2 ? 2048 : 0) + j * 128;
            const int row = is_h ? 0 : (g >> 1) * 128, par = is_h ? g : g & 1;
#pragma unroll 1
            for (int hb = is_h ? q == EV_H3 : q & 1; hb <= (is_h ? 1 : q & 1); hb++) {
#pragma unroll
              for (int w = 0; w < 2; w++) {
                const bool sw = last;
                const int wg = sw ? hb : w, h = sw ? w : hb, p = sw ? pe - hb + w : pe;
                mbar_wait(sb + BAR_SFULL + 16 * wg + 8 * (p & 1), (p >> 1) & 1);
                if (w == 0) TL(3, 20 + e);
                tma_st3(map, sb + SM_STAGE + wg * PAGE + h * 8192, col + h * 64, par, row + wg * 64);
              }
              pe++;
            }
            bulk_commit();
            if (e != EV_N + EV_XB) bulk_wait<0>();
            TL(3, 40 + e);
            if (is_h || (q & 1)) mbar_arrive(sb + BAR_SEMPTY);
            if (!last) red_release(fl, 1u << j);
            TL(3, e);
            fl += 32;
          }
          *epoch_ptr(P) = tag;
        }
      }
    }
  } else {
    if (!spare) {
      if (warp == 0) asm volatile("prefetch.global.L2 [%0];" :: "l"(ptr_add(P.x, (2 * ((g >> 1) * 128 + j * 16 + (lane >> 1)) + (g & 1)) * 2048u + (lane & 1) * 128u)));
      else if (warp < 3 && (warp == 1 || lane < 16)) asm volatile("prefetch.global.L2 [%0];" :: "l"(ptr_add(P.wqkv, role * 6144u + (warp - 1) * 4096u + lane * 128u)));
      __syncwarp();
    }
    asm volatile("barrier.cluster.arrive.relaxed.aligned;" ::: "memory");
    asm volatile("setmaxnreg.inc.sync.aligned.u32 232;");
    SP(4);
    asm volatile("barrier.cluster.wait.acquire.aligned;" ::: "memory");
    SP(5);
    const int wg = warp >> 2;
    const int quad = lane & 3, gr = lane >> 2;
    Cons c; c.sb = sb; c.n = 0; c.off = 0; c.prev = 0; c.lane = lane;
    c.ebar = mapa(sb + BAR_EMPTY - 64, shared_b() ? lane & 1 : rank);
    const uint32_t stage = sb + SM_STAGE + wg * PAGE;
    const uint32_t dstage = desc_lo(stage, 16);
    if (spare) {
      const uint32_t tag = ld_relaxed(epoch_ptr(P)) + 1;
      const int tid = threadIdx.x & 127;
#pragma unroll
      for (int i = 0; i < 4; i++) sts128(stage + (i * 128 + tid) * 16, 0x3f803f80u, 0x3f803f80u, 0x3f803f80u, 0x3f803f80u);
      fence_async_smem();
      bar_sync(2 + wg, 128);
      c.db0 = desc_lo(sb + wg * PAGE, 8192);
#pragma unroll 1
      for (int r = -1; r < 7; r++) {
        float acc[64];
#pragma unroll 1
        for (int k = 0; k < 16; k++) c.step_ab<128, 2>(acc, dstage, c.db0 + c.off, k);
        c.drain();
        acc_fence<64>(acc);
        {
          float v = 0;
#pragma unroll
          for (int i = 0; i < 32; i++) asm("{\n.reg .pred p;\nsetp.eq.u32 p, %2, %3;\nselp.f32 %0, %1, %0, p;\n}" : "+f"(v) : "f"(acc[4 * (i >> 1) + (i & 1)]), "r"(tid >> 2), "r"(i));
          st_b128(scratch<uint4>(P, G_CS + (uint32_t)((r < 0 ? j * 256 + wg * 128 : 3 * DM + wg * FF + ((r < 2 ? r : r == 2 ? 6 : r - 1) * 4 + j) * 128) + (tid >> 3) * 8 + quad * 2 + (gr & 1)) * 16u),
                  tagf(v, tag), tag & 15u, tag & 15u, tag & 15u);
        }
        __syncwarp();
      }
      if (wg == 0) {
        const uint32_t* p = scratch<uint32_t>(P, (tid >> 3) * G_BLOCK + G_STATS + (tid & 7) * 8u);
        uint32_t spins = 0;
        while (__any_sync(0xffffffffu, (ld_relaxed(p) ^ tag) & 15u)) spin_check(++spins);
      }
      bar_sync(1, 256);
      if (threadIdx.x == 0) *epoch_ptr(P) = tag;
    } else {
    c.da0 = desc_lo(sb + wg * 8192, 16); c.db0 = desc_lo(sb, 8192);
    uint32_t sphase = 1, sfull = sb + BAR_SFULL + 16 * wg;
    const uint32_t maddr = stage + ((warp & 3) * 16 + (lane & 15)) * 128 + (((lane >> 4) ^ (lane & 7)) << 4);
    const uint32_t csaddr = sb + SM_CS + quad * 16;
    float st[8] = {0, 0, 0, 0, 0, 0, 0, 0};
    float* const mean = st; float* const rstd = st + 2;
    SP(6);

    auto stage_wait = [&]() { mbar_wait_fast(sb + BAR_SEMPTY, sphase); sphase ^= 1; };
    auto stage_publish = [&]() { fence_async_smem(); __syncwarp(); if (lane == 0) mbar_arrive(sfull); sfull ^= 8; };
    auto cs_load = [&](uint32_t (&cs)[16], int grp) {
#pragma unroll
      for (int i = 0; i < 4; i++) lds128(csaddr + grp * 256 + i * 64, cs[4 * i], cs[4 * i + 1], cs[4 * i + 2], cs[4 * i + 3]);
    };
    auto cs_apply = [&](float* acc, uint32_t (&cs)[16]) {
      acc_fence<32>(acc);
#pragma unroll
      for (int b = 0; b < 8; b++) {
        acc[4 * b] -= mean[0] * __uint_as_float(cs[2 * b]); acc[4 * b + 1] -= mean[0] * __uint_as_float(cs[2 * b + 1]);
        acc[4 * b + 2] -= mean[1] * __uint_as_float(cs[2 * b]); acc[4 * b + 3] -= mean[1] * __uint_as_float(cs[2 * b + 1]);
      }
      acc_fence<32>(acc);
    };
    auto glu_pair = [&](float g0, float g1, float u0, float u1, int r) {
      const float nl = -LOG2E * rstd[r], r2 = rstd[r] * rstd[r];
      return pack_bf16(g0 * u0 * r2 * rcp(1.0f + ex2(g0 * nl)), g1 * u1 * r2 * rcp(1.0f + ex2(g1 * nl)));
    };
    auto glu_slice = [&](uint32_t (&pk)[64], int i) {
      uint32_t hp[4];
#pragma unroll
      for (int e = 0; e < 4; e++) {
        asm volatile("" : "+r"(pk[4 * i + e]), "+r"(pk[32 + 4 * i + e]));
        const uint32_t pg = pk[4 * i + e], pu = pk[32 + 4 * i + e];
        hp[e] = glu_pair(bf_lo(pg), bf_hi(pg), bf_lo(pu), bf_hi(pu), e & 1);
      }
      stsm4((maddr ^ ((i & 3) << 5)) + (i >> 2) * 8192, hp[0], hp[1], hp[2], hp[3]);
    };
    auto glu_slice_acc = [&](float (&acc)[128], int i) {
      uint32_t hp[4];
      acc_fence<8>(acc + 8 * i);
#pragma unroll
      for (int e = 0; e < 4; e++) hp[e] = glu_pair(acc[8 * i + 2 * e], acc[8 * i + 2 * e + 1], acc[64 + 8 * i + 2 * e], acc[64 + 8 * i + 2 * e + 1], e & 1);
      stsm4((maddr ^ ((i & 3) << 5)) + (i >> 2) * 8192, hp[0], hp[1], hp[2], hp[3]);
    };
    auto stage_x = [&](uint32_t (&x)[32], int hf) {
#pragma unroll
      for (int i = 4 * hf; i < 4 * hf + 4; i++) stsm4((maddr ^ ((i & 3) << 5)) + hf * 8192, x[4 * i], x[4 * i + 1], x[4 * i + 2], x[4 * i + 3]);
    };

    float acc[128];
    mbar_wait_fast(sb + BAR_XIN, 0);
    SP(7);
    c.step_own<256>(acc, dstage, 0);
    mbar_wait_fast(sb + BAR_XIN + 8, 0);
    SP(8);
#pragma unroll 1
    for (int hl = 0;; hl++) {
      int t = hl & 1;
      float acc2[64];
      uint32_t res[32];
      c.step_own<256>(acc, dstage + 512, 1);
#pragma unroll
      for (int s = 0; s < 2; s++) c.step_own<128>(acc2, dstage + s * 512, s);
#pragma unroll 1
      for (int s = 2; s < 11; s++) {
        const uint32_t apage = (c.off << 4) - (SM_STAGE + wg * 8192);
        c.step<256>(acc);
        int act = s;
        asm volatile("" : "+r"(act));
        auto get_tag = [&]() { uint32_t tag; asm volatile("ld.shared.u32 %0, [%1];" : "=r"(tag) : "r"(sb + SM_TAG) : "memory"); return tag; };
        auto stat_ptr = [&]() { return scratch<uint2>(P, g * G_BLOCK + G_STATS + (hl * 128 + warp * 16 + (lane_now() >> 2)) * 64u); };
        auto stat_get = [&]() {
          const uint2* sp = ptr_add(stat_ptr(), (lane_now() & 3) * 16);
          const uint4 a = ld_relaxed4(sp), b = ld_relaxed4(sp + 64);
          st[0] = __uint_as_float(a.x); st[1] = __uint_as_float(a.y); st[2] = __uint_as_float(a.z); st[3] = __uint_as_float(a.w);
          st[4] = __uint_as_float(b.x); st[5] = __uint_as_float(b.y); st[6] = __uint_as_float(b.z); st[7] = __uint_as_float(b.w);
        };
        switch (act) {
          case 4: case 5: {
            const uint32_t ra = maddr + ((hl || j == 0) ? (s & 1) * 8192 : apage);
#pragma unroll
            for (int i = 0; i < 4; i++) {
              uint32_t v[4];
              ldsm4(ra ^ (i << 5), v[0], v[1], v[2], v[3]);
              if (i == 0 && s == 4) { st[0] = bf_lo(v[0]); st[1] = bf_lo(v[1]); st[2] = st[3] = st[4] = st[5] = 0; }
#pragma unroll
              for (int e = 0; e < 4; e++) {
                const float a = bf_lo(v[e]) - st[e & 1], b = bf_hi(v[e]) - st[e & 1];
                st[2 + (e & 1)] += a + b; st[4 + (e & 1)] += a * a; st[4 + (e & 1)] += b * b;
              }
            }
          } break;
          case 6: {
            mbar_wait_fast(sb + BAR_TAG, 0);
            const uint32_t tag = get_tag();
#pragma unroll
            for (int r = 0; r < 2; r++) {
              const float mt = st[r] + st[2 + r] * (1.0f / 32);
              float m = mt + __shfl_xor_sync(0xffffffffu, mt, 1); m += __shfl_xor_sync(0xffffffffu, m, 2); m *= 0.25f;
              float q = st[4 + r] - st[2 + r] * st[2 + r] * (1.0f / 32) + 32.0f * (mt - m) * (mt - m);
              q += __shfl_xor_sync(0xffffffffu, q, 1); q += __shfl_xor_sync(0xffffffffu, q, 2);
              if (quad == 0) st_relaxed2(ptr_add(stat_ptr(), r * 512 + j * 8), tagf(m, tag), tagf(q, tag));
            }
          } break;
          case 8: stat_get(); break;
          case 10: {
            const uint32_t tag = get_tag();
            uint32_t spins = 0;
            for (;;) {
              uint32_t bad = 0;
#pragma unroll
              for (int i = 0; i < 8; i++) bad |= __float_as_uint(st[i]) ^ tag;
              if (!__any_sync(0xffffffffu, bad & 15u)) break;
              stat_get(); spin_check(++spins);
            }
            float mr[4];
#pragma unroll
            for (int r = 0; r < 2; r++) {
              const float m0 = untag(__float_as_uint(st[4 * r])), m1 = untag(__float_as_uint(st[4 * r + 2]));
              float m = m0 + m1; m += __shfl_xor_sync(0xffffffffu, m, 1); m += __shfl_xor_sync(0xffffffffu, m, 2); m *= 0.125f;
              float q = untag(__float_as_uint(st[4 * r + 1])) + untag(__float_as_uint(st[4 * r + 3])) + 128.0f * ((m0 - m) * (m0 - m) + (m1 - m) * (m1 - m));
              q += __shfl_xor_sync(0xffffffffu, q, 1); q += __shfl_xor_sync(0xffffffffu, q, 2);
              mr[r] = m; mr[2 + r] = rsqrtf(fmaxf(q, 0.f) * (1.0f / DM) + LN_EPS);
            }
            st[0] = mr[0]; st[1] = mr[1]; st[2] = mr[2]; st[3] = mr[3];
          } break;
          default: break;
        }
      }
#pragma unroll 1
      for (;;) {
      const int it = (hl >> 1) * 4 + t;
#pragma unroll
      for (int s = 0; s < 4; s++) {
        uint32_t cs[16];
        c.step<256>(acc);
        if (!(s & 1)) mbar_wait_fast(sb + BAR_CSF + 4 * s, t & 1);
        if (s >= 2 && t <= 1) { cs_load(cs, 2 + s); cs_apply(acc2 + 32 * (s - 2), cs); }
        cs_load(cs, s);
        c.drain();
        cs_apply(acc + 32 * s, cs);
      }
      c.step<256>(acc);
      if (lane == 0) mbar_arrive(sb + BAR_CSE);
      c.drain();
      acc_fence<128>(acc);
      TLC(1 + it * 6);
      uint32_t pkB[64];
      if (t == 2) {
#pragma unroll
        for (int i = 0; i < 64; i++) pkB[i] = pack_bf16(acc[2 * i], acc[2 * i + 1]);
      } else if (t == 0) {
        uint32_t pkA[64];
        auto kv_pack = [&](int v, int r) {
#pragma unroll
          for (int i = 32 * v + r; i < 32 * v + 32; i += 2) { acc_fence<2>(acc + 2 * i); pkA[i] = pack_bf16(acc[2 * i] * rstd[r], acc[2 * i + 1] * rstd[r]); }
        };
        const uint32_t l16 = lane_now() * 16u;
        uint4* const xs = ptr_add((uint4*)smem_raw, SM_STAGE + l16);
        uint4* const hp = scratch<uint4>(P, G_HALO + (((hl >> 1) * 16 + g) * 8 + j) * 4096u + l16);
        {
          uint4* const dst = (warp == 7 && g < 14) ? hp : ptr_add(xs, warp * 4096u);
#pragma unroll
          for (int s = 0; s < 2; s++) {
            c.steps<128>(acc2, s ? 2 : 1 + wg);
            if (s == 0) stage_wait();
            kv_pack(s, 1);
#pragma unroll
            for (int i = 4 * s; i < 4 * s + 4; i++) { pkA[8 * i + 1] = pkt_head(pkA[8 * i + 1]); gen_store(dst + i * 32, pkA[8 * i + 1], pkA[8 * i + 3], pkA[8 * i + 5], pkA[8 * i + 7]); }
          }
        }
        __syncwarp();
        if (lane == 0) mbar_arrive(sb + BAR_XFULL);
#pragma unroll
        for (int s = 0; s < 2; s++) {
          c.steps<128>(acc2, 2);
#pragma unroll
          for (int i = 33 - s; i < 64; i += 2) pkA[i] = movm(pkA[i]);
          kv_pack(1 - s, 0);
        }
        uint32_t kvH[32];
        {
          const uint4* const src = (warp == 0 && g >= 2) ? hp - 2 * 8 * 256 : ptr_add(xs, (warp ? warp - 1 : 0) * 4096u);
          c.steps<128>(acc2, 2);
          mbar_wait_fast(sb + BAR_XFULL, hl >> 1);
#pragma unroll
          for (int i = 0; i < 8; i++) gen_load(src + i * 32, kvH + 4 * i);
          c.steps<128>(acc2, 3 - wg);
          uint32_t spins = 0;
          while (__any_sync(0xffffffffu, !(kvH[0] && kvH[4] && kvH[8] && kvH[12] && kvH[16] && kvH[20] && kvH[24] && kvH[28]))) {
#pragma unroll
            for (int i = 0; i < 8; i++) gen_load(src + i * 32, kvH + 4 * i);
            spin_check(++spins);
          }
        }
#pragma unroll
        for (int i = 16; i < 32; i++) kvH[i] = movm(kvH[i]);
        mbar_wait_fast(sb + BAR_CLR, hl >> 1);
        c.steps<128>(acc2, 2);
        AP(0);
        c.wait_full(0);
        AP(1);
        c.drain();
        AP(2);
        acc_fence<64>(acc2);
        TLC(2 + it * 6);
        uint32_t q[32];
#pragma unroll
        for (int i = 0; i < 32; i++) q[i] = pack_bf16(acc2[2 * i], acc2[2 * i + 1]);
        const uint32_t zm = bar_sync_zero(1, 256);
        AP(3);
        uint32_t ob[4][16];
        uint4* const omail = scratch<uint4>(P, g * G_BLOCK + G_O + warp * 2048u + l16);
        auto o_fetch = [&](uint32_t (&v0)[16], uint32_t (&v1)[16], const uint4* p0, const uint4* p1) {
#pragma unroll
          for (int i = 0; i < 4; i++) pkt_load(p0 + i * 32, v0 + 4 * i);
#pragma unroll
          for (int i = 0; i < 4; i++) pkt_load(p1 + i * 32, v1 + 4 * i);
        };
        float o2[8][4], r2[4];
        {
          const float hv = (warp == 0 && g < 2) ? -INFINITY : 0.f;
          const float hinit[4] = {hv, hv, hv, hv};
          const bool c0 = (2 * quad <= gr), c1 = (2 * quad + 1 <= gr);
          const uint32_t lm = (c0 ? 0xffffu : 0u) | (c1 ? 0xffff0000u : 0u);
          const float sc[2] = {rstd[0] * (0.17677669529663687f * LOG2E), rstd[1] * (0.17677669529663687f * LOG2E)};
          float lg[4][4], mx[4][2];
#pragma unroll
          for (int h = 0; h < 4; h++) {
            const int b = h * 4;
            float sH[4], sL[4], sU[4];
            q[2 * b] |= zm;
            mma16816(sH, q[2 * b], q[2 * b + 1], q[2 * b + 2], q[2 * b + 3], kvH[b], kvH[b + 1], hinit);
            mma16816z(sL, q[2 * b], q[2 * b + 1], q[2 * b + 2], q[2 * b + 3], pkA[2 * b], pkA[2 * b + 2]);
            mma16816z(sU, q[2 * b], q[2 * b + 1], q[2 * b + 2], q[2 * b + 3], pkA[2 * b + 1], pkA[2 * b + 3]);
            mma16816(sH, q[2 * b + 4], q[2 * b + 5], q[2 * b + 6], q[2 * b + 7], kvH[b + 2], kvH[b + 3], sH);
            mma16816(sL, q[2 * b + 4], q[2 * b + 5], q[2 * b + 6], q[2 * b + 7], pkA[2 * b + 4], pkA[2 * b + 6], sL);
            mma16816(sU, q[2 * b + 4], q[2 * b + 5], q[2 * b + 6], q[2 * b + 7], pkA[2 * b + 5], pkA[2 * b + 7], sU);
            lg[h][0] = c0 ? sL[0] : sH[0]; lg[h][1] = c1 ? sL[1] : sH[1]; lg[h][2] = c0 ? sU[2] : sL[2]; lg[h][3] = c1 ? sU[3] : sL[3];
            mx[h][0] = fmaxf(lg[h][0], lg[h][1]); mx[h][1] = fmaxf(lg[h][2], lg[h][3]);
          }
#pragma unroll
          for (int o = 1; o < 4; o <<= 1) {
#pragma unroll
            for (int i = 0; i < 8; i++) mx[i >> 1][i & 1] = fmaxf(mx[i >> 1][i & 1], __shfl_xor_sync(0xffffffffu, mx[i >> 1][i & 1], o));
          }
          AP(4);
          uint32_t z = zm, pp[4][2];
          float rs[4][2];
          auto probs = [&](int h) {
            pp[h][0] = pack_bf16(ex2((lg[h][0] - mx[h][0]) * sc[0]), ex2((lg[h][1] - mx[h][0]) * sc[0]));
            pp[h][1] = pack_bf16(ex2((lg[h][2] - mx[h][1]) * sc[1]), ex2((lg[h][3] - mx[h][1]) * sc[1]));
            float sum[4];
            mma1688z(sum, pp[h][0], pp[h][1], 0x3f803f80u);
            rs[h][0] = rcp(sum[0]); rs[h][1] = rcp(sum[2]);
            asm volatile("" : "+f"(rs[h][0]), "+f"(rs[h][1]));
          };
          probs(0); probs(1); probs(2); probs(3);
#pragma unroll
          for (int hf = 0; hf < 2; hf++) {
#pragma unroll
            for (int hh = 0; hh < 2; hh++) {
              const int h = hf * 2 + hh, b = h * 4;
              const uint32_t pa = pp[h][0], pb = pp[h][1];
              const uint32_t p0 = pa & ~lm, p1 = pa & z, p2 = pa & lm, p3 = pb & ~lm, p4 = pb & z, p5 = pb & lm;
              const float ra = rs[h][0], rb = rs[h][1];
#pragma unroll
              for (int d = 0; d < 4; d++) {
                float o[4];
                mma16816z(o, p0, p1, p2, p3, kvH[16 + b + d], pkA[32 + 2 * (b + d)]);
                mma1688(o, p4, p5, pkA[32 + 2 * (b + d) + 1], o);
                if (hf == 0) { ob[0][(hh * 4 + d) * 2] = pack_bf16(o[0] * ra, o[1] * ra); ob[0][(hh * 4 + d) * 2 + 1] = pack_bf16(o[2] * rb, o[3] * rb); }
                else { o2[hh * 4 + d][0] = o[0]; o2[hh * 4 + d][1] = o[1]; o2[hh * 4 + d][2] = o[2]; o2[hh * 4 + d][3] = o[3]; }
              }
              if (hf) { r2[2 * hh] = ra; r2[2 * hh + 1] = rb; }
            }
            if (hf == 0) {
#pragma unroll
              for (int i = 0; i < 4; i++) ob[0][4 * i] = pkt_head(ob[0][4 * i]);
              AP(5);
              uint4* op = ptr_add(omail, j * 32768u);
#pragma unroll
              for (int i = 0; i < 4; i++) st_b128(op + i * 32, ob[0][4 * i], ob[0][4 * i + 1], ob[0][4 * i + 2], ob[0][4 * i + 3]);
              z = late_zero(zm);
              AP(6);
            }
          }
        }
        auto finish_o2 = [&](uint32_t z) {
#pragma unroll
          for (int i = 0; i < 4; i++) r2[i] = __uint_as_float(__float_as_uint(r2[i]) | z);
#pragma unroll
          for (int i = 0; i < 8; i++) {
            ob[1][2 * i] = pack_bf16(o2[i][0] * r2[(i >> 2) * 2], o2[i][1] * r2[(i >> 2) * 2]);
            ob[1][2 * i + 1] = pack_bf16(o2[i][2] * r2[(i >> 2) * 2 + 1], o2[i][3] * r2[(i >> 2) * 2 + 1]);
          }
#pragma unroll
          for (int i = 0; i < 4; i++) { ob[1][4 * i] = pkt_head(ob[1][4 * i]); sts128(stage + (warp & 3) * 2048 + i * 512 + l16, ob[1][4 * i], ob[1][4 * i + 1], ob[1][4 * i + 2], ob[1][4 * i + 3]); }
        };
        {
          uint32_t dep = __float_as_uint(r2[0]) | __float_as_uint(r2[2]);
#pragma unroll
          for (int i = 0; i < 8; i++) dep |= __float_as_uint(o2[i][3]);
          const uint32_t cnt = 256 | (dep & zm);
          AP(7);
          if (wg) { asm volatile("bar.arrive 1, %0;" :: "r"(cnt) : "memory"); bar_sync(6, 256); } else bar_sync(1, cnt);
        }
        TLC(3 + it * 6);
        AP(8);
        uint64_t todo;
        { const uint32_t o7 = 0x6543210u | (7u << (4 * j) & 0xfffffffu); todo = (uint64_t)(o7 * 2) | (uint64_t)(o7 * 2 + 0x1111111u) << 28; }
        const uint4* p0 = ptr_add(omail, ((uint32_t)todo & 15u) << 14);
        const uint4* p1 = ptr_add(omail, ((uint32_t)todo & 240u) << 10);
        auto batch = [&](int b, bool first) {
          uint32_t (&y0)[16] = ob[b ^ 2], (&y1)[16] = ob[b ^ 3];
          if (first) {
            c.issue_rs(acc2, ob[0], 0, 0);
            finish_o2(late_zero(zm));
            o_fetch(y0, y1, p0, p1);
          } else {
            o_fetch(y0, y1, p0, p1);
            c.issue_rs(acc2, ob[b], 0, 1);
          }
          c.issue_rs(acc2, ob[b + 1], 1, 1);
          if (first && !wg) asm volatile("bar.arrive 6, 256;" ::: "memory");
          const uint32_t z = late_zero(zm);
          todo >>= 8;
          const uint4* n0 = ptr_add(omail, ((uint32_t)todo & 15u) << 14);
          const uint4* n1 = ptr_add(omail, ((uint32_t)todo & 240u) << 10);
          asm volatile("" : "+l"(n0), "+l"(n1));
          c.wait_full(0);
          uint32_t spins = 0;
          while (__builtin_expect(__any_sync(0xffffffffu, (y0[0] == z || y0[4] == z || y0[8] == z || y0[12] == z) | (y1[0] == z || y1[4] == z || y1[8] == z || y1[12] == z)), 0)) {
            o_fetch(y0, y1, p0, p1);
            spin_check(++spins);
          }
          if (first) {
            fence_async_smem();
            __syncwarp();
            if (elect_one()) {
              asm volatile("cp.async.bulk.global.shared::cta.bulk_group [%0], [%1], 2048;"
                           :: "l"(scratch<uint4>(P, g * G_BLOCK + G_O + (2 * j + 1) * 16384u + warp * 2048u)), "r"(stage + (warp & 3) * 2048) : "memory");
              bulk_commit();
            }
          }
          p0 = n0; p1 = n1;
          c.drain();
        };
        batch(0, true);
#pragma unroll 1
        for (int i = 0; i < 3; i++) { batch(2, false); batch(0, false); }
        c.issue_rs(acc2, ob[2], 0, 1); c.issue_rs(acc2, ob[3], 1, 1);
        if (elect_one()) bulk_wait<0>();
        __syncwarp();
        {
          c.off += 2 << 10;
          c.wait_full(0);
          const uint32_t ra = maddr - (SM_STAGE + wg * 8192) + (c.off << 4);
#pragma unroll
          for (int i = 0; i < 8; i++) ldsm4((ra ^ ((i & 3) << 5)) + (i >> 2) * PAGE, res[4 * i], res[4 * i + 1], res[4 * i + 2], res[4 * i + 3]);
          if (lane < 2) mbar_arrive_cluster(c.ebar + 64 + ((c.n & 7) << 3));
          c.advance<2>();
          c.drain();
        }
        break;
      } else {
        c.steps<128>(acc2, 1 + wg);
        stage_wait();
        glu_slice_acc(acc, 0);
#pragma unroll
        for (int s = 1; s < 8; s++) {
          if (s == 5) c.steps_skip(acc2, t == 1 ? 1 - wg : 2); else c.steps<128>(acc2, (s & 1) || t == 3 ? 2 : 1);
          if (s == 4) stage_publish();
          glu_slice_acc(acc, s);
        }
        c.steps<128>(acc2, 2 - wg);
        stage_publish();
        if (t == 3) {
#pragma unroll
          for (int i = 0; i < 32; i++) { res[i] = 0x80008000u; asm volatile("" : "+r"(res[i])); }
#pragma unroll 1
          for (int i = 0; i < 3; i++) {
            c.steps<128>(acc2, i == 0 ? 15 : i == 1 ? 24 - TAIL_LAG : TAIL_LAG);
            if (i == 0) c.off = 0;
            else if (hl == 3) { if (wg == 1 && i == 1) { c.drain(); bar_sync(5, 256); } else if (wg == 0 && i == 2) asm volatile("bar.arrive 5, 256;" ::: "memory"); }
          }
          stage_wait();
          c.drain();
          break;
        }
        c.drain();
        TLC(2 + it * 6);
        c.step<256>(acc, 0);
        acc_fence<64>(acc2);
#pragma unroll
        for (int i = 0; i < 16; i++) {
          pkB[16 + i] = pack_bf16(acc2[2 * i], acc2[2 * i + 1]); pkB[48 + i] = pack_bf16(acc2[32 + 2 * i], acc2[32 + 2 * i + 1]);
          pkB[i] = 0; pkB[32 + i] = 0;
        }
      }
      t++;
#pragma unroll 1
      for (int s = 3 - t; s < 8; s++) {
        c.step<256>(acc, s);
        int act = (t == 3 || s >= 4) ? s : 8;
        asm volatile("" : "+r"(act));
        if (act < 8) {
          if (!(act & 3)) { if (act && t == 3) stage_publish(); else stage_wait(); }
          auto f = [&](int i) { glu_slice(pkB, i); };
          SELECT8(act, f);
        }
      }
#pragma unroll
      for (int s = 0; s < 2; s++) {
        const uint32_t ra = maddr - (SM_STAGE + wg * 8192) + (c.off << 4);
        c.step<256>(acc);
        if (s == 0) stage_publish();
#pragma unroll
        for (int i = 0; i < 4; i++) {
          uint32_t v[4];
          ldsm4(ra ^ (i << 5), v[0], v[1], v[2], v[3]);
#pragma unroll
          for (int e = 0; e < 4; e++) { acc2[32 * s + 8 * i + 2 * e] = bf_lo(v[e]); acc2[32 * s + 8 * i + 2 * e + 1] = bf_hi(v[e]); }
        }
        acc_fence<32>(acc2 + 32 * s);
      }
      c.step<256>(acc);
      }
      const int it = (hl >> 1) * 4 + t;
      acc_fence<64>(acc2);
      TLC(4 + it * 6);
      uint32_t xn[32];
#pragma unroll
      for (int i = 0; i < 16; i++) xn[i] = add_bf16x2(res[i], pack_bf16(acc2[2 * i], acc2[2 * i + 1]));
      stage_x(xn, 0);
#pragma unroll
      for (int i = 16; i < 32; i++) { xn[i] = add_bf16x2(res[i], pack_bf16(acc2[2 * i], acc2[2 * i + 1])); asm volatile("" : "+r"(xn[i])); }
      stage_publish();
      if (hl == 3) { stage_x(xn, 1); stage_publish(); TLE(47); TLG(63); break; }
      bar_sync(2 + wg, 128);
      TLC(5 + it * 6);
      c.step_own<256>(acc, dstage, 0);
      stage_x(xn, 1);
      stage_publish();
      bar_sync(2 + wg, 128);
    }
    }
  }
}

typedef CUresult (*EncodeFn)(CUtensorMap*, CUtensorMapDataType, cuuint32_t, void*, const cuuint64_t*, const cuuint64_t*, const cuuint32_t*,
                             const cuuint32_t*, CUtensorMapInterleave, CUtensorMapSwizzle, CUtensorMapL2promotion, CUtensorMapFloatOOBfill);

void encode(EncodeFn fn, CUtensorMap* m, const void* ptr, int rank, const cuuint64_t* dims, const cuuint64_t* strides, const cuuint32_t* box) {
  cuuint32_t es[5] = {1, 1, 1, 1, 1};
  fn(m, CU_TENSOR_MAP_DATA_TYPE_BFLOAT16, rank, const_cast<void*>(ptr), dims, strides, box, es, CU_TENSOR_MAP_INTERLEAVE_NONE,
     CU_TENSOR_MAP_SWIZZLE_128B, CU_TENSOR_MAP_L2_PROMOTION_L2_128B, CU_TENSOR_MAP_FLOAT_OOB_FILL_NONE);
}

}

extern "C" void kernel_launch(void* const* d_in, const int* in_sizes, int n_in, void* d_out, int out_size) {
  const __nv_bfloat16* x = (const __nv_bfloat16*)d_in[0];
  const __nv_bfloat16* wqkv = (const __nv_bfloat16*)d_in[1];
  const __nv_bfloat16* wo = (const __nv_bfloat16*)d_in[2];
  const __nv_bfloat16* w1 = (const __nv_bfloat16*)d_in[4];
  const __nv_bfloat16* w3 = (const __nv_bfloat16*)d_in[5];
  const __nv_bfloat16* w2 = (const __nv_bfloat16*)d_in[6];

  void* fnp = nullptr; cudaDriverEntryPointQueryResult qr;
  cudaGetDriverEntryPoint("cuTensorMapEncodeTiled", &fnp, cudaEnableDefault, &qr);
  EncodeFn fn = (EncodeFn)fnp;
  void* sym;
  cudaGetSymbolAddress(&sym, g_scratch);
  uint8_t* scr = (uint8_t*)(((uintptr_t)sym + G_PAGE - 1) / G_PAGE * G_PAGE);

  Params P = {};
  { cuuint64_t d[3] = {DM, 2, SEQ / 2}, s[2] = {DM * 2, DM * 4}; cuuint32_t b[3] = {64, 1, 128}, b2[3] = {64, 1, 64};
    encode(fn, &P.map[M_XIN], x, 3, d, s, b); encode(fn, &P.map[M_XIN64], x, 3, d, s, b2);
    encode(fn, &P.map[M_OUT_LD], d_out, 3, d, s, b); encode(fn, &P.map[M_OUT_ST], d_out, 3, d, s, b2); }
  { cuuint64_t d[3] = {FF, 16, 128}, s[2] = {G_BLOCK, FF * 2}; cuuint32_t b[3] = {64, 1, 128}, b2[3] = {64, 1, 64};
    encode(fn, &P.map[M_H_LD], scr + G_H, 3, d, s, b); encode(fn, &P.map[M_H_ST], scr + G_H, 3, d, s, b2); }
  { const cuuint32_t b2[3] = {64, 64, 2}, b1[3] = {64, 64, 1};
    { cuuint64_t d[3] = {64, DM, 48}, s[2] = {3 * DM * 2, 128}; encode(fn, &P.map[M_WKV], wqkv, 3, d, s, b2); encode(fn, &P.map[M_WQ], wqkv, 3, d, s, b1); }
    { cuuint64_t d[3] = {64, DM, 16}, s[2] = {DM * 2, 128}; encode(fn, &P.map[M_WO], wo, 3, d, s, b1); }
    { cuuint64_t d[3] = {64, FF, 16}, s[2] = {DM * 2, 128}; encode(fn, &P.map[M_W2], w2, 3, d, s, b1); }
    { cuuint64_t d[3] = {64, DM, FF / 64}, s[2] = {FF * 2, 128};
      encode(fn, &P.map[M_W1], w1, 3, d, s, b2); encode(fn, &P.map[M_W3], w3, 3, d, s, b2);
      encode(fn, &P.map[M_W1H], w1, 3, d, s, b1); encode(fn, &P.map[M_W3H], w3, 3, d, s, b1); }
  }
  P.scratch = scr; P.x = x; P.wqkv = wqkv; P.wo = wo; P.w2 = w2;
  int dev = 0, sms = 0;
  cudaGetDevice(&dev);
  cudaDeviceGetAttribute(&sms, cudaDevAttrMultiProcessorCount, dev);
  P.use_smid = (sms == 132);
  cudaFuncSetAttribute(fused_kernel, cudaFuncAttributeMaxDynamicSharedMemorySize, SM_ALLOC);
  fused_kernel<<<132, 384, SM_ALLOC>>>(P);
}
```

```cpp
#include <cuda_runtime.h>
#include <cuda_bf16.h>
#include <cuda.h>
#include <stdint.h>
#include <math.h>

namespace {

constexpr int SEQ = 2048, DM = 1024, FF = 3584;
constexpr float LN_EPS = 1e-5f;
constexpr float LOG2E = 1.4426950408889634f;

#define G_SKEW 4096
constexpr uint32_t G_PAGE = 2u << 20, G_BLOCK = G_PAGE + G_SKEW;
constexpr uint32_t G_H = 0;
constexpr uint32_t G_O = G_H + 128 * FF * 2;
constexpr uint32_t G_STATS = G_O + 128 * DM * 2;
constexpr uint32_t G_FLAGS = G_STATS + 4 * 128 * 64;
static_assert(G_FLAGS + 4096 + 15 * G_SKEW <= G_PAGE, "");
constexpr uint32_t G_HALO = 16 * G_PAGE;
constexpr uint32_t G_CS = G_HALO + 2 * 16 * 8 * 4096;
constexpr uint32_t G_EPOCH = G_CS + (3 * DM + 2 * FF) * 16;
__device__ __align__(1024) uint8_t g_scratch[18 * G_PAGE];

enum { M_XIN, M_XIN64, M_H_LD, M_H_ST, M_OUT_LD, M_OUT_ST, M_WKV, M_WQ, M_WO, M_W1, M_W3, M_W1H, M_W3H, M_W2, M_COUNT };
struct alignas(64) Params {
  CUtensorMap map[M_COUNT];
  uint8_t* scratch;
  const __nv_bfloat16* x;
  const __nv_bfloat16* wqkv;
  const __nv_bfloat16* wo;
  const __nv_bfloat16* w2;
  int use_smid;
};

constexpr uint32_t PAGE = 16384, NPAGE = 12;
constexpr uint32_t SM_STAGE = NPAGE * PAGE;
constexpr uint32_t SM_BAR = SM_STAGE + 2 * PAGE;
constexpr uint32_t SM_CS = SM_BAR + 256;
constexpr uint32_t SM_TOTAL = SM_CS + 1536;
constexpr uint32_t SM_ALLOC = SM_TOTAL;
static_assert(SM_ALLOC <= 232448, "shared memory");
constexpr uint32_t BAR_FULL = SM_BAR, BAR_EMPTY = SM_BAR + 64, BAR_SFULL = SM_BAR + 128;
constexpr uint32_t BAR_XFULL = SM_BAR + 160, BAR_CSE = SM_BAR + 168;
constexpr uint32_t BAR_SEMPTY = SM_BAR + 176, BAR_CSF = SM_BAR + 184, BAR_XIN = SM_BAR + 200;
constexpr uint32_t BAR_CLR = SM_BAR + 240, BAR_TAG = SM_BAR + 216, SM_ROLE = SM_BAR + 224, SM_TAG = SM_BAR + 228, SM_SEEN = SM_BAR + 232;
enum { EV_XA, EV_XA2, EV_H0, EV_H3, EV_H1, EV_H2, EV_XB, EV_XB2, EV_N };

struct Sched { uint32_t pat[16]; uint32_t page0[16]; bool ok; };
constexpr int seg_steps(int seg) { return seg == 0 || seg == 3 ? 18 : seg == 1 || seg == 4 ? 14 : seg == 2 ? 7 : seg == 7 ? 24 : 32; }
constexpr int step_pages(int seg, int i) {
  return seg == 0 || seg == 3 ? (i < 2 ? 2 : i < 4 ? 1 : 3) : seg == 5 || (seg == 2 && i >= 1 && i <= 4) ? 3 : 2;
}
constexpr Sched make_sched() {
  Sched s = {};
  int owner[NPAGE] = {-1, -1, -1, -1, -1, -1, -1, -1, -1, -1, -1, -1};
  int n = 0, tail = 0, page = 0;
  s.ok = true;
  for (int sg = 0; sg < 16; sg++) {
    const int seg = sg % 8;
    s.page0[sg] = page;
    for (int i = 0; i < seg_steps(seg); i++) {
      const int p = step_pages(seg, i);
      if ((seg == 2 && i == 6) || (seg == 4 && i == 8) || (seg == 7 && i == 0)) page = (page + 2) % NPAGE;
      if (page + p > (int)NPAGE) { s.ok = false; return s; }
      int need = n - 8;
      for (int q = 0; q < p; q++) { if (owner[page + q] > need) need = owner[page + q]; owner[page + q] = n; }
      int nw = need + 1 - tail; if (nw < 0) nw = 0;
      tail += nw;
      if (i < 16) s.pat[sg] |= (uint32_t)nw << (2 * i); else if (nw != 1) s.ok = false;
      if (nw > 3) s.ok = false;
      page = (page + p) % NPAGE; n++;
    }
  }
  for (int sg = 0; sg < 8; sg++) if (s.page0[sg] != s.page0[sg + 8] || (sg && s.pat[sg] != s.pat[sg + 8])) s.ok = false;
  return s;
}
constexpr Sched SCHED = make_sched();
static_assert(SCHED.ok && SCHED.page0[0] == 0 && SCHED.page0[3] == 0 && SCHED.page0[5] == 6 && SCHED.page0[2] == 4 && SCHED.page0[7] == 10 && (SCHED.pat[0] & 0xfff) == 0, "ring schedule");
template <int SEG> struct Pat { static constexpr uint32_t v = SCHED.pat[SEG]; };

#define TAIL_LAG 3
__device__ __forceinline__ uint32_t smem_u32(const void* p) { return (uint32_t)__cvta_generic_to_shared(p); }
__device__ __forceinline__ void mbar_init(uint32_t bar, uint32_t cnt) { asm volatile("mbarrier.init.shared::cta.b64 [%0], %1;" :: "r"(bar), "r"(cnt)); }
__device__ __forceinline__ void mbar_expect_tx(uint32_t bar, uint32_t bytes) { asm volatile("mbarrier.arrive.expect_tx.shared::cta.b64 _, [%0], %1;" :: "r"(bar), "r"(bytes) : "memory"); }
__device__ __forceinline__ void mbar_arrive(uint32_t bar) { asm volatile("mbarrier.arrive.shared::cta.b64 _, [%0];" :: "r"(bar) : "memory"); }
__device__ __forceinline__ void mbar_wait(uint32_t bar, uint32_t parity) {
  asm volatile("{\n.reg .pred p;\n.reg .u32 n;\nmov.u32 n, 0;\nLAB_WAIT:\n"
               "mbarrier.try_wait.parity.shared::cta.b64 p, [%0], %1;\n@p bra LAB_DONE;\n"
               "add.u32 n, n, 1;\nsetp.lt.u32 p, n, 4194304;\n@p bra LAB_WAIT;\ntrap;\nLAB_DONE:\n}" :: "r"(bar), "r"(parity) : "memory");
}
__device__ __forceinline__ void mbar_wait_fast(uint32_t bar, uint32_t parity) {
  asm volatile("{\n.reg .pred p;\nLAB_WAIT:\nmbarrier.try_wait.parity.shared::cta.b64 p, [%0], %1;\n@!p bra LAB_WAIT;\n}" :: "r"(bar), "r"(parity) : "memory");
}
__device__ __forceinline__ void spin_check(uint32_t n) { asm volatile("{\n.reg .pred p;\nsetp.ge.u32 p, %0, 4194304;\n@p st.volatile.global.u32 [%1], %0;\n}" :: "r"(n), "l"(0ull)); }
__device__ __forceinline__ void tma_ld3(uint32_t dst, const CUtensorMap* m, uint32_t bar, int c0, int c1, int c2) {
  asm volatile("cp.async.bulk.tensor.3d.shared::cluster.global.mbarrier::complete_tx::bytes [%0], [%1, {%3, %4, %5}], [%2];" :: "r"(dst), "l"(m), "r"(bar), "r"(c0), "r"(c1), "r"(c2) : "memory");
}
__device__ __forceinline__ void tma_ld3_mc(uint32_t dst, const CUtensorMap* m, uint32_t bar, int c0, int c1, int c2, uint16_t mask) {
  asm volatile("cp.async.bulk.tensor.3d.shared::cluster.global.mbarrier::complete_tx::bytes.multicast::cluster [%0], [%1, {%3, %4, %5}], [%2], %6;"
               :: "r"(dst), "l"(m), "r"(bar), "r"(c0), "r"(c1), "r"(c2), "h"(mask) : "memory");
}
__device__ __forceinline__ uint32_t mapa(uint32_t addr, uint32_t cta) { uint32_t r; asm("mapa.shared::cluster.u32 %0, %1, %2;" : "=r"(r) : "r"(addr), "r"(cta)); return r; }
__device__ __forceinline__ void mbar_arrive_cluster(uint32_t bar) { asm volatile("mbarrier.arrive.shared::cluster.b64 _, [%0];" :: "r"(bar) : "memory"); }
__device__ __forceinline__ void tma_st3(const CUtensorMap* m, uint32_t src, int c0, int c1, int c2) {
  asm volatile("cp.async.bulk.tensor.3d.global.shared::cta.bulk_group [%0, {%2, %3, %4}], [%1];" :: "l"(m), "r"(src), "r"(c0), "r"(c1), "r"(c2) : "memory");
}
__device__ __forceinline__ void bulk_commit() { asm volatile("cp.async.bulk.commit_group;" ::: "memory"); }
template <int N> __device__ __forceinline__ void bulk_wait() { asm volatile("cp.async.bulk.wait_group %0;" :: "n"(N) : "memory"); }
__device__ __forceinline__ void fence_async_smem() { asm volatile("fence.proxy.async.shared::cta;" ::: "memory"); }
__device__ __forceinline__ void fence_async_global() { asm volatile("fence.proxy.async.global;" ::: "memory"); }
__device__ __forceinline__ bool elect_one() { uint32_t p; asm volatile("{\n.reg .pred P;\nelect.sync _|P, 0xffffffff;\nselp.u32 %0, 1, 0, P;\n}" : "=r"(p)); return p; }
__device__ __forceinline__ void prefetch_map(const CUtensorMap* m) { asm volatile("prefetch.tensormap [%0];" :: "l"(m) : "memory"); }
__device__ __forceinline__ void prefetch_l2(const void* p, uint32_t bytes) { asm volatile("cp.async.bulk.prefetch.L2.global [%0], %1;" :: "l"(p), "r"(bytes) : "memory"); }
__device__ __forceinline__ void wgmma_fence() { asm volatile("wgmma.fence.sync.aligned;" ::: "memory"); }
__device__ __forceinline__ void wgmma_commit() { asm volatile("wgmma.commit_group.sync.aligned;" ::: "memory"); }
template <int N> __device__ __forceinline__ void wgmma_wait() { asm volatile("wgmma.wait_group.sync.aligned %0;" :: "n"(N) : "memory"); }
__device__ __forceinline__ uint32_t desc_lo(uint32_t addr, uint32_t lbo) { return ((addr & 0x3FFFF) >> 4) | ((lbo >> 4) << 16); }
__device__ __forceinline__ uint64_t desc64(uint32_t lo) { uint64_t r; asm("mov.b64 %0, {%1, %2};" : "=l"(r) : "r"(lo), "r"(0x40000040u)); return r; }
__device__ __forceinline__ void bar_sync(int id, int n) { asm volatile("bar.sync %0, %1;" :: "r"(id), "r"(n) : "memory"); }
__device__ __forceinline__ uint32_t pack_bf16(float lo, float hi) { uint32_t r; asm("cvt.rn.bf16x2.f32 %0, %1, %2;" : "=r"(r) : "f"(hi), "f"(lo)); return r; }
__device__ __forceinline__ float bf_lo(uint32_t v) { return __uint_as_float(v << 16); }
__device__ __forceinline__ float bf_hi(uint32_t v) { return __uint_as_float(v & 0xffff0000u); }
__device__ __forceinline__ float ex2(float x) { float r; asm("ex2.approx.ftz.f32 %0, %1;" : "=f"(r) : "f"(x)); return r; }
__device__ __forceinline__ float rcp(float x) { float r; asm("rcp.approx.ftz.f32 %0, %1;" : "=f"(r) : "f"(x)); return r; }
__device__ __forceinline__ void stsm4(uint32_t a, uint32_t r0, uint32_t r1, uint32_t r2, uint32_t r3) {
  asm volatile("stmatrix.sync.aligned.m8n8.x4.shared.b16 [%0], {%1, %2, %3, %4};" :: "r"(a), "r"(r0), "r"(r1), "r"(r2), "r"(r3) : "memory");
}
__device__ __forceinline__ void ldsm4(uint32_t a, uint32_t& r0, uint32_t& r1, uint32_t& r2, uint32_t& r3) {
  asm volatile("ldmatrix.sync.aligned.m8n8.x4.shared.b16 {%0, %1, %2, %3}, [%4];" : "=r"(r0), "=r"(r1), "=r"(r2), "=r"(r3) : "r"(a) : "memory");
}
__device__ __forceinline__ uint32_t movm(uint32_t v) { uint32_t r; asm volatile("movmatrix.sync.aligned.m8n8.trans.b16 %0, %1;" : "=r"(r) : "r"(v)); return r; }
__device__ __forceinline__ void sts128(uint32_t a, uint32_t r0, uint32_t r1, uint32_t r2, uint32_t r3) {
  asm volatile("st.shared.v4.b32 [%0], {%1, %2, %3, %4};" :: "r"(a), "r"(r0), "r"(r1), "r"(r2), "r"(r3) : "memory");
}
__device__ __forceinline__ void lds128(uint32_t a, uint32_t& r0, uint32_t& r1, uint32_t& r2, uint32_t& r3) {
  asm volatile("ld.shared.v4.b32 {%0, %1, %2, %3}, [%4];" : "=r"(r0), "=r"(r1), "=r"(r2), "=r"(r3) : "r"(a) : "memory");
}
__device__ __forceinline__ uint32_t add_bf16x2(uint32_t a, uint32_t b) { uint32_t r; asm("add.rn.bf16x2 %0, %1, %2;" : "=r"(r) : "r"(a), "r"(b)); return r; }
__device__ __forceinline__ void sts32f(uint32_t a, float v) { asm volatile("st.shared.f32 [%0], %1;" :: "r"(a), "f"(v) : "memory"); }
__device__ __forceinline__ void mma16816(float (&d)[4], uint32_t a0, uint32_t a1, uint32_t a2, uint32_t a3, uint32_t b0, uint32_t b1, const float (&c)[4]) {
  asm("mma.sync.aligned.m16n8k16.row.col.f32.bf16.bf16.f32 {%0, %1, %2, %3}, {%4, %5, %6, %7}, {%8, %9}, {%10, %11, %12, %13};"
      : "=f"(d[0]), "=f"(d[1]), "=f"(d[2]), "=f"(d[3]) : "r"(a0), "r"(a1), "r"(a2), "r"(a3), "r"(b0), "r"(b1), "f"(c[0]), "f"(c[1]), "f"(c[2]), "f"(c[3]));
}
__device__ __forceinline__ void mma1688(float (&d)[4], uint32_t a0, uint32_t a1, uint32_t b0, const float (&c)[4]) {
  asm("mma.sync.aligned.m16n8k8.row.col.f32.bf16.bf16.f32 {%0, %1, %2, %3}, {%4, %5}, {%6}, {%7, %8, %9, %10};"
      : "=f"(d[0]), "=f"(d[1]), "=f"(d[2]), "=f"(d[3]) : "r"(a0), "r"(a1), "r"(b0), "f"(c[0]), "f"(c[1]), "f"(c[2]), "f"(c[3]));
}
__device__ __forceinline__ void mma16816z(float (&d)[4], uint32_t a0, uint32_t a1, uint32_t a2, uint32_t a3, uint32_t b0, uint32_t b1) {
  asm("mma.sync.aligned.m16n8k16.row.col.f32.bf16.bf16.f32 {%0, %1, %2, %3}, {%4, %5, %6, %7}, {%8, %9}, {0f00000000, 0f00000000, 0f00000000, 0f00000000};"
      : "=f"(d[0]), "=f"(d[1]), "=f"(d[2]), "=f"(d[3]) : "r"(a0), "r"(a1), "r"(a2), "r"(a3), "r"(b0), "r"(b1));
}
__device__ __forceinline__ void mma1688z(float (&d)[4], uint32_t a0, uint32_t a1, uint32_t b0) {
  asm("mma.sync.aligned.m16n8k8.row.col.f32.bf16.bf16.f32 {%0, %1, %2, %3}, {%4, %5}, {%6}, {0f00000000, 0f00000000, 0f00000000, 0f00000000};"
      : "=f"(d[0]), "=f"(d[1]), "=f"(d[2]), "=f"(d[3]) : "r"(a0), "r"(a1), "r"(b0));
}
__device__ __forceinline__ uint32_t bar_sync_zero(int id, int n) {
  uint32_t r;
  asm volatile("{\n.reg .pred p;\nsetp.eq.u32 p, %1, 0;\nbarrier.cta.red.popc.aligned.u32 %0, %1, %2, p;\n}" : "=r"(r) : "r"(id), "r"(n) : "memory");
  return r;
}
__device__ __forceinline__ uint32_t late_zero(uint32_t zm) { uint32_t c; asm volatile("mov.u32 %0, %%clock;" : "=r"(c) :: "memory"); return c & zm; }
__device__ __forceinline__ void st_b128(uint4* p, uint32_t a, uint32_t b, uint32_t c, uint32_t d) {
  asm volatile("{\n.reg .b128 t;\n.reg .b64 lo, hi;\nmov.b64 lo, {%0, %1};\nmov.b64 hi, {%2, %3};\nmov.b128 t, {lo, hi};\nst.relaxed.gpu.global.b128 [%4], t;\n}"
               :: "r"(a), "r"(b), "r"(c), "r"(d), "l"(p) : "memory");
}
__device__ __forceinline__ uint32_t pkt_head(uint32_t a) { return a ? a : 0x8000u; }
__device__ __forceinline__ void gen_store(uint4* p, uint32_t a, uint32_t b, uint32_t c, uint32_t d) {
  asm volatile("{\n.reg .b128 t;\n.reg .b64 lo, hi;\nmov.b64 lo, {%0, %1};\nmov.b64 hi, {%2, %3};\nmov.b128 t, {lo, hi};\nst.relaxed.gpu.b128 [%4], t;\n}"
               :: "r"(a), "r"(b), "r"(c), "r"(d), "l"(p) : "memory");
}
__device__ __forceinline__ void gen_load(const uint4* p, uint32_t* v) {
  asm volatile("{\n.reg .b128 t;\n.reg .b64 lo, hi;\nld.relaxed.gpu.b128 t, [%4];\nmov.b128 {lo, hi}, t;\nmov.b64 {%0, %1}, lo;\nmov.b64 {%2, %3}, hi;\n}"
               : "=r"(v[0]), "=r"(v[1]), "=r"(v[2]), "=r"(v[3]) : "l"(p) : "memory");
}
__device__ __forceinline__ void pkt_load(const uint4* p, uint32_t* v) {
  asm volatile("{\n.reg .b128 t;\n.reg .b64 lo, hi;\nld.relaxed.gpu.global.b128 t, [%4];\nmov.b128 {lo, hi}, t;\nmov.b64 {%0, %1}, lo;\nmov.b64 {%2, %3}, hi;\n}"
               : "=r"(v[0]), "=r"(v[1]), "=r"(v[2]), "=r"(v[3]) : "l"(p) : "memory");
}
__device__ __forceinline__ uint32_t ld_relaxed(const uint32_t* p) { uint32_t v; asm volatile("ld.relaxed.gpu.global.u32 %0, [%1];" : "=r"(v) : "l"(p) : "memory"); return v; }
__device__ __forceinline__ uint4 ld_relaxed4(const void* p) { uint4 v; asm volatile("ld.relaxed.gpu.global.v4.u32 {%0, %1, %2, %3}, [%4];" : "=r"(v.x), "=r"(v.y), "=r"(v.z), "=r"(v.w) : "l"(p) : "memory"); return v; }
__device__ __forceinline__ void st_relaxed(uint32_t* p, uint32_t v) { asm volatile("st.relaxed.gpu.global.u32 [%0], %1;" :: "l"(p), "r"(v) : "memory"); }
__device__ __forceinline__ void st_relaxed2(void* p, uint32_t a, uint32_t b) { asm volatile("st.relaxed.gpu.global.v2.u32 [%0], {%1, %2};" :: "l"(p), "r"(a), "r"(b) : "memory"); }
__device__ __forceinline__ void red_release(uint32_t* p, uint32_t v) { asm volatile("red.release.gpu.global.add.u32 [%0], %1;" :: "l"(p), "r"(v) : "memory"); }
__device__ __forceinline__ uint32_t tagf(float v, uint32_t tag) { return (__float_as_uint(v) & ~15u) | (tag & 15u); }
__device__ __forceinline__ bool tag_ok4(const uint4& v, uint32_t tag) { return (((v.x ^ tag) | (v.y ^ tag) | (v.z ^ tag) | (v.w ^ tag)) & 15u) == 0; }
__device__ __forceinline__ float untag(uint32_t v) { return __uint_as_float(v & ~15u); }
template <typename T> __device__ __forceinline__ T* ptr_add(T* p, uint32_t bytes) {
  uint64_t r;
  asm("{\n.reg .u32 lo, hi;\nmov.b64 {lo, hi}, %1;\nadd.cc.u32 lo, lo, %2;\naddc.u32 hi, hi, 0;\nmov.b64 %0, {lo, hi};\n}" : "=l"(r) : "l"(p), "r"(bytes));
  return (T*)r;
}
#define TL(who, slot) do {} while (0)
#define TLC(slot) do {} while (0)
#define TLE(slot) do {} while (0)
#define ST(who, n) do {} while (0)
#define AP(i) do {} while (0)
#define SP(v) do {} while (0)
#define TLG(slot) do {} while (0)
#define STA() do {} while (0)
#define STB(n) do {} while (0)

__device__ __forceinline__ void wgmma_n128(float (&d)[64], uint64_t da, uint64_t db, int scale_d) {
  asm volatile("{\n.reg .pred p;\nsetp.ne.b32 p, %66, 0;\n"
    "wgmma.mma_async.sync.aligned.m64n128k16.f32.bf16.bf16 "
    "{%0, %1, %2, %3, %4, %5, %6, %7, %8, %9, %10, %11, %12, %13, %14, %15, "
    "%16, %17, %18, %19, %20, %21, %22, %23, %24, %25, %26, %27, %28, %29, %30, %31, "
    "%32, %33, %34, %35, %36, %37, %38, %39, %40, %41, %42, %43, %44, %45, %46, %47, "
    "%48, %49, %50, %51, %52, %53, %54, %55, %56, %57, %58, %59, %60, %61, %62, %63}, "
    "%64, %65, p, 1, 1, 0, 1;\n}\n"
    : "+f"(d[0]), "+f"(d[1]), "+f"(d[2]), "+f"(d[3]), "+f"(d[4]), "+f"(d[5]), "+f"(d[6]), "+f"(d[7]),
      "+f"(d[8]), "+f"(d[9]), "+f"(d[10]), "+f"(d[11]), "+f"(d[12]), "+f"(d[13]), "+f"(d[14]), "+f"(d[15]),
      "+f"(d[16]), "+f"(d[17]), "+f"(d[18]), "+f"(d[19]), "+f"(d[20]), "+f"(d[21]), "+f"(d[22]), "+f"(d[23]),
      "+f"(d[24]), "+f"(d[25]), "+f"(d[26]), "+f"(d[27]), "+f"(d[28]), "+f"(d[29]), "+f"(d[30]), "+f"(d[31]),
      "+f"(d[32]), "+f"(d[33]), "+f"(d[34]), "+f"(d[35]), "+f"(d[36]), "+f"(d[37]), "+f"(d[38]), "+f"(d[39]),
      "+f"(d[40]), "+f"(d[41]), "+f"(d[42]), "+f"(d[43]), "+f"(d[44]), "+f"(d[45]), "+f"(d[46]), "+f"(d[47]),
      "+f"(d[48]), "+f"(d[49]), "+f"(d[50]), "+f"(d[51]), "+f"(d[52]), "+f"(d[53]), "+f"(d[54]), "+f"(d[55]),
      "+f"(d[56]), "+f"(d[57]), "+f"(d[58]), "+f"(d[59]), "+f"(d[60]), "+f"(d[61]), "+f"(d[62]), "+f"(d[63])
    : "l"(da), "l"(db), "r"(scale_d));
}
__device__ __forceinline__ void wgmma_n256(float (&d)[128], uint64_t da, uint64_t db, int scale_d) {
  asm volatile("{\n.reg .pred p;\nsetp.ne.b32 p, %130, 0;\n"
    "wgmma.mma_async.sync.aligned.m64n256k16.f32.bf16.bf16 "
    "{%0, %1, %2, %3, %4, %5, %6, %7, %8, %9, %10, %11, %12, %13, %14, %15, "
    "%16, %17, %18, %19, %20, %21, %22, %23, %24, %25, %26, %27, %28, %29, %30, %31, "
    "%32, %33, %34, %35, %36, %37, %38, %39, %40, %41, %42, %43, %44, %45, %46, %47, "
    "%48, %49, %50, %51, %52, %53, %54, %55, %56, %57, %58, %59, %60, %61, %62, %63, "
    "%64, %65, %66, %67, %68, %69, %70, %71, %72, %73, %74, %75, %76, %77, %78, %79, "
    "%80, %81, %82, %83, %84, %85, %86, %87, %88, %89, %90, %91, %92, %93, %94, %95, "
    "%96, %97, %98, %99, %100, %101, %102, %103, %104, %105, %106, %107, %108, %109, %110, %111, "
    "%112, %113, %114, %115, %116, %117, %118, %119, %120, %121, %122, %123, %124, %125, %126, %127}, "
    "%128, %129, p, 1, 1, 0, 1;\n}\n"
    : "+f"(d[0]), "+f"(d[1]), "+f"(d[2]), "+f"(d[3]), "+f"(d[4]), "+f"(d[5]), "+f"(d[6]), "+f"(d[7]),
      "+f"(d[8]), "+f"(d[9]), "+f"(d[10]), "+f"(d[11]), "+f"(d[12]), "+f"(d[13]), "+f"(d[14]), "+f"(d[15]),
      "+f"(d[16]), "+f"(d[17]), "+f"(d[18]), "+f"(d[19]), "+f"(d[20]), "+f"(d[21]), "+f"(d[22]), "+f"(d[23]),
      "+f"(d[24]), "+f"(d[25]), "+f"(d[26]), "+f"(d[27]), "+f"(d[28]), "+f"(d[29]), "+f"(d[30]), "+f"(d[31]),
      "+f"(d[32]), "+f"(d[33]), "+f"(d[34]), "+f"(d[35]), "+f"(d[36]), "+f"(d[37]), "+f"(d[38]), "+f"(d[39]),
      "+f"(d[40]), "+f"(d[41]), "+f"(d[42]), "+f"(d[43]), "+f"(d[44]), "+f"(d[45]), "+f"(d[46]), "+f"(d[47]),
      "+f"(d[48]), "+f"(d[49]), "+f"(d[50]), "+f"(d[51]), "+f"(d[52]), "+f"(d[53]), "+f"(d[54]), "+f"(d[55]),
      "+f"(d[56]), "+f"(d[57]), "+f"(d[58]), "+f"(d[59]), "+f"(d[60]), "+f"(d[61]), "+f"(d[62]), "+f"(d[63]),
      "+f"(d[64]), "+f"(d[65]), "+f"(d[66]), "+f"(d[67]), "+f"(d[68]), "+f"(d[69]), "+f"(d[70]), "+f"(d[71]),
      "+f"(d[72]), "+f"(d[73]), "+f"(d[74]), "+f"(d[75]), "+f"(d[76]), "+f"(d[77]), "+f"(d[78]), "+f"(d[79]),
      "+f"(d[80]), "+f"(d[81]), "+f"(d[82]), "+f"(d[83]), "+f"(d[84]), "+f"(d[85]), "+f"(d[86]), "+f"(d[87]),
      "+f"(d[88]), "+f"(d[89]), "+f"(d[90]), "+f"(d[91]), "+f"(d[92]), "+f"(d[93]), "+f"(d[94]), "+f"(d[95]),
      "+f"(d[96]), "+f"(d[97]), "+f"(d[98]), "+f"(d[99]), "+f"(d[100]), "+f"(d[101]), "+f"(d[102]), "+f"(d[103]),
      "+f"(d[104]), "+f"(d[105]), "+f"(d[106]), "+f"(d[107]), "+f"(d[108]), "+f"(d[109]), "+f"(d[110]), "+f"(d[111]),
      "+f"(d[112]), "+f"(d[113]), "+f"(d[114]), "+f"(d[115]), "+f"(d[116]), "+f"(d[117]), "+f"(d[118]), "+f"(d[119]),
      "+f"(d[120]), "+f"(d[121]), "+f"(d[122]), "+f"(d[123]), "+f"(d[124]), "+f"(d[125]), "+f"(d[126]), "+f"(d[127])
    : "l"(da), "l"(db), "r"(scale_d));
}
__device__ __forceinline__ void wgmma_rs_n128(float (&d)[64], const uint32_t* a, uint64_t db, int scale_d) {
  asm volatile("{\n.reg .pred p;\nsetp.ne.b32 p, %69, 0;\n"
    "wgmma.mma_async.sync.aligned.m64n128k16.f32.bf16.bf16 "
    "{%0, %1, %2, %3, %4, %5, %6, %7, %8, %9, %10, %11, %12, %13, %14, %15, "
    "%16, %17, %18, %19, %20, %21, %22, %23, %24, %25, %26, %27, %28, %29, %30, %31, "
    "%32, %33, %34, %35, %36, %37, %38, %39, %40, %41, %42, %43, %44, %45, %46, %47, "
    "%48, %49, %50, %51, %52, %53, %54, %55, %56, %57, %58, %59, %60, %61, %62, %63}, "
    "{%64, %65, %66, %67}, %68, p, 1, 1, 1;\n}\n"
    : "+f"(d[0]), "+f"(d[1]), "+f"(d[2]), "+f"(d[3]), "+f"(d[4]), "+f"(d[5]), "+f"(d[6]), "+f"(d[7]),
      "+f"(d[8]), "+f"(d[9]), "+f"(d[10]), "+f"(d[11]), "+f"(d[12]), "+f"(d[13]), "+f"(d[14]), "+f"(d[15]),
      "+f"(d[16]), "+f"(d[17]), "+f"(d[18]), "+f"(d[19]), "+f"(d[20]), "+f"(d[21]), "+f"(d[22]), "+f"(d[23]),
      "+f"(d[24]), "+f"(d[25]), "+f"(d[26]), "+f"(d[27]), "+f"(d[28]), "+f"(d[29]), "+f"(d[30]), "+f"(d[31]),
      "+f"(d[32]), "+f"(d[33]), "+f"(d[34]), "+f"(d[35]), "+f"(d[36]), "+f"(d[37]), "+f"(d[38]), "+f"(d[39]),
      "+f"(d[40]), "+f"(d[41]), "+f"(d[42]), "+f"(d[43]), "+f"(d[44]), "+f"(d[45]), "+f"(d[46]), "+f"(d[47]),
      "+f"(d[48]), "+f"(d[49]), "+f"(d[50]), "+f"(d[51]), "+f"(d[52]), "+f"(d[53]), "+f"(d[54]), "+f"(d[55]),
      "+f"(d[56]), "+f"(d[57]), "+f"(d[58]), "+f"(d[59]), "+f"(d[60]), "+f"(d[61]), "+f"(d[62]), "+f"(d[63])
    : "r"(a[0]), "r"(a[1]), "r"(a[2]), "r"(a[3]), "l"(db), "r"(scale_d));
}

template <int BN> __device__ __forceinline__ void wgmma(float (&d)[BN / 2], uint64_t a, uint64_t b, int s) {
  if constexpr (BN == 128) wgmma_n128(d, a, b, s);
  else wgmma_n256(d, a, b, s);
}

template <int N> __device__ __forceinline__ void acc_fence(float* a) {
#pragma unroll
  for (int i = 0; i < N; i++) asm volatile("" : "+f"(a[i]) :: "memory");
}

#define SELECT8(a, f) do { \
  if ((a) & 4) { if ((a) & 2) { if ((a) & 1) f(7); else f(6); } else { if ((a) & 1) f(5); else f(4); } } \
  else { if ((a) & 2) { if ((a) & 1) f(3); else f(2); } else { if ((a) & 1) f(1); else f(0); } } } while (0)
__device__ __forceinline__ uint32_t lane_now() { uint32_t l; asm volatile("mov.u32 %0, %%laneid;" : "=r"(l)); return l; }

struct Prod {
  uint32_t sb, n, tail, addr, pat, ready;
  uint32_t rank, flip; uint16_t mask;
  __device__ __forceinline__ void load_b(uint32_t dst, uint32_t half, const CUtensorMap* m, uint32_t mstep, uint32_t fb, int k, int ch, int cstep) {
    uint32_t h = rank;
    do { tma_ld3_mc(dst + h * half, ptr_add(m, h * mstep), fb, 0, k * 64, ch + h * cstep, mask); h ^= flip; } while (h != rank);
  }
  __device__ __forceinline__ void load_wide(const Params& P, int ffn, uint32_t dst, uint32_t fb, int k, int ch) {
    load_b(dst, PAGE, &P.map[ffn ? M_W1 : M_WKV], ffn ? 128 : 0, fb, k, ffn ? ch : ch + 16, ffn ? 0 : 16);
  }
  __device__ __forceinline__ void load_narrow(const Params& P, int ffn, uint32_t dst, uint32_t fb, int k, int j) {
    load_b(dst, 8192, &P.map[ffn ? M_W1H : M_WQ], ffn ? 128 : 0, fb, k, ffn ? 48 + j : 2 * j, ffn ? 0 : 1);
  }
  __device__ __forceinline__ void finish() {
#pragma unroll 1
    for (; tail < n; tail++) mbar_wait(sb + BAR_EMPTY + ((tail & 7) << 3), (tail >> 3) & 1);
  }
  template <int PAGES> __device__ __forceinline__ uint32_t acquire(uint32_t& fb) { return acquire_n(PAGES, fb); }
  __device__ __forceinline__ uint32_t acquire_n(uint32_t PAGES, uint32_t& fb) {
    uint32_t nw = pat & 3; pat = (pat >> 2) | 0x40000000u;
#pragma unroll 1
    for (; nw; nw--) { mbar_wait(sb + BAR_EMPTY + ((tail & 7) << 3), (tail >> 3) & 1); tail++; }
    ST(4, n);
    fb = sb + BAR_FULL + ((n & 7) << 3);
    mbar_expect_tx(fb, PAGES * PAGE);
    const uint32_t a = sb + addr;
    addr += PAGES * PAGE; if (addr >= NPAGE * PAGE) addr = 0;
    n++;
    return a;
  }
  const uint32_t* flag; uint32_t base, seen;
  __device__ __forceinline__ void acquire_fence() { asm volatile("fence.acquire.gpu;" ::: "memory"); fence_async_global(); }
  __device__ __forceinline__ void next() {
    uint32_t v, spins = 0;
    seen++;
    do { asm volatile("ld.acquire.cta.shared.u32 %0, [%1];" : "=r"(v) : "r"(sb + SM_SEEN) : "memory"); spin_check(++spins >> 4); } while (v < seen);
    fence_async_global();
  }
  __device__ __forceinline__ void need(uint32_t mask) {
    if ((ready & mask) != mask) {
      uint32_t spins = 0;
      do { ready = ld_relaxed(flag) - base; spin_check(++spins); } while ((ready & mask) != mask);
      acquire_fence();
    }
    ST(5, n - 1);
  }
};

struct Cons {
  uint32_t sb, n, off, prev;
  uint32_t ebar;
  uint32_t da0, db0;
  int lane;
  template <int PAGES> __device__ __forceinline__ void advance() {
    n++; off += PAGES << 10; if (off >= (NPAGE << 10)) off = 0;
    asm volatile("" : "+r"(n), "+r"(off));
  }
  template <int BN, int PAGES> __device__ __forceinline__ void step_ab(float (&acc)[BN / 2], uint32_t da, uint32_t db, int accumulate) {
    STA();
    mbar_wait_fast(sb + BAR_FULL + ((n & 7) << 3), (n >> 3) & 1);
    STB(n);
    const uint64_t da64 = desc64(da), db64 = desc64(db);
    wgmma_fence();
#pragma unroll
    for (int k = 0; k < 4; k++) wgmma<BN>(acc, da64 + 2 * k, db64 + 128 * k, k ? 1 : accumulate);
    wgmma_commit();
    wgmma_wait<1>();
    if (prev && lane < 2) mbar_arrive_cluster(ebar + prev);
    prev = 64 + ((n & 7) << 3);
    advance<PAGES>();
  }
  template <int BN> __device__ __forceinline__ void step(float (&acc)[BN / 2], int accumulate = 1) { step_ab<BN, BN / 128 + 1>(acc, da0 + off, db0 + 1024 + off, accumulate); }
  template <int BN> __device__ __forceinline__ void step_own(float (&acc)[BN / 2], uint32_t da, int accumulate) { step_ab<BN, BN / 128>(acc, da, db0 + off, accumulate); }
  __device__ __forceinline__ void wait_full(uint32_t i) { mbar_wait_fast(sb + BAR_FULL + (((n + i) & 7) << 3), ((n + i) >> 3) & 1); }
  template <int I, int N> __device__ __forceinline__ void issue_rs(float (&acc)[64], uint32_t (&a)[16], int accumulate = 1) {
    if (I == 0) { STA(); STB(n); }
    const uint64_t db64 = desc64(db0 + off) + 1024 * I;
    wgmma_fence();
#pragma unroll
    for (int k = 0; k < 4; k++) wgmma_rs_n128(acc, a + 4 * k, db64 + 128 * k, k ? 1 : accumulate);
    if (I == N - 1) {
      wgmma_commit();
      prev = 64 + ((n & 7) << 3);
      advance<N>();
    }
  }
  template <int BN> __device__ __forceinline__ void steps(float (&acc)[BN / 2], int cnt) {
#pragma unroll 1
    do { step<BN>(acc); } while (--cnt > 0);
  }
  __device__ __forceinline__ void steps_skip(float (&acc)[64], int at) {
    int i = 0;
#pragma unroll 1
    do { if (i == at) off += 2 << 10; step<128>(acc); } while (++i < 2);
  }
  __device__ __forceinline__ void drain() {
    wgmma_wait<0>();
    if (lane < 2) mbar_arrive_cluster(ebar + prev);
    prev = 0;
  }
};

#define MAPPING 2
__device__ __forceinline__ uint32_t role_of_sm(uint32_t smid) {
  const uint32_t t = smid >> 1;
  uint32_t q, i;
  if (t < 32) { q = t & 7; i = t >> 3; }
  else if (t < 60) { const uint32_t u = t - 32, d = (u * 37) >> 8; q = 1 + u - d * 7; i = 4 + d; }
  else if (t < 62) return 128 + smid - 120;
  else { q = 0; i = t - 58; }
  return (q * 2 + (smid & 1)) * 8 + i;
}

template <typename T> __device__ __forceinline__ T* scratch(const Params& P, uint32_t off) { return (T*)ptr_add(P.scratch, off); }
__device__ __forceinline__ uint32_t* epoch_ptr(const Params& P) { uint32_t b; asm volatile("mov.u32 %0, %%ctaid.x;" : "=r"(b)); return scratch<uint32_t>(P, G_EPOCH + b * 4u); }

__device__ __forceinline__ int o_chunk(int s, int j) { const int hf = s >= 9, m = s - 2 - 7 * hf; return s < 2 ? 2 * j + s : 2 * (m == j ? 7 : m) + hf; }

__global__ void __cluster_dims__(2, 1, 1) __launch_bounds__(384, 1) fused_kernel(const __grid_constant__ Params P) {
  extern __shared__ __align__(1024) uint8_t smem_raw[];
  SP(0);
  const uint32_t sb = __shfl_sync(0xffffffffu, smem_u32(smem_raw), 0);
  const int warp = __shfl_sync(0xffffffffu, threadIdx.x >> 5, 0);
  const int lane = threadIdx.x & 31;
  if (warp == 7 && elect_one()) { prefetch_map(&P.map[M_XIN64]); prefetch_map(&P.map[M_WKV]); prefetch_map(&P.map[M_XIN]); }
  uint32_t role = blockIdx.x < 128 ? ((blockIdx.x >> 4) * 2 + (blockIdx.x & 1)) * 8 + ((blockIdx.x >> 1) & 7) : blockIdx.x;
  if (P.use_smid) { uint32_t smid; asm volatile("mov.u32 %0, %%smid;" : "=r"(smid)); role = role_of_sm(smid); }
  const bool spare = role >= 128;
  const int g = role >> 3, j = role & 7;
  uint32_t rank; asm("mov.u32 %0, %%cluster_ctarank;" : "=r"(rank));
  auto shared_b = [&]() {
    uint32_t peer;
    asm volatile("ld.shared::cluster.u32 %0, [%1];" : "=r"(peer) : "r"(mapa(sb + SM_ROLE, rank ^ 1)) : "memory");
    return !spare && peer < 128 && (peer & 7) == (uint32_t)j;
  };
  SP(1);

  if (warp >= 8) {
    asm volatile("setmaxnreg.dec.sync.aligned.u32 40;");
    if (elect_one()) {
      if (warp == 8) {
#pragma unroll
        for (int i = 0; i < 6; i++) mbar_init(sb + BAR_FULL + 8 * i, 1);
        mbar_init(sb + BAR_XIN, 1); mbar_init(sb + BAR_XIN + 8, 1);
      } else if (warp == 9) {
#pragma unroll
        for (int i = 0; i < 8; i++) mbar_init(sb + BAR_EMPTY + 8 * i, 16);
      } else if (warp == 10) {
#pragma unroll
        for (int i = 0; i < 4; i++) mbar_init(sb + BAR_SFULL + 8 * i, 4);
        mbar_init(sb + BAR_CLR, 1); mbar_init(sb + BAR_FULL + 48, 1); mbar_init(sb + BAR_FULL + 56, 1);
      } else {
        sts128(sb + SM_ROLE, role, 0, 0, 0);
        mbar_init(sb + BAR_TAG, 1); mbar_init(sb + BAR_XFULL, 8); mbar_init(sb + BAR_CSE, 8);
        mbar_init(sb + BAR_SEMPTY, 1); mbar_init(sb + BAR_CSF, 1); mbar_init(sb + BAR_CSF + 8, 2);
      }
      asm volatile("fence.mbarrier_init.release.cluster;\nfence.release.sync_restrict::shared::cta.cluster;" ::: "memory");
      fence_async_smem();
    }
    __syncwarp();
    SP(2);
    asm volatile("barrier.cluster.arrive.relaxed.aligned;" ::: "memory");
    if (warp == 8 && !spare) {
      if (elect_one()) {
        const int par = g & 1, row = (g >> 1) * 128;
#pragma unroll 1
        for (int s = 0; s < 2; s++) {
          const uint32_t xb = sb + BAR_XIN + 8 * s, fb = sb + BAR_FULL + 8 * s;
          mbar_expect_tx(xb, PAGE); mbar_expect_tx(fb, 2 * PAGE);
#pragma unroll
          for (int h = 0; h < 2; h++) tma_ld3(sb + SM_STAGE + h * PAGE + s * 8192, &P.map[M_XIN64], xb, s * 64, par, row + h * 64);
#pragma unroll
          for (int h = 0; h < 2; h++) tma_ld3(sb + (2 * s + h) * PAGE, &P.map[M_WKV], fb, 0, s * 64, 16 + 16 * h + 2 * j);
        }
#pragma unroll 1
        for (int s = 0; s < 2; s++) {
          const uint32_t fb = sb + BAR_FULL + 16 + 8 * s;
          mbar_expect_tx(fb, PAGE);
          tma_ld3(sb + (4 + s) * PAGE, &P.map[M_WKV], fb, 0, s * 64, 2 * j);
        }
#pragma unroll 1
        for (int s = 0; s < 2; s++) {
          const uint32_t fb = sb + BAR_FULL + 32 + 8 * s, a = sb + (6 + 3 * s) * PAGE;
          const int k = (j == 1 ? 4 : 2) + s;
          mbar_expect_tx(fb, 3 * PAGE);
          tma_ld3(a, &P.map[M_XIN], fb, k * 64, par, row);
#pragma unroll
          for (int h = 0; h < 2; h++) tma_ld3(a + PAGE + h * PAGE, &P.map[M_WKV], fb, 0, k * 64, 16 + 16 * h + 2 * j);
        }
        spin_check((sb & 1023) << 22);
      }
      __syncwarp();
    }
    SP(3);
    asm volatile("barrier.cluster.wait.acquire.aligned;" ::: "memory");
    SP(4);
    if (warp == 8) {
      if (elect_one()) {
        Prod p; p.sb = sb; p.n = 0; p.tail = 0; p.ready = 0; p.addr = 0;
        { const bool mc = shared_b(); p.rank = rank; p.flip = !mc; p.mask = mc ? 3 : 1 << rank; }
        uint32_t fb;
        if (spare) {
          p.pat = 0x55555000u;
#pragma unroll 1
          for (int r = -1; r < 7; r++) {
            const int ch = r < 0 ? 4 * j : ((r < 2 ? r : r == 2 ? 6 : r - 1) * 4 + j) * 2;
#pragma unroll 1
            for (int k = 0; k < 16; k++) { const uint32_t a = p.acquire<2>(fb); p.load_b(a, PAGE, &P.map[r < 0 ? M_WKV : M_W1], r < 0 ? 0 : 128, fb, k, ch, r < 0 ? 2 : 0); }
          }
        } else {
          p.seen = 0;
          const int xpar = g & 1, xrow = (g >> 1) * 128;
          SP(5);
#pragma unroll 1
          for (int hl = 0; hl < 4; hl++) {
            const int ffn = hl & 1;
            const CUtensorMap* xmap = &P.map[hl ? M_OUT_LD : M_XIN];
            if (hl) {
              p.pat = ffn ? Pat<3>::v : Pat<8>::v;
#pragma unroll 1
              for (int s = 0; s < 2; s++) { const uint32_t a = p.acquire<2>(fb); p.load_wide(P, ffn, a, fb, 2 * j + s, 2 * j); }
#pragma unroll 1
              for (int s = 0; s < 2; s++) { const uint32_t a = p.acquire<1>(fb); p.load_narrow(P, ffn, a, fb, 2 * j + s, j); }
            } else { p.pat = (Pat<0>::v >> 12) | 0x55500000u; p.addr = 0; p.n = 6; }
            if (hl == 0) SP(6);
            uint32_t fb0 = 0;
#pragma unroll 1
            for (int m = hl ? 0 : 2; m < 14; m++) {
              const int hf = m >= 7, mm = m - 7 * hf, jj = mm == j ? 7 : mm;
              int k = 2 * jj + hf;
              if (hl == 0) {
                const int pr = (m >> 1) + 1;
                k = 2 * (j && pr == 2 ? j : pr == j ? 2 : pr) + (m & 1);
              }
              const uint32_t a = p.acquire<3>(fb);
              p.load_wide(P, ffn, a + PAGE, fb, k, 2 * j);
              if (hl) {
                if (m == 0) { fb0 = fb; continue; }
                if (m == 1) {
                  const int j0 = j ? 0 : 7;
                  p.flag = scratch<uint32_t>(P, g * G_BLOCK + G_FLAGS + (ffn ? (hl >> 1) * EV_N + EV_XA : EV_XB) * 128);
                  p.ready = 0; p.need((1u << j0) | (1u << j));
                  tma_ld3(a - 3 * PAGE, xmap, fb0, j0 * 128, xpar, xrow);
                }
                if (m < 7) p.need(1u << jj); else if (m == 7) p.next();
              }
              tma_ld3(a, xmap, fb, k * 64, xpar, xrow);
            }
            if (hl == 0) { mbar_wait(sb + BAR_TAG, 0); asm volatile("ld.shared.u32 %0, [%1];" : "=r"(p.base) : "r"(sb + SM_TAG) : "memory"); p.base = (p.base - 1) * 255; }
            p.pat = ffn ? Pat<4>::v : Pat<1>::v;
#pragma unroll 1
            for (int m = 0; m < 14; m++) {
              const int k = (m >> 1) == (hl ? j : 0) ? 14 + (m & 1) : m;
              if (ffn && m == 8) p.addr += 2 * PAGE;
              const uint32_t a = p.acquire<2>(fb);
              p.load_narrow(P, ffn, a + PAGE, fb, k, j);
              tma_ld3(a, xmap, fb, k * 64, xpar, xrow);
            }
            if (!ffn) {
              p.pat = Pat<2>::v;
              uint32_t a = 0;
#pragma unroll 1
              for (int s = 0; s < 16; s++) {
                if ((0x4925 >> s) & 1) a = p.acquire_n(s == 0 || s == 14 ? 2 : 3, fb); else a += PAGE;
                p.load_b(a, 8192, &P.map[M_WO], 0, fb, o_chunk(s, j), 2 * j, 1);
              }
              p.addr += 2 * PAGE;
              a = p.acquire<2>(fb);
              tma_ld3(a, xmap, fb, j * 128, xpar, xrow); tma_ld3(a + PAGE, xmap, fb, j * 128 + 64, xpar, xrow);
            } else {
              p.pat = Pat<5>::v;
#pragma unroll 1
              for (int s = 16; s < 48; s++) {
                const int pi = (s >> 1) & 7;
                const int k = (s < 32 ? pi : pi == 4 ? j : pi == j ? 4 : pi) * 2 + (s & 1);
                const uint32_t a = p.acquire<3>(fb);
                p.load_wide(P, 1, a + PAGE, fb, k, (s & 48) + 2 * j);
                tma_ld3(a, xmap, fb, k * 64, xpar, xrow);
              }
              p.pat = Pat<6>::v;
#pragma unroll 1
              for (int q = 0; q < 4; q++) {
                p.next();
                const int k0 = q == 0 ? 0 : q == 1 ? 48 : q * 16 - 16, k1 = k0 + (q == 1 ? 8 : 16);
#pragma unroll 1
                for (int k = k0; k < k1; k++) {
                  if (k == 24) { p.addr = 0; p.pat = Pat<7>::v; }
                  const uint32_t a = p.acquire<2>(fb);
                  p.load_b(a + PAGE, 8192, &P.map[M_W2], 0, fb, k, 2 * j, 1);
                  tma_ld3(a, &P.map[M_H_LD], fb, k * 64, g, 0);
                }
              }
            }
            TL(2, 1 + hl);
          }
        }
        p.finish();
      }
    } else if (!spare) {
      mbar_wait(sb + BAR_XIN, 0);
      if (elect_one()) {
#pragma unroll 1
        for (int i = warp - 9; i < 8; i += 3) prefetch_l2(ptr_add(P.wqkv, (i * 128 + role) * 6144u + 2048u), 4096);
      }
      uint32_t tag;
      {
        const uint32_t part = warp - 9, col = DM + role * 16 + (lane & 1) * 8;
        const int cnt = part ? 21 : 22;
        const uint4* wp = ptr_add((const uint4*)P.wqkv, ((part ? 16 + part * 336 : 0) + (lane >> 1)) * 6144u + col * 2);
        float s[8] = {0, 0, 0, 0, 0, 0, 0, 0};
        uint4 v[4];
#pragma unroll
        for (int i = 0; i < 4; i++) v[i] = ld_relaxed4(wp + i * (16 * 6144 / 16));
        tag = ld_relaxed(epoch_ptr(P)) + 1;
        if (warp == 10 && lane == 0) { asm volatile("st.shared.u32 [%0], %1;" :: "r"(sb + SM_TAG), "r"(tag) : "memory"); mbar_arrive(sb + BAR_TAG); }
#pragma unroll 1
        for (int b = 4; b < 28; b += 4) {
          wp += 64 * 6144 / 16;
#pragma unroll
          for (int i = 0; i < 4; i++) {
            s[0] += bf_lo(v[i].x); s[1] += bf_hi(v[i].x); s[2] += bf_lo(v[i].y); s[3] += bf_hi(v[i].y);
            s[4] += bf_lo(v[i].z); s[5] += bf_hi(v[i].z); s[6] += bf_lo(v[i].w); s[7] += bf_hi(v[i].w);
            v[i] = make_uint4(0, 0, 0, 0);
            if (b + i < cnt) v[i] = __ldcg(wp + i * (16 * 6144 / 16));
          }
        }
#pragma unroll
        for (int e = 0; e < 4; e++) { const bool h = lane & 16; const float t = __shfl_xor_sync(0xffffffffu, h ? s[e] : s[e + 4], 16); s[e] = (h ? s[e + 4] : s[e]) + t; }
#pragma unroll
        for (int e = 0; e < 2; e++) { const bool h = lane & 8; const float t = __shfl_xor_sync(0xffffffffu, h ? s[e] : s[e + 2], 8); s[e] = (h ? s[e + 2] : s[e]) + t; }
        { const bool h = lane & 4; const float t = __shfl_xor_sync(0xffffffffu, h ? s[0] : s[1], 4); s[0] = (h ? s[1] : s[0]) + t; }
        s[0] += __shfl_xor_sync(0xffffffffu, s[0], 2);
        if (!(lane & 2) || part == 0) st_relaxed(scratch<uint32_t>(P, G_CS + (col + (lane >> 2)) * 16 + ((lane & 2) ? 3 : part) * 4), tagf((lane & 2) ? 0.f : s[0], tag));
        __syncwarp();
      }
      if (warp == 11 && lane == 0) TL(2, 30);
      {
        const uint32_t cspos = sb + SM_CS + ((lane & 16) + ((lane >> 1) & 3) * 4 + ((lane >> 3) & 1) * 2 + (lane & 1)) * 4;
#pragma unroll 1
        for (int it = 0; it < (warp == 10 ? 8 : 1); it++) {
          const int t = it & 3;
          if (it) mbar_wait(sb + BAR_CSE, (it - 1) & 1);
          if (t == 1) mbar_wait(sb + BAR_SEMPTY, 0);
#pragma unroll 1
          for (int b = it ? 0 : warp - 9; b < (it == 0 ? warp - 8 : t < 2 ? 3 : 2); b++) {
            uint32_t c0, c1;
            if (b < 2) { c0 = (t ? 2048 + t * 1024 + b * FF : 1024 + b * 1024) + j * 128; c1 = c0 + 64; }
            else if (t) { c0 = 6144 + j * 64; c1 = c0 + FF; }
            else { c0 = j * 128; c1 = c0 + 64; }
            const uint4* p0 = scratch<uint4>(P, G_CS + (c0 + lane) * 16u);
            const uint4* p1 = scratch<uint4>(P, G_CS + (c1 + lane) * 16u);
            uint4 v[4]; uint32_t spins = 0; bool ok;
            do {
              if (spins) __nanosleep(200);
              v[0] = ld_relaxed4(p0); v[1] = ld_relaxed4(p0 + 32); v[2] = ld_relaxed4(p1); v[3] = ld_relaxed4(p1 + 32);
              ok = tag_ok4(v[0], tag) && tag_ok4(v[1], tag) && tag_ok4(v[2], tag) && tag_ok4(v[3], tag);
              spin_check(++spins);
            } while (__any_sync(0xffffffffu, !ok));
#pragma unroll
            for (int m = 0; m < 4; m++) sts32f(cspos + b * 512 + m * 128, (untag(v[m].x) + untag(v[m].y)) + (untag(v[m].z) + untag(v[m].w)));
            __syncwarp();
            if (lane == 0) mbar_arrive(sb + BAR_CSF + (b ? 8 : 0));
          }
          if (lane == 0) { if (t >= 2) mbar_arrive(sb + BAR_CSF + 8); TL(2, 16 + it + (warp == 11 ? 8 : warp == 9 ? 9 : 0)); }
          if (t == 3) {
            if (g >= 2) {
              uint4* op = scratch<uint4>(P, G_HALO + (((it >> 2) * 16 + g - 2) * 8 + j) * 4096u + lane * 16u);
#pragma unroll 1
              for (int i = 0; i < 8; i++) { st_b128(op, 0, 0, 0, 0); op += 32; }
            }
          }
        }
      }
      if (warp == 11) {
        if (elect_one()) prefetch_l2(ptr_add(P.wo, role * 16384u), 16384);
        uint32_t* const fl = scratch<uint32_t>(P, g * G_BLOCK + G_FLAGS);
        uint32_t seen = 0;
#pragma unroll 1
        for (int e = EV_XA; e < EV_N + EV_XB; e++) {
          if (e == EV_XB) continue;
          const bool clr = (e & 7) == EV_XA;
          uint32_t* const f = ptr_add(fl, (clr ? 16 + e : e) * 128u);
          if (clr) {
            uint4* op = scratch<uint4>(P, g * G_BLOCK + G_O + j * 32768u + lane * 16u);
#pragma unroll 1
            for (int i = 0; i < 64; i++) { st_b128(op, 0, 0, 0, 0); op += 32; if (e || (i & 1)) __nanosleep(10); }
            __syncwarp();
            if (lane == 0) red_release(f, 1u << j);
          }
          uint32_t spins = 0, m;
          while ((m = ld_relaxed(f) - (tag - 1) * 255) != 255) { __nanosleep(m ? 50 : 500); spin_check(++spins); }
          asm volatile("fence.acquire.gpu;" ::: "memory");
          if (lane == 0) {
            if (clr) mbar_arrive(sb + BAR_CLR);
            else asm volatile("st.release.cta.shared.u32 [%0], %1;" :: "r"(sb + SM_SEEN), "r"(++seen) : "memory");
          }
          if (e == EV_H3) {
#pragma unroll 1
            for (int i = 0; i < 7; i++) { if (elect_one()) prefetch_l2(ptr_add(P.w2, (i * 128 + role) * 8192u), 8192); __nanosleep(500); }
          }
          __syncwarp();
        }
      } else if (warp == 9) {
        if (elect_one()) {
          prefetch_map(&P.map[M_WQ]); prefetch_map(&P.map[M_OUT_LD]); prefetch_map(&P.map[M_WO]); prefetch_map(&P.map[M_W1 + rank]);
          prefetch_map(&P.map[M_H_ST]); prefetch_map(&P.map[M_H_LD]); prefetch_map(&P.map[M_W1H + rank]); prefetch_map(&P.map[M_W2]); prefetch_map(&P.map[M_OUT_ST]);
          uint32_t* fl = scratch<uint32_t>(P, g * G_BLOCK + G_FLAGS);
          int pe = 0;
#pragma unroll 1
          for (int e = 0; e < 2 * EV_N; e++) {
            const int q = e & 7;
            const bool is_h = q >= EV_H0 && q < EV_XB, last = e >= EV_N + EV_XB;
            const CUtensorMap* map = &P.map[is_h ? M_H_ST : M_OUT_ST];
            const int col = q == EV_H3 ? 3072 - 64 + j * 64 : (q == EV_H1 ? 1024 : q == EV_H2 ? 2048 : 0) + j * 128;
            const int row = is_h ? 0 : (g >> 1) * 128, par = is_h ? g : g & 1;
#pragma unroll 1
            for (int hb = is_h ? q == EV_H3 : q & 1; hb <= (is_h ? 1 : q & 1); hb++) {
#pragma unroll
              for (int w = 0; w < 2; w++) {
                const bool sw = last;
                const int wg = sw ? hb : w, h = sw ? w : hb, p = sw ? pe - hb + w : pe;
                mbar_wait(sb + BAR_SFULL + 16 * wg + 8 * (p & 1), (p >> 1) & 1);
                if (w == 0) TL(3, 20 + e);
                tma_st3(map, sb + SM_STAGE + wg * PAGE + h * 8192, col + h * 64, par, row + wg * 64);
              }
              pe++;
            }
            bulk_commit();
            if (e != EV_N + EV_XB) bulk_wait<0>();
            TL(3, 40 + e);
            if (is_h || (q & 1)) mbar_arrive(sb + BAR_SEMPTY);
            if (!last) red_release(fl, 1u << j);
            TL(3, e);
            fl += 32;
          }
          *epoch_ptr(P) = tag;
        }
      }
    }
  } else {
    if (!spare) {
      if (warp == 0) asm volatile("prefetch.global.L2 [%0];" :: "l"(ptr_add(P.x, (2 * ((g >> 1) * 128 + j * 16 + (lane >> 1)) + (g & 1)) * 2048u + (lane & 1) * 128u)));
      else if (warp < 3 && (warp == 1 || lane < 16)) asm volatile("prefetch.global.L2 [%0];" :: "l"(ptr_add(P.wqkv, role * 6144u + (warp - 1) * 4096u + lane * 128u)));
      __syncwarp();
    }
    asm volatile("barrier.cluster.arrive.relaxed.aligned;" ::: "memory");
    asm volatile("setmaxnreg.inc.sync.aligned.u32 232;");
    SP(4);
    asm volatile("barrier.cluster.wait.acquire.aligned;" ::: "memory");
    SP(5);
    const int wg = warp >> 2;
    const int quad = lane & 3, gr = lane >> 2;
    Cons c; c.sb = sb; c.n = 0; c.off = 0; c.prev = 0; c.lane = lane;
    c.ebar = mapa(sb + BAR_EMPTY - 64, shared_b() ? lane & 1 : rank);
    const uint32_t stage = sb + SM_STAGE + wg * PAGE;
    const uint32_t dstage = desc_lo(stage, 16);
    if (spare) {
      const uint32_t tag = ld_relaxed(epoch_ptr(P)) + 1;
      const int tid = threadIdx.x & 127;
#pragma unroll
      for (int i = 0; i < 4; i++) sts128(stage + (i * 128 + tid) * 16, 0x3f803f80u, 0x3f803f80u, 0x3f803f80u, 0x3f803f80u);
      fence_async_smem();
      bar_sync(2 + wg, 128);
      c.db0 = desc_lo(sb + wg * PAGE, 8192);
#pragma unroll 1
      for (int r = -1; r < 7; r++) {
        float acc[64];
#pragma unroll 1
        for (int k = 0; k < 16; k++) c.step_ab<128, 2>(acc, dstage, c.db0 + c.off, k);
        c.drain();
        acc_fence<64>(acc);
        {
          float v = 0;
#pragma unroll
          for (int i = 0; i < 32; i++) asm("{\n.reg .pred p;\nsetp.eq.u32 p, %2, %3;\nselp.f32 %0, %1, %0, p;\n}" : "+f"(v) : "f"(acc[4 * (i >> 1) + (i & 1)]), "r"(tid >> 2), "r"(i));
          st_b128(scratch<uint4>(P, G_CS + (uint32_t)((r < 0 ? j * 256 + wg * 128 : 3 * DM + wg * FF + ((r < 2 ? r : r == 2 ? 6 : r - 1) * 4 + j) * 128) + (tid >> 3) * 8 + quad * 2 + (gr & 1)) * 16u),
                  tagf(v, tag), tag & 15u, tag & 15u, tag & 15u);
        }
        __syncwarp();
      }
      if (wg == 0) {
        const uint32_t* p = scratch<uint32_t>(P, (tid >> 3) * G_BLOCK + G_STATS + (tid & 7) * 8u);
        uint32_t spins = 0;
        while (__any_sync(0xffffffffu, (ld_relaxed(p) ^ tag) & 15u)) spin_check(++spins);
      }
      bar_sync(1, 256);
      if (threadIdx.x == 0) *epoch_ptr(P) = tag;
    } else {
    c.da0 = desc_lo(sb + wg * 8192, 16); c.db0 = desc_lo(sb, 8192);
    uint32_t sphase = 1, sfull = sb + BAR_SFULL + 16 * wg;
    const uint32_t maddr = stage + ((warp & 3) * 16 + (lane & 15)) * 128 + (((lane >> 4) ^ (lane & 7)) << 4);
    const uint32_t csaddr = sb + SM_CS + quad * 16;
    float st[8] = {0, 0, 0, 0, 0, 0, 0, 0};
    float* const mean = st; float* const rstd = st + 2;
    SP(6);

    auto stage_wait = [&]() { mbar_wait_fast(sb + BAR_SEMPTY, sphase); sphase ^= 1; };
    auto stage_publish = [&]() { fence_async_smem(); __syncwarp(); if (lane == 0) mbar_arrive(sfull); sfull ^= 8; };
    auto cs_load = [&](uint32_t (&cs)[16], int grp) {
#pragma unroll
      for (int i = 0; i < 4; i++) lds128(csaddr + grp * 256 + i * 64, cs[4 * i], cs[4 * i + 1], cs[4 * i + 2], cs[4 * i + 3]);
    };
    auto cs_apply = [&](float* acc, uint32_t (&cs)[16]) {
      acc_fence<32>(acc);
#pragma unroll
      for (int b = 0; b < 8; b++) {
        acc[4 * b] -= mean[0] * __uint_as_float(cs[2 * b]); acc[4 * b + 1] -= mean[0] * __uint_as_float(cs[2 * b + 1]);
        acc[4 * b + 2] -= mean[1] * __uint_as_float(cs[2 * b]); acc[4 * b + 3] -= mean[1] * __uint_as_float(cs[2 * b + 1]);
      }
      acc_fence<32>(acc);
    };
    auto glu_pair = [&](float g0, float g1, float u0, float u1, int r) {
      const float nl = -LOG2E * rstd[r], r2 = rstd[r] * rstd[r];
      return pack_bf16(g0 * u0 * r2 * rcp(1.0f + ex2(g0 * nl)), g1 * u1 * r2 * rcp(1.0f + ex2(g1 * nl)));
    };
    auto glu_slice = [&](uint32_t (&pk)[64], int i) {
      uint32_t hp[4];
#pragma unroll
      for (int e = 0; e < 4; e++) {
        asm volatile("" : "+r"(pk[4 * i + e]), "+r"(pk[32 + 4 * i + e]));
        const uint32_t pg = pk[4 * i + e], pu = pk[32 + 4 * i + e];
        hp[e] = glu_pair(bf_lo(pg), bf_hi(pg), bf_lo(pu), bf_hi(pu), e & 1);
      }
      stsm4((maddr ^ ((i & 3) << 5)) + (i >> 2) * 8192, hp[0], hp[1], hp[2], hp[3]);
    };
    auto glu_slice_acc = [&](float (&acc)[128], int i) {
      uint32_t hp[4];
      acc_fence<8>(acc + 8 * i);
#pragma unroll
      for (int e = 0; e < 4; e++) hp[e] = glu_pair(acc[8 * i + 2 * e], acc[8 * i + 2 * e + 1], acc[64 + 8 * i + 2 * e], acc[64 + 8 * i + 2 * e + 1], e & 1);
      stsm4((maddr ^ ((i & 3) << 5)) + (i >> 2) * 8192, hp[0], hp[1], hp[2], hp[3]);
    };
    auto stage_x = [&](uint32_t (&x)[32], int hf) {
#pragma unroll
      for (int i = 4 * hf; i < 4 * hf + 4; i++) stsm4((maddr ^ ((i & 3) << 5)) + hf * 8192, x[4 * i], x[4 * i + 1], x[4 * i + 2], x[4 * i + 3]);
    };

    float acc[128];
    mbar_wait_fast(sb + BAR_XIN, 0);
    SP(7);
    c.step_own<256>(acc, dstage, 0);
    mbar_wait_fast(sb + BAR_XIN + 8, 0);
    SP(8);
#pragma unroll 1
    for (int hl = 0;; hl++) {
      int t = hl & 1;
      float acc2[64];
      uint32_t res[32];
      c.step_own<256>(acc, dstage + 512, 1);
#pragma unroll
      for (int s = 0; s < 2; s++) c.step_own<128>(acc2, dstage + s * 512, s);
#pragma unroll 1
      for (int s = 2; s < 11; s++) {
        const uint32_t apage = (c.off << 4) - (SM_STAGE + wg * 8192);
        c.step<256>(acc);
        int act = s;
        asm volatile("" : "+r"(act));
        auto get_tag = [&]() { uint32_t tag; asm volatile("ld.shared.u32 %0, [%1];" : "=r"(tag) : "r"(sb + SM_TAG) : "memory"); return tag; };
        auto stat_ptr = [&]() { return scratch<uint2>(P, g * G_BLOCK + G_STATS + (hl * 128 + warp * 16 + (lane_now() >> 2)) * 64u); };
        auto stat_get = [&]() {
          const uint2* sp = ptr_add(stat_ptr(), (lane_now() & 3) * 16);
          const uint4 a = ld_relaxed4(sp), b = ld_relaxed4(sp + 64);
          st[0] = __uint_as_float(a.x); st[1] = __uint_as_float(a.y); st[2] = __uint_as_float(a.z); st[3] = __uint_as_float(a.w);
          st[4] = __uint_as_float(b.x); st[5] = __uint_as_float(b.y); st[6] = __uint_as_float(b.z); st[7] = __uint_as_float(b.w);
        };
        switch (act) {
          case 4: case 5: {
            const uint32_t ra = maddr + ((hl || j == 0) ? (s & 1) * 8192 : apage);
#pragma unroll
            for (int i = 0; i < 4; i++) {
              uint32_t v[4];
              ldsm4(ra ^ (i << 5), v[0], v[1], v[2], v[3]);
              if (i == 0 && s == 4) { st[0] = bf_lo(v[0]); st[1] = bf_lo(v[1]); st[2] = st[3] = st[4] = st[5] = 0; }
#pragma unroll
              for (int e = 0; e < 4; e++) {
                const float a = bf_lo(v[e]) - st[e & 1], b = bf_hi(v[e]) - st[e & 1];
                st[2 + (e & 1)] += a + b; st[4 + (e & 1)] += a * a; st[4 + (e & 1)] += b * b;
              }
            }
          } break;
          case 6: {
            mbar_wait_fast(sb + BAR_TAG, 0);
            const uint32_t tag = get_tag();
#pragma unroll
            for (int r = 0; r < 2; r++) {
              const float mt = st[r] + st[2 + r] * (1.0f / 32);
              float m = mt + __shfl_xor_sync(0xffffffffu, mt, 1); m += __shfl_xor_sync(0xffffffffu, m, 2); m *= 0.25f;
              float q = st[4 + r] - st[2 + r] * st[2 + r] * (1.0f / 32) + 32.0f * (mt - m) * (mt - m);
              q += __shfl_xor_sync(0xffffffffu, q, 1); q += __shfl_xor_sync(0xffffffffu, q, 2);
              if (quad == 0) st_relaxed2(ptr_add(stat_ptr(), r * 512 + j * 8), tagf(m, tag), tagf(q, tag));
            }
          } break;
          case 8: stat_get(); break;
          case 10: {
            const uint32_t tag = get_tag();
            uint32_t spins = 0;
            for (;;) {
              uint32_t bad = 0;
#pragma unroll
              for (int i = 0; i < 8; i++) bad |= __float_as_uint(st[i]) ^ tag;
              if (!__any_sync(0xffffffffu, bad & 15u)) break;
              stat_get(); spin_check(++spins);
            }
            float mr[4];
#pragma unroll
            for (int r = 0; r < 2; r++) {
              const float m0 = untag(__float_as_uint(st[4 * r])), m1 = untag(__float_as_uint(st[4 * r + 2]));
              float m = m0 + m1; m += __shfl_xor_sync(0xffffffffu, m, 1); m += __shfl_xor_sync(0xffffffffu, m, 2); m *= 0.125f;
              float q = untag(__float_as_uint(st[4 * r + 1])) + untag(__float_as_uint(st[4 * r + 3])) + 128.0f * ((m0 - m) * (m0 - m) + (m1 - m) * (m1 - m));
              q += __shfl_xor_sync(0xffffffffu, q, 1); q += __shfl_xor_sync(0xffffffffu, q, 2);
              mr[r] = m; mr[2 + r] = rsqrtf(fmaxf(q, 0.f) * (1.0f / DM) + LN_EPS);
            }
            st[0] = mr[0]; st[1] = mr[1]; st[2] = mr[2]; st[3] = mr[3];
          } break;
          default: break;
        }
      }
#pragma unroll 1
      for (;;) {
      const int it = (hl >> 1) * 4 + t;
#pragma unroll
      for (int s = 0; s < 4; s++) {
        uint32_t cs[16];
        c.step<256>(acc);
        if (!(s & 1)) mbar_wait_fast(sb + BAR_CSF + 4 * s, t & 1);
        if (s >= 2 && t <= 1) { cs_load(cs, 2 + s); cs_apply(acc2 + 32 * (s - 2), cs); }
        cs_load(cs, s);
        c.drain();
        cs_apply(acc + 32 * s, cs);
      }
      c.step<256>(acc);
      if (lane == 0) mbar_arrive(sb + BAR_CSE);
      c.drain();
      acc_fence<128>(acc);
      TLC(1 + it * 6);
      uint32_t pkB[64];
      if (t == 2) {
#pragma unroll
        for (int i = 0; i < 64; i++) pkB[i] = pack_bf16(acc[2 * i], acc[2 * i + 1]);
      } else if (t == 0) {
        uint32_t pkA[64];
        auto kv_pack = [&](int v, int r) {
#pragma unroll
          for (int i = 32 * v + r; i < 32 * v + 32; i += 2) { acc_fence<2>(acc + 2 * i); pkA[i] = pack_bf16(acc[2 * i] * rstd[r], acc[2 * i + 1] * rstd[r]); }
        };
        const uint32_t l16 = lane_now() * 16u;
        uint4* const xs = ptr_add((uint4*)smem_raw, SM_STAGE + l16);
        uint4* const hp = scratch<uint4>(P, G_HALO + (((hl >> 1) * 16 + g) * 8 + j) * 4096u + l16);
        {
          uint4* const dst = (warp == 7 && g < 14) ? hp : ptr_add(xs, warp * 4096u);
#pragma unroll
          for (int s = 0; s < 2; s++) {
            c.steps<128>(acc2, s ? 2 : 1 + wg);
            if (s == 0) stage_wait();
            kv_pack(s, 1);
#pragma unroll
            for (int i = 4 * s; i < 4 * s + 4; i++) { pkA[8 * i + 1] = pkt_head(pkA[8 * i + 1]); gen_store(dst + i * 32, pkA[8 * i + 1], pkA[8 * i + 3], pkA[8 * i + 5], pkA[8 * i + 7]); }
          }
        }
        __syncwarp();
        if (lane == 0) mbar_arrive(sb + BAR_XFULL);
#pragma unroll
        for (int s = 0; s < 2; s++) {
          c.steps<128>(acc2, 2);
#pragma unroll
          for (int i = 33 - s; i < 64; i += 2) pkA[i] = movm(pkA[i]);
          kv_pack(1 - s, 0);
        }
        uint32_t kvH[32];
        {
          const uint4* const src = (warp == 0 && g >= 2) ? hp - 2 * 8 * 256 : ptr_add(xs, (warp ? warp - 1 : 0) * 4096u);
          c.steps<128>(acc2, 2);
          mbar_wait_fast(sb + BAR_XFULL, hl >> 1);
#pragma unroll
          for (int i = 0; i < 8; i++) gen_load(src + i * 32, kvH + 4 * i);
          c.steps<128>(acc2, 3 - wg);
          uint32_t spins = 0;
          while (__any_sync(0xffffffffu, !(kvH[0] && kvH[4] && kvH[8] && kvH[12] && kvH[16] && kvH[20] && kvH[24] && kvH[28]))) {
#pragma unroll
            for (int i = 0; i < 8; i++) gen_load(src + i * 32, kvH + 4 * i);
            spin_check(++spins);
          }
        }
#pragma unroll
        for (int i = 16; i < 32; i++) kvH[i] = movm(kvH[i]);
        mbar_wait_fast(sb + BAR_CLR, hl >> 1);
        c.steps<128>(acc2, 2);
        AP(0);
        c.wait_full(0);
        AP(1);
        c.drain();
        AP(2);
        acc_fence<64>(acc2);
        TLC(2 + it * 6);
        uint32_t q[32];
#pragma unroll
        for (int i = 0; i < 32; i++) q[i] = pack_bf16(acc2[2 * i], acc2[2 * i + 1]);
        const uint32_t zm = bar_sync_zero(1, 256);
        AP(3);
        uint32_t ob[6][16];
        uint4* const omail = scratch<uint4>(P, g * G_BLOCK + G_O + warp * 2048u + l16);
        float o2[8][4], r2[4];
        {
          const float hv = (warp == 0 && g < 2) ? -INFINITY : 0.f;
          const float hinit[4] = {hv, hv, hv, hv};
          const bool c0 = (2 * quad <= gr), c1 = (2 * quad + 1 <= gr);
          const uint32_t lm = (c0 ? 0xffffu : 0u) | (c1 ? 0xffff0000u : 0u);
          const float sc[2] = {rstd[0] * (0.17677669529663687f * LOG2E), rstd[1] * (0.17677669529663687f * LOG2E)};
          float lg[4][4], mx[4][2];
#pragma unroll
          for (int h = 0; h < 4; h++) {
            const int b = h * 4;
            float sH[4], sL[4], sU[4];
            q[2 * b] |= zm;
            mma16816(sH, q[2 * b], q[2 * b + 1], q[2 * b + 2], q[2 * b + 3], kvH[b], kvH[b + 1], hinit);
            mma16816z(sL, q[2 * b], q[2 * b + 1], q[2 * b + 2], q[2 * b + 3], pkA[2 * b], pkA[2 * b + 2]);
            mma16816z(sU, q[2 * b], q[2 * b + 1], q[2 * b + 2], q[2 * b + 3], pkA[2 * b + 1], pkA[2 * b + 3]);
            mma16816(sH, q[2 * b + 4], q[2 * b + 5], q[2 * b + 6], q[2 * b + 7], kvH[b + 2], kvH[b + 3], sH);
            mma16816(sL, q[2 * b + 4], q[2 * b + 5], q[2 * b + 6], q[2 * b + 7], pkA[2 * b + 4], pkA[2 * b + 6], sL);
            mma16816(sU, q[2 * b + 4], q[2 * b + 5], q[2 * b + 6], q[2 * b + 7], pkA[2 * b + 5], pkA[2 * b + 7], sU);
            lg[h][0] = c0 ? sL[0] : sH[0]; lg[h][1] = c1 ? sL[1] : sH[1]; lg[h][2] = c0 ? sU[2] : sL[2]; lg[h][3] = c1 ? sU[3] : sL[3];
            mx[h][0] = fmaxf(lg[h][0], lg[h][1]); mx[h][1] = fmaxf(lg[h][2], lg[h][3]);
          }
#pragma unroll
          for (int o = 1; o < 4; o <<= 1) {
#pragma unroll
            for (int i = 0; i < 8; i++) mx[i >> 1][i & 1] = fmaxf(mx[i >> 1][i & 1], __shfl_xor_sync(0xffffffffu, mx[i >> 1][i & 1], o));
          }
          AP(4);
          uint32_t z = zm, pp[4][2];
          float rs[4][2];
          auto probs = [&](int h) {
            pp[h][0] = pack_bf16(ex2((lg[h][0] - mx[h][0]) * sc[0]), ex2((lg[h][1] - mx[h][0]) * sc[0]));
            pp[h][1] = pack_bf16(ex2((lg[h][2] - mx[h][1]) * sc[1]), ex2((lg[h][3] - mx[h][1]) * sc[1]));
            float sum[4];
            mma1688z(sum, pp[h][0], pp[h][1], 0x3f803f80u);
            rs[h][0] = rcp(sum[0]); rs[h][1] = rcp(sum[2]);
            asm volatile("" : "+f"(rs[h][0]), "+f"(rs[h][1]));
          };
          probs(0); probs(1); probs(2); probs(3);
#pragma unroll
          for (int hf = 0; hf < 2; hf++) {
#pragma unroll
            for (int hh = 0; hh < 2; hh++) {
              const int h = hf * 2 + hh, b = h * 4;
              const uint32_t pa = pp[h][0], pb = pp[h][1];
              const uint32_t p0 = pa & ~lm, p1 = pa & z, p2 = pa & lm, p3 = pb & ~lm, p4 = pb & z, p5 = pb & lm;
              const float ra = rs[h][0], rb = rs[h][1];
#pragma unroll
              for (int d = 0; d < 4; d++) {
                float o[4];
                mma16816z(o, p0, p1, p2, p3, kvH[16 + b + d], pkA[32 + 2 * (b + d)]);
                mma1688(o, p4, p5, pkA[32 + 2 * (b + d) + 1], o);
                if (hf == 0) { ob[0][(hh * 4 + d) * 2] = pack_bf16(o[0] * ra, o[1] * ra); ob[0][(hh * 4 + d) * 2 + 1] = pack_bf16(o[2] * rb, o[3] * rb); }
                else { o2[hh * 4 + d][0] = o[0]; o2[hh * 4 + d][1] = o[1]; o2[hh * 4 + d][2] = o[2]; o2[hh * 4 + d][3] = o[3]; }
              }
              if (hf) { r2[2 * hh] = ra; r2[2 * hh + 1] = rb; }
            }
            if (hf == 0) {
#pragma unroll
              for (int i = 0; i < 4; i++) ob[0][4 * i] = pkt_head(ob[0][4 * i]);
              AP(5);
              uint4* op = ptr_add(omail, j * 32768u);
#pragma unroll
              for (int i = 0; i < 4; i++) st_b128(op + i * 32, ob[0][4 * i], ob[0][4 * i + 1], ob[0][4 * i + 2], ob[0][4 * i + 3]);
              z = late_zero(zm);
              AP(6);
            }
          }
        }
        auto finish_o2 = [&](uint32_t z) {
#pragma unroll
          for (int i = 0; i < 4; i++) r2[i] = __uint_as_float(__float_as_uint(r2[i]) | z);
#pragma unroll
          for (int i = 0; i < 8; i++) {
            ob[1][2 * i] = pack_bf16(o2[i][0] * r2[(i >> 2) * 2], o2[i][1] * r2[(i >> 2) * 2]);
            ob[1][2 * i + 1] = pack_bf16(o2[i][2] * r2[(i >> 2) * 2 + 1], o2[i][3] * r2[(i >> 2) * 2 + 1]);
          }
#pragma unroll
          for (int i = 0; i < 4; i++) { ob[1][4 * i] = pkt_head(ob[1][4 * i]); sts128(stage + (warp & 3) * 2048 + i * 512 + l16, ob[1][4 * i], ob[1][4 * i + 1], ob[1][4 * i + 2], ob[1][4 * i + 3]); }
        };
        {
          uint32_t dep = __float_as_uint(r2[0]) | __float_as_uint(r2[2]);
#pragma unroll
          for (int i = 0; i < 8; i++) dep |= __float_as_uint(o2[i][3]);
          const uint32_t cnt = 256 | (dep & zm);
          AP(7);
          if (wg) { asm volatile("bar.arrive 1, %0;" :: "r"(cnt) : "memory"); bar_sync(6, 256); } else bar_sync(1, cnt);
        }
        TLC(3 + it * 6);
        AP(8);
        uint64_t todo;
        { const uint32_t o7 = 0x6543210u | (7u << (4 * j) & 0xfffffffu); todo = (uint64_t)(o7 * 2) | (uint64_t)(o7 * 2 + 0x1111111u) << 28; }
        const uint4* pf[3];
        auto next_ptrs = [&](const uint4* (&p)[3]) {
#pragma unroll
          for (int i = 0; i < 3; i++) p[i] = ptr_add(omail, (((uint32_t)todo >> (4 * i)) & 15u) << 14);
          asm volatile("" : "+l"(p[0]), "+l"(p[1]), "+l"(p[2]));
          todo >>= 12;
        };
        next_ptrs(pf);
        auto batch = [&](int b, bool first, bool three) {
          const int y = 3 - b;
          auto o_fetch = [&]() {
#pragma unroll
            for (int i = 0; i < 8; i++) pkt_load(pf[i >> 2] + (i & 3) * 32, ob[y + (i >> 2)] + 4 * (i & 3));
            if (three) {
#pragma unroll
              for (int i = 0; i < 4; i++) pkt_load(pf[2] + i * 32, ob[y + 2] + 4 * i);
            }
          };
          if (first) {
            c.issue_rs<0, 2>(acc2, ob[0], 0);
            finish_o2(late_zero(zm));
            o_fetch();
            c.issue_rs<1, 2>(acc2, ob[1]);
            if (!wg) asm volatile("bar.arrive 6, 256;" ::: "memory");
          } else {
            o_fetch();
            c.issue_rs<0, 3>(acc2, ob[b]); c.issue_rs<1, 3>(acc2, ob[b + 1]); c.issue_rs<2, 3>(acc2, ob[b + 2]);
          }
          const uint32_t z = late_zero(zm);
          const uint4* pn[3];
          next_ptrs(pn);
          c.wait_full(0);
          uint32_t spins = 0;
          for (;;) {
            bool bad[3];
#pragma unroll
            for (int i = 0; i < 3; i++) bad[i] = ob[y + i][0] == z || ob[y + i][4] == z || ob[y + i][8] == z || ob[y + i][12] == z;
            if (__builtin_expect(!__any_sync(0xffffffffu, bad[0] | bad[1] | bad[2]), 1)) break;
            o_fetch();
            spin_check(++spins);
          }
          if (first) {
            fence_async_smem();
            __syncwarp();
            if (elect_one()) {
              asm volatile("cp.async.bulk.global.shared::cta.bulk_group [%0], [%1], 2048;"
                           :: "l"(scratch<uint4>(P, g * G_BLOCK + G_O + (2 * j + 1) * 16384u + warp * 2048u)), "r"(stage + (warp & 3) * 2048) : "memory");
              bulk_commit();
            }
          }
          pf[0] = pn[0]; pf[1] = pn[1]; pf[2] = pn[2];
          c.drain();
        };
        batch(0, true, true);
#pragma unroll 1
        for (int i = 0; i < 2; i++) { batch(3, false, true); batch(0, false, i == 0); }
        c.issue_rs<0, 2>(acc2, ob[3]); c.issue_rs<1, 2>(acc2, ob[4]);
        if (elect_one()) bulk_wait<0>();
        __syncwarp();
        {
          c.off += 2 << 10;
          c.wait_full(0);
          const uint32_t ra = maddr - (SM_STAGE + wg * 8192) + (c.off << 4);
#pragma unroll
          for (int i = 0; i < 8; i++) ldsm4((ra ^ ((i & 3) << 5)) + (i >> 2) * PAGE, res[4 * i], res[4 * i + 1], res[4 * i + 2], res[4 * i + 3]);
          if (lane < 2) mbar_arrive_cluster(c.ebar + 64 + ((c.n & 7) << 3));
          c.advance<2>();
          c.drain();
        }
        break;
      } else {
        c.steps<128>(acc2, 1 + wg);
        stage_wait();
        glu_slice_acc(acc, 0);
#pragma unroll
        for (int s = 1; s < 8; s++) {
          if (s == 5) c.steps_skip(acc2, t == 1 ? 1 - wg : 2); else c.steps<128>(acc2, (s & 1) || t == 3 ? 2 : 1);
          if (s == 4) stage_publish();
          glu_slice_acc(acc, s);
        }
        c.steps<128>(acc2, 2 - wg);
        stage_publish();
        if (t == 3) {
#pragma unroll
          for (int i = 0; i < 32; i++) { res[i] = 0x80008000u; asm volatile("" : "+r"(res[i])); }
#pragma unroll 1
          for (int i = 0; i < 3; i++) {
            c.steps<128>(acc2, i == 0 ? 15 : i == 1 ? 24 - TAIL_LAG : TAIL_LAG);
            if (i == 0) c.off = 0;
            else if (hl == 3) { if (wg == 1 && i == 1) { c.drain(); bar_sync(5, 256); } else if (wg == 0 && i == 2) asm volatile("bar.arrive 5, 256;" ::: "memory"); }
          }
          stage_wait();
          c.drain();
          break;
        }
        c.drain();
        TLC(2 + it * 6);
        c.step<256>(acc, 0);
        acc_fence<64>(acc2);
#pragma unroll
        for (int i = 0; i < 16; i++) {
          pkB[16 + i] = pack_bf16(acc2[2 * i], acc2[2 * i + 1]); pkB[48 + i] = pack_bf16(acc2[32 + 2 * i], acc2[32 + 2 * i + 1]);
          pkB[i] = 0; pkB[32 + i] = 0;
        }
      }
      t++;
#pragma unroll 1
      for (int s = 3 - t; s < 8; s++) {
        c.step<256>(acc, s);
        int act = (t == 3 || s >= 4) ? s : 8;
        asm volatile("" : "+r"(act));
        if (act < 8) {
          if (!(act & 3)) { if (act && t == 3) stage_publish(); else stage_wait(); }
          auto f = [&](int i) { glu_slice(pkB, i); };
          SELECT8(act, f);
        }
      }
#pragma unroll
      for (int s = 0; s < 2; s++) {
        const uint32_t ra = maddr - (SM_STAGE + wg * 8192) + (c.off << 4);
        c.step<256>(acc);
        if (s == 0) stage_publish();
#pragma unroll
        for (int i = 0; i < 4; i++) {
          uint32_t v[4];
          ldsm4(ra ^ (i << 5), v[0], v[1], v[2], v[3]);
#pragma unroll
          for (int e = 0; e < 4; e++) { acc2[32 * s + 8 * i + 2 * e] = bf_lo(v[e]); acc2[32 * s + 8 * i + 2 * e + 1] = bf_hi(v[e]); }
        }
        acc_fence<32>(acc2 + 32 * s);
      }
      c.step<256>(acc);
      }
      const int it = (hl >> 1) * 4 + t;
      acc_fence<64>(acc2);
      TLC(4 + it * 6);
      uint32_t xn[32];
#pragma unroll
      for (int i = 0; i < 16; i++) xn[i] = add_bf16x2(res[i], pack_bf16(acc2[2 * i], acc2[2 * i + 1]));
      stage_x(xn, 0);
#pragma unroll
      for (int i = 16; i < 32; i++) { xn[i] = add_bf16x2(res[i], pack_bf16(acc2[2 * i], acc2[2 * i + 1])); asm volatile("" : "+r"(xn[i])); }
      stage_publish();
      if (hl == 3) { stage_x(xn, 1); stage_publish(); TLE(47); TLG(63); break; }
      bar_sync(2 + wg, 128);
      TLC(5 + it * 6);
      c.step_own<256>(acc, dstage, 0);
      stage_x(xn, 1);
      stage_publish();
      bar_sync(2 + wg, 128);
    }
    }
  }
}

typedef CUresult (*EncodeFn)(CUtensorMap*, CUtensorMapDataType, cuuint32_t, void*, const cuuint64_t*, const cuuint64_t*, const cuuint32_t*,
                             const cuuint32_t*, CUtensorMapInterleave, CUtensorMapSwizzle, CUtensorMapL2promotion, CUtensorMapFloatOOBfill);

void encode(EncodeFn fn, CUtensorMap* m, const void* ptr, int rank, const cuuint64_t* dims, const cuuint64_t* strides, const cuuint32_t* box) {
  cuuint32_t es[5] = {1, 1, 1, 1, 1};
  fn(m, CU_TENSOR_MAP_DATA_TYPE_BFLOAT16, rank, const_cast<void*>(ptr), dims, strides, box, es, CU_TENSOR_MAP_INTERLEAVE_NONE,
     CU_TENSOR_MAP_SWIZZLE_128B, CU_TENSOR_MAP_L2_PROMOTION_L2_128B, CU_TENSOR_MAP_FLOAT_OOB_FILL_NONE);
}

}

extern "C" void kernel_launch(void* const* d_in, const int* in_sizes, int n_in, void* d_out, int out_size) {
  const __nv_bfloat16* x = (const __nv_bfloat16*)d_in[0];
  const __nv_bfloat16* wqkv = (const __nv_bfloat16*)d_in[1];
  const __nv_bfloat16* wo = (const __nv_bfloat16*)d_in[2];
  const __nv_bfloat16* w1 = (const __nv_bfloat16*)d_in[4];
  const __nv_bfloat16* w3 = (const __nv_bfloat16*)d_in[5];
  const __nv_bfloat16* w2 = (const __nv_bfloat16*)d_in[6];

  void* fnp = nullptr; cudaDriverEntryPointQueryResult qr;
  cudaGetDriverEntryPoint("cuTensorMapEncodeTiled", &fnp, cudaEnableDefault, &qr);
  EncodeFn fn = (EncodeFn)fnp;
  void* sym;
  cudaGetSymbolAddress(&sym, g_scratch);
  uint8_t* scr = (uint8_t*)(((uintptr_t)sym + G_PAGE - 1) / G_PAGE * G_PAGE);

  Params P = {};
  { cuuint64_t d[3] = {DM, 2, SEQ / 2}, s[2] = {DM * 2, DM * 4}; cuuint32_t b[3] = {64, 1, 128}, b2[3] = {64, 1, 64};
    encode(fn, &P.map[M_XIN], x, 3, d, s, b); encode(fn, &P.map[M_XIN64], x, 3, d, s, b2);
    encode(fn, &P.map[M_OUT_LD], d_out, 3, d, s, b); encode(fn, &P.map[M_OUT_ST], d_out, 3, d, s, b2); }
  { cuuint64_t d[3] = {FF, 16, 128}, s[2] = {G_BLOCK, FF * 2}; cuuint32_t b[3] = {64, 1, 128}, b2[3] = {64, 1, 64};
    encode(fn, &P.map[M_H_LD], scr + G_H, 3, d, s, b); encode(fn, &P.map[M_H_ST], scr + G_H, 3, d, s, b2); }
  { const cuuint32_t b2[3] = {64, 64, 2}, b1[3] = {64, 64, 1};
    { cuuint64_t d[3] = {64, DM, 48}, s[2] = {3 * DM * 2, 128}; encode(fn, &P.map[M_WKV], wqkv, 3, d, s, b2); encode(fn, &P.map[M_WQ], wqkv, 3, d, s, b1); }
    { cuuint64_t d[3] = {64, DM, 16}, s[2] = {DM * 2, 128}; encode(fn, &P.map[M_WO], wo, 3, d, s, b1); }
    { cuuint64_t d[3] = {64, FF, 16}, s[2] = {DM * 2, 128}; encode(fn, &P.map[M_W2], w2, 3, d, s, b1); }
    { cuuint64_t d[3] = {64, DM, FF / 64}, s[2] = {FF * 2, 128};
      encode(fn, &P.map[M_W1], w1, 3, d, s, b2); encode(fn, &P.map[M_W3], w3, 3, d, s, b2);
      encode(fn, &P.map[M_W1H], w1, 3, d, s, b1); encode(fn, &P.map[M_W3H], w3, 3, d, s, b1); }
  }
  P.scratch = scr; P.x = x; P.wqkv = wqkv; P.wo = wo; P.w2 = w2;
  int dev = 0, sms = 0;
  cudaGetDevice(&dev);
  cudaDeviceGetAttribute(&sms, cudaDevAttrMultiProcessorCount, dev);
  P.use_smid = (sms == 132);
  cudaFuncSetAttribute(fused_kernel, cudaFuncAttributeMaxDynamicSharedMemorySize, SM_ALLOC);
  fused_kernel<<<132, 384, SM_ALLOC>>>(P);
}
```

```cpp
#include <cuda_runtime.h>
#include <cuda_bf16.h>
#include <cuda.h>
#include <stdint.h>
#include <math.h>

namespace {

constexpr int SEQ = 2048, DM = 1024, FF = 3584;
constexpr float LN_EPS = 1e-5f;
constexpr float LOG2E = 1.4426950408889634f;

#define G_SKEW 4096
constexpr uint32_t G_PAGE = 2u << 20, G_BLOCK = G_PAGE + G_SKEW;
constexpr uint32_t G_H = 0;
constexpr uint32_t G_O = G_H + 128 * FF * 2;
constexpr uint32_t G_STATS = G_O + 128 * DM * 2;
constexpr uint32_t G_FLAGS = G_STATS + 4 * 128 * 64;
static_assert(G_FLAGS + 4096 + 15 * G_SKEW <= G_PAGE, "");
constexpr uint32_t G_HALO = 16 * G_PAGE;
constexpr uint32_t G_CS = G_HALO + 2 * 16 * 8 * 4096;
constexpr uint32_t G_EPOCH = G_CS + (3 * DM + 2 * FF) * 16;
__device__ __align__(1024) uint8_t g_scratch[18 * G_PAGE];

enum { M_XIN, M_XIN64, M_H_LD, M_H_ST, M_OUT_LD, M_OUT_ST, M_WKV, M_WQ, M_WO, M_W1, M_W3, M_W1H, M_W3H, M_W2, M_COUNT };
struct alignas(64) Params {
  CUtensorMap map[M_COUNT];
  uint8_t* scratch;
  const __nv_bfloat16* x;
  const __nv_bfloat16* wqkv;
  const __nv_bfloat16* wo;
  const __nv_bfloat16* w2;
  int use_smid;
};

constexpr uint32_t PAGE = 16384, NPAGE = 12;
constexpr uint32_t SM_STAGE = NPAGE * PAGE;
constexpr uint32_t SM_BAR = SM_STAGE + 2 * PAGE;
constexpr uint32_t SM_CS = SM_BAR + 256;
constexpr uint32_t SM_TOTAL = SM_CS + 1536;
constexpr uint32_t SM_ALLOC = SM_TOTAL;
static_assert(SM_ALLOC <= 232448, "shared memory");
constexpr uint32_t BAR_FULL = SM_BAR, BAR_EMPTY = SM_BAR + 64, BAR_SFULL = SM_BAR + 128;
constexpr uint32_t BAR_XFULL = SM_BAR + 160, BAR_CSE = SM_BAR + 168;
constexpr uint32_t BAR_SEMPTY = SM_BAR + 176, BAR_CSF = SM_BAR + 184, BAR_XIN = SM_BAR + 200;
constexpr uint32_t BAR_CLR = SM_BAR + 240, BAR_TAG = SM_BAR + 216, SM_ROLE = SM_BAR + 224, SM_TAG = SM_BAR + 228, SM_SEEN = SM_BAR + 232;
enum { EV_XA, EV_XA2, EV_H0, EV_H3, EV_H1, EV_H2, EV_XB, EV_XB2, EV_N };

struct Sched { uint32_t pat[16]; uint32_t page0[16]; bool ok; };
constexpr int seg_steps(int seg) { return seg == 0 || seg == 3 ? 18 : seg == 1 || seg == 4 ? 14 : seg == 2 ? 7 : seg == 7 ? 24 : 32; }
constexpr int step_pages(int seg, int i) {
  return seg == 0 || seg == 3 ? (i < 2 ? 2 : i < 4 ? 1 : 3) : seg == 5 || (seg == 2 && i >= 1 && i <= 4) ? 3 : 2;
}
constexpr Sched make_sched() {
  Sched s = {};
  int owner[NPAGE] = {-1, -1, -1, -1, -1, -1, -1, -1, -1, -1, -1, -1};
  int n = 0, tail = 0, page = 0;
  s.ok = true;
  for (int sg = 0; sg < 16; sg++) {
    const int seg = sg % 8;
    s.page0[sg] = page;
    for (int i = 0; i < seg_steps(seg); i++) {
      const int p = step_pages(seg, i);
      if ((seg == 2 && i == 6) || (seg == 4 && i == 8) || (seg == 7 && i == 0)) page = (page + 2) % NPAGE;
      if (page + p > (int)NPAGE) { s.ok = false; return s; }
      int need = n - 8;
      for (int q = 0; q < p; q++) { if (owner[page + q] > need) need = owner[page + q]; owner[page + q] = n; }
      int nw = need + 1 - tail; if (nw < 0) nw = 0;
      tail += nw;
      if (i < 16) s.pat[sg] |= (uint32_t)nw << (2 * i); else if (nw != 1) s.ok = false;
      if (nw > 3) s.ok = false;
      page = (page + p) % NPAGE; n++;
    }
  }
  for (int sg = 0; sg < 8; sg++) if (s.page0[sg] != s.page0[sg + 8] || (sg && s.pat[sg] != s.pat[sg + 8])) s.ok = false;
  return s;
}
constexpr Sched SCHED = make_sched();
static_assert(SCHED.ok && SCHED.page0[0] == 0 && SCHED.page0[3] == 0 && SCHED.page0[5] == 6 && SCHED.page0[2] == 4 && SCHED.page0[7] == 10 && (SCHED.pat[0] & 0xfff) == 0, "ring schedule");
template <int SEG> struct Pat { static constexpr uint32_t v = SCHED.pat[SEG]; };

#define TAIL_LAG 3
#define LAG_ALL 1
__device__ __forceinline__ uint32_t smem_u32(const void* p) { return (uint32_t)__cvta_generic_to_shared(p); }
__device__ __forceinline__ void mbar_init(uint32_t bar, uint32_t cnt) { asm volatile("mbarrier.init.shared::cta.b64 [%0], %1;" :: "r"(bar), "r"(cnt)); }
__device__ __forceinline__ void mbar_expect_tx(uint32_t bar, uint32_t bytes) { asm volatile("mbarrier.arrive.expect_tx.shared::cta.b64 _, [%0], %1;" :: "r"(bar), "r"(bytes) : "memory"); }
__device__ __forceinline__ void mbar_arrive(uint32_t bar) { asm volatile("mbarrier.arrive.shared::cta.b64 _, [%0];" :: "r"(bar) : "memory"); }
__device__ __forceinline__ void mbar_wait(uint32_t bar, uint32_t parity) {
  asm volatile("{\n.reg .pred p;\n.reg .u32 n;\nmov.u32 n, 0;\nLAB_WAIT:\n"
               "mbarrier.try_wait.parity.shared::cta.b64 p, [%0], %1;\n@p bra LAB_DONE;\n"
               "add.u32 n, n, 1;\nsetp.lt.u32 p, n, 4194304;\n@p bra LAB_WAIT;\ntrap;\nLAB_DONE:\n}" :: "r"(bar), "r"(parity) : "memory");
}
__device__ __forceinline__ void mbar_wait_fast(uint32_t bar, uint32_t parity) {
  asm volatile("{\n.reg .pred p;\nLAB_WAIT:\nmbarrier.try_wait.parity.shared::cta.b64 p, [%0], %1;\n@!p bra LAB_WAIT;\n}" :: "r"(bar), "r"(parity) : "memory");
}
__device__ __forceinline__ void spin_check(uint32_t n) { asm volatile("{\n.reg .pred p;\nsetp.ge.u32 p, %0, 4194304;\n@p st.volatile.global.u32 [%1], %0;\n}" :: "r"(n), "l"(0ull)); }
__device__ __forceinline__ void tma_ld3(uint32_t dst, const CUtensorMap* m, uint32_t bar, int c0, int c1, int c2) {
  asm volatile("cp.async.bulk.tensor.3d.shared::cluster.global.mbarrier::complete_tx::bytes [%0], [%1, {%3, %4, %5}], [%2];" :: "r"(dst), "l"(m), "r"(bar), "r"(c0), "r"(c1), "r"(c2) : "memory");
}
__device__ __forceinline__ void tma_ld3_mc(uint32_t dst, const CUtensorMap* m, uint32_t bar, int c0, int c1, int c2, uint16_t mask) {
  asm volatile("cp.async.bulk.tensor.3d.shared::cluster.global.mbarrier::complete_tx::bytes.multicast::cluster [%0], [%1, {%3, %4, %5}], [%2], %6;"
               :: "r"(dst), "l"(m), "r"(bar), "r"(c0), "r"(c1), "r"(c2), "h"(mask) : "memory");
}
__device__ __forceinline__ uint32_t mapa(uint32_t addr, uint32_t cta) { uint32_t r; asm("mapa.shared::cluster.u32 %0, %1, %2;" : "=r"(r) : "r"(addr), "r"(cta)); return r; }
__device__ __forceinline__ void mbar_arrive_cluster(uint32_t bar) { asm volatile("mbarrier.arrive.shared::cluster.b64 _, [%0];" :: "r"(bar) : "memory"); }
__device__ __forceinline__ void tma_st3(const CUtensorMap* m, uint32_t src, int c0, int c1, int c2) {
  asm volatile("cp.async.bulk.tensor.3d.global.shared::cta.bulk_group [%0, {%2, %3, %4}], [%1];" :: "l"(m), "r"(src), "r"(c0), "r"(c1), "r"(c2) : "memory");
}
__device__ __forceinline__ void bulk_commit() { asm volatile("cp.async.bulk.commit_group;" ::: "memory"); }
template <int N> __device__ __forceinline__ void bulk_wait() { asm volatile("cp.async.bulk.wait_group %0;" :: "n"(N) : "memory"); }
__device__ __forceinline__ void fence_async_smem() { asm volatile("fence.proxy.async.shared::cta;" ::: "memory"); }
__device__ __forceinline__ void fence_async_global() { asm volatile("fence.proxy.async.global;" ::: "memory"); }
__device__ __forceinline__ bool elect_one() { uint32_t p; asm volatile("{\n.reg .pred P;\nelect.sync _|P, 0xffffffff;\nselp.u32 %0, 1, 0, P;\n}" : "=r"(p)); return p; }
__device__ __forceinline__ void prefetch_map(const CUtensorMap* m) { asm volatile("prefetch.tensormap [%0];" :: "l"(m) : "memory"); }
__device__ __forceinline__ void prefetch_l2(const void* p, uint32_t bytes) { asm volatile("cp.async.bulk.prefetch.L2.global [%0], %1;" :: "l"(p), "r"(bytes) : "memory"); }
__device__ __forceinline__ void wgmma_fence() { asm volatile("wgmma.fence.sync.aligned;" ::: "memory"); }
__device__ __forceinline__ void wgmma_commit() { asm volatile("wgmma.commit_group.sync.aligned;" ::: "memory"); }
template <int N> __device__ __forceinline__ void wgmma_wait() { asm volatile("wgmma.wait_group.sync.aligned %0;" :: "n"(N) : "memory"); }
__device__ __forceinline__ uint32_t desc_lo(uint32_t addr, uint32_t lbo) { return ((addr & 0x3FFFF) >> 4) | ((lbo >> 4) << 16); }
__device__ __forceinline__ uint64_t desc64(uint32_t lo) { uint64_t r; asm("mov.b64 %0, {%1, %2};" : "=l"(r) : "r"(lo), "r"(0x40000040u)); return r; }
__device__ __forceinline__ void bar_sync(int id, int n) { asm volatile("bar.sync %0, %1;" :: "r"(id), "r"(n) : "memory"); }
__device__ __forceinline__ uint32_t pack_bf16(float lo, float hi) { uint32_t r; asm("cvt.rn.bf16x2.f32 %0, %1, %2;" : "=r"(r) : "f"(hi), "f"(lo)); return r; }
__device__ __forceinline__ float bf_lo(uint32_t v) { return __uint_as_float(v << 16); }
__device__ __forceinline__ float bf_hi(uint32_t v) { return __uint_as_float(v & 0xffff0000u); }
__device__ __forceinline__ float ex2(float x) { float r; asm("ex2.approx.ftz.f32 %0, %1;" : "=f"(r) : "f"(x)); return r; }
__device__ __forceinline__ float rcp(float x) { float r; asm("rcp.approx.ftz.f32 %0, %1;" : "=f"(r) : "f"(x)); return r; }
__device__ __forceinline__ void stsm4(uint32_t a, uint32_t r0, uint32_t r1, uint32_t r2, uint32_t r3) {
  asm volatile("stmatrix.sync.aligned.m8n8.x4.shared.b16 [%0], {%1, %2, %3, %4};" :: "r"(a), "r"(r0), "r"(r1), "r"(r2), "r"(r3) : "memory");
}
__device__ __forceinline__ void ldsm4(uint32_t a, uint32_t& r0, uint32_t& r1, uint32_t& r2, uint32_t& r3) {
  asm volatile("ldmatrix.sync.aligned.m8n8.x4.shared.b16 {%0, %1, %2, %3}, [%4];" : "=r"(r0), "=r"(r1), "=r"(r2), "=r"(r3) : "r"(a) : "memory");
}
__device__ __forceinline__ uint32_t movm(uint32_t v) { uint32_t r; asm volatile("movmatrix.sync.aligned.m8n8.trans.b16 %0, %1;" : "=r"(r) : "r"(v)); return r; }
__device__ __forceinline__ void sts128(uint32_t a, uint32_t r0, uint32_t r1, uint32_t r2, uint32_t r3) {
  asm volatile("st.shared.v4.b32 [%0], {%1, %2, %3, %4};" :: "r"(a), "r"(r0), "r"(r1), "r"(r2), "r"(r3) : "memory");
}
__device__ __forceinline__ void lds128(uint32_t a, uint32_t& r0, uint32_t& r1, uint32_t& r2, uint32_t& r3) {
  asm volatile("ld.shared.v4.b32 {%0, %1, %2, %3}, [%4];" : "=r"(r0), "=r"(r1), "=r"(r2), "=r"(r3) : "r"(a) : "memory");
}
__device__ __forceinline__ uint32_t add_bf16x2(uint32_t a, uint32_t b) { uint32_t r; asm("add.rn.bf16x2 %0, %1, %2;" : "=r"(r) : "r"(a), "r"(b)); return r; }
__device__ __forceinline__ void sts32f(uint32_t a, float v) { asm volatile("st.shared.f32 [%0], %1;" :: "r"(a), "f"(v) : "memory"); }
__device__ __forceinline__ void mma16816(float (&d)[4], uint32_t a0, uint32_t a1, uint32_t a2, uint32_t a3, uint32_t b0, uint32_t b1, const float (&c)[4]) {
  asm("mma.sync.aligned.m16n8k16.row.col.f32.bf16.bf16.f32 {%0, %1, %2, %3}, {%4, %5, %6, %7}, {%8, %9}, {%10, %11, %12, %13};"
      : "=f"(d[0]), "=f"(d[1]), "=f"(d[2]), "=f"(d[3]) : "r"(a0), "r"(a1), "r"(a2), "r"(a3), "r"(b0), "r"(b1), "f"(c[0]), "f"(c[1]), "f"(c[2]), "f"(c[3]));
}
__device__ __forceinline__ void mma1688(float (&d)[4], uint32_t a0, uint32_t a1, uint32_t b0, const float (&c)[4]) {
  asm("mma.sync.aligned.m16n8k8.row.col.f32.bf16.bf16.f32 {%0, %1, %2, %3}, {%4, %5}, {%6}, {%7, %8, %9, %10};"
      : "=f"(d[0]), "=f"(d[1]), "=f"(d[2]), "=f"(d[3]) : "r"(a0), "r"(a1), "r"(b0), "f"(c[0]), "f"(c[1]), "f"(c[2]), "f"(c[3]));
}
__device__ __forceinline__ void mma16816z(float (&d)[4], uint32_t a0, uint32_t a1, uint32_t a2, uint32_t a3, uint32_t b0, uint32_t b1) {
  asm("mma.sync.aligned.m16n8k16.row.col.f32.bf16.bf16.f32 {%0, %1, %2, %3}, {%4, %5, %6, %7}, {%8, %9}, {0f00000000, 0f00000000, 0f00000000, 0f00000000};"
      : "=f"(d[0]), "=f"(d[1]), "=f"(d[2]), "=f"(d[3]) : "r"(a0), "r"(a1), "r"(a2), "r"(a3), "r"(b0), "r"(b1));
}
__device__ __forceinline__ void mma1688z(float (&d)[4], uint32_t a0, uint32_t a1, uint32_t b0) {
  asm("mma.sync.aligned.m16n8k8.row.col.f32.bf16.bf16.f32 {%0, %1, %2, %3}, {%4, %5}, {%6}, {0f00000000, 0f00000000, 0f00000000, 0f00000000};"
      : "=f"(d[0]), "=f"(d[1]), "=f"(d[2]), "=f"(d[3]) : "r"(a0), "r"(a1), "r"(b0));
}
__device__ __forceinline__ uint32_t bar_sync_zero(int id, int n) {
  uint32_t r;
  asm volatile("{\n.reg .pred p;\nsetp.eq.u32 p, %1, 0;\nbarrier.cta.red.popc.aligned.u32 %0, %1, %2, p;\n}" : "=r"(r) : "r"(id), "r"(n) : "memory");
  return r;
}
__device__ __forceinline__ uint32_t late_zero(uint32_t zm) { uint32_t c; asm volatile("mov.u32 %0, %%clock;" : "=r"(c) :: "memory"); return c & zm; }
__device__ __forceinline__ void st_b128(uint4* p, uint32_t a, uint32_t b, uint32_t c, uint32_t d) {
  asm volatile("{\n.reg .b128 t;\n.reg .b64 lo, hi;\nmov.b64 lo, {%0, %1};\nmov.b64 hi, {%2, %3};\nmov.b128 t, {lo, hi};\nst.relaxed.gpu.global.b128 [%4], t;\n}"
               :: "r"(a), "r"(b), "r"(c), "r"(d), "l"(p) : "memory");
}
__device__ __forceinline__ uint32_t pkt_head(uint32_t a) { return a ? a : 0x8000u; }
__device__ __forceinline__ void gen_store(uint4* p, uint32_t a, uint32_t b, uint32_t c, uint32_t d) {
  asm volatile("{\n.reg .b128 t;\n.reg .b64 lo, hi;\nmov.b64 lo, {%0, %1};\nmov.b64 hi, {%2, %3};\nmov.b128 t, {lo, hi};\nst.relaxed.gpu.b128 [%4], t;\n}"
               :: "r"(a), "r"(b), "r"(c), "r"(d), "l"(p) : "memory");
}
__device__ __forceinline__ void gen_load(const uint4* p, uint32_t* v) {
  asm volatile("{\n.reg .b128 t;\n.reg .b64 lo, hi;\nld.relaxed.gpu.b128 t, [%4];\nmov.b128 {lo, hi}, t;\nmov.b64 {%0, %1}, lo;\nmov.b64 {%2, %3}, hi;\n}"
               : "=r"(v[0]), "=r"(v[1]), "=r"(v[2]), "=r"(v[3]) : "l"(p) : "memory");
}
__device__ __forceinline__ void pkt_load(const uint4* p, uint32_t* v) {
  asm volatile("{\n.reg .b128 t;\n.reg .b64 lo, hi;\nld.relaxed.gpu.global.b128 t, [%4];\nmov.b128 {lo, hi}, t;\nmov.b64 {%0, %1}, lo;\nmov.b64 {%2, %3}, hi;\n}"
               : "=r"(v[0]), "=r"(v[1]), "=r"(v[2]), "=r"(v[3]) : "l"(p) : "memory");
}
__device__ __forceinline__ uint32_t ld_relaxed(const uint32_t* p) { uint32_t v; asm volatile("ld.relaxed.gpu.global.u32 %0, [%1];" : "=r"(v) : "l"(p) : "memory"); return v; }
__device__ __forceinline__ uint4 ld_relaxed4(const void* p) { uint4 v; asm volatile("ld.relaxed.gpu.global.v4.u32 {%0, %1, %2, %3}, [%4];" : "=r"(v.x), "=r"(v.y), "=r"(v.z), "=r"(v.w) : "l"(p) : "memory"); return v; }
__device__ __forceinline__ void st_relaxed(uint32_t* p, uint32_t v) { asm volatile("st.relaxed.gpu.global.u32 [%0], %1;" :: "l"(p), "r"(v) : "memory"); }
__device__ __forceinline__ void st_relaxed2(void* p, uint32_t a, uint32_t b) { asm volatile("st.relaxed.gpu.global.v2.u32 [%0], {%1, %2};" :: "l"(p), "r"(a), "r"(b) : "memory"); }
__device__ __forceinline__ void red_release(uint32_t* p, uint32_t v) { asm volatile("red.release.gpu.global.add.u32 [%0], %1;" :: "l"(p), "r"(v) : "memory"); }
__device__ __forceinline__ uint32_t tagf(float v, uint32_t tag) { return (__float_as_uint(v) & ~15u) | (tag & 15u); }
__device__ __forceinline__ bool tag_ok4(const uint4& v, uint32_t tag) { return (((v.x ^ tag) | (v.y ^ tag) | (v.z ^ tag) | (v.w ^ tag)) & 15u) == 0; }
__device__ __forceinline__ float untag(uint32_t v) { return __uint_as_float(v & ~15u); }
template <typename T> __device__ __forceinline__ T* ptr_add(T* p, uint32_t bytes) {
  uint64_t r;
  asm("{\n.reg .u32 lo, hi;\nmov.b64 {lo, hi}, %1;\nadd.cc.u32 lo, lo, %2;\naddc.u32 hi, hi, 0;\nmov.b64 %0, {lo, hi};\n}" : "=l"(r) : "l"(p), "r"(bytes));
  return (T*)r;
}
#define TL(who, slot) do {} while (0)
#define TLC(slot) do {} while (0)
#define TLE(slot) do {} while (0)
#define ST(who, n) do {} while (0)
#define AP(i) do {} while (0)
#define SP(v) do {} while (0)
#define TLG(slot) do {} while (0)
#define STA() do {} while (0)
#define STB(n) do {} while (0)

__device__ __forceinline__ void wgmma_n128(float (&d)[64], uint64_t da, uint64_t db, int scale_d) {
  asm volatile("{\n.reg .pred p;\nsetp.ne.b32 p, %66, 0;\n"
    "wgmma.mma_async.sync.aligned.m64n128k16.f32.bf16.bf16 "
    "{%0, %1, %2, %3, %4, %5, %6, %7, %8, %9, %10, %11, %12, %13, %14, %15, "
    "%16, %17, %18, %19, %20, %21, %22, %23, %24, %25, %26, %27, %28, %29, %30, %31, "
    "%32, %33, %34, %35, %36, %37, %38, %39, %40, %41, %42, %43, %44, %45, %46, %47, "
    "%48, %49, %50, %51, %52, %53, %54, %55, %56, %57, %58, %59, %60, %61, %62, %63}, "
    "%64, %65, p, 1, 1, 0, 1;\n}\n"
    : "+f"(d[0]), "+f"(d[1]), "+f"(d[2]), "+f"(d[3]), "+f"(d[4]), "+f"(d[5]), "+f"(d[6]), "+f"(d[7]),
      "+f"(d[8]), "+f"(d[9]), "+f"(d[10]), "+f"(d[11]), "+f"(d[12]), "+f"(d[13]), "+f"(d[14]), "+f"(d[15]),
      "+f"(d[16]), "+f"(d[17]), "+f"(d[18]), "+f"(d[19]), "+f"(d[20]), "+f"(d[21]), "+f"(d[22]), "+f"(d[23]),
      "+f"(d[24]), "+f"(d[25]), "+f"(d[26]), "+f"(d[27]), "+f"(d[28]), "+f"(d[29]), "+f"(d[30]), "+f"(d[31]),
      "+f"(d[32]), "+f"(d[33]), "+f"(d[34]), "+f"(d[35]), "+f"(d[36]), "+f"(d[37]), "+f"(d[38]), "+f"(d[39]),
      "+f"(d[40]), "+f"(d[41]), "+f"(d[42]), "+f"(d[43]), "+f"(d[44]), "+f"(d[45]), "+f"(d[46]), "+f"(d[47]),
      "+f"(d[48]), "+f"(d[49]), "+f"(d[50]), "+f"(d[51]), "+f"(d[52]), "+f"(d[53]), "+f"(d[54]), "+f"(d[55]),
      "+f"(d[56]), "+f"(d[57]), "+f"(d[58]), "+f"(d[59]), "+f"(d[60]), "+f"(d[61]), "+f"(d[62]), "+f"(d[63])
    : "l"(da), "l"(db), "r"(scale_d));
}
__device__ __forceinline__ void wgmma_n256(float (&d)[128], uint64_t da, uint64_t db, int scale_d) {
  asm volatile("{\n.reg .pred p;\nsetp.ne.b32 p, %130, 0;\n"
    "wgmma.mma_async.sync.aligned.m64n256k16.f32.bf16.bf16 "
    "{%0, %1, %2, %3, %4, %5, %6, %7, %8, %9, %10, %11, %12, %13, %14, %15, "
    "%16, %17, %18, %19, %20, %21, %22, %23, %24, %25, %26, %27, %28, %29, %30, %31, "
    "%32, %33, %34, %35, %36, %37, %38, %39, %40, %41, %42, %43, %44, %45, %46, %47, "
    "%48, %49, %50, %51, %52, %53, %54, %55, %56, %57, %58, %59, %60, %61, %62, %63, "
    "%64, %65, %66, %67, %68, %69, %70, %71, %72, %73, %74, %75, %76, %77, %78, %79, "
    "%80, %81, %82, %83, %84, %85, %86, %87, %88, %89, %90, %91, %92, %93, %94, %95, "
    "%96, %97, %98, %99, %100, %101, %102, %103, %104, %105, %106, %107, %108, %109, %110, %111, "
    "%112, %113, %114, %115, %116, %117, %118, %119, %120, %121, %122, %123, %124, %125, %126, %127}, "
    "%128, %129, p, 1, 1, 0, 1;\n}\n"
    : "+f"(d[0]), "+f"(d[1]), "+f"(d[2]), "+f"(d[3]), "+f"(d[4]), "+f"(d[5]), "+f"(d[6]), "+f"(d[7]),
      "+f"(d[8]), "+f"(d[9]), "+f"(d[10]), "+f"(d[11]), "+f"(d[12]), "+f"(d[13]), "+f"(d[14]), "+f"(d[15]),
      "+f"(d[16]), "+f"(d[17]), "+f"(d[18]), "+f"(d[19]), "+f"(d[20]), "+f"(d[21]), "+f"(d[22]), "+f"(d[23]),
      "+f"(d[24]), "+f"(d[25]), "+f"(d[26]), "+f"(d[27]), "+f"(d[28]), "+f"(d[29]), "+f"(d[30]), "+f"(d[31]),
      "+f"(d[32]), "+f"(d[33]), "+f"(d[34]), "+f"(d[35]), "+f"(d[36]), "+f"(d[37]), "+f"(d[38]), "+f"(d[39]),
      "+f"(d[40]), "+f"(d[41]), "+f"(d[42]), "+f"(d[43]), "+f"(d[44]), "+f"(d[45]), "+f"(d[46]), "+f"(d[47]),
      "+f"(d[48]), "+f"(d[49]), "+f"(d[50]), "+f"(d[51]), "+f"(d[52]), "+f"(d[53]), "+f"(d[54]), "+f"(d[55]),
      "+f"(d[56]), "+f"(d[57]), "+f"(d[58]), "+f"(d[59]), "+f"(d[60]), "+f"(d[61]), "+f"(d[62]), "+f"(d[63]),
      "+f"(d[64]), "+f"(d[65]), "+f"(d[66]), "+f"(d[67]), "+f"(d[68]), "+f"(d[69]), "+f"(d[70]), "+f"(d[71]),
      "+f"(d[72]), "+f"(d[73]), "+f"(d[74]), "+f"(d[75]), "+f"(d[76]), "+f"(d[77]), "+f"(d[78]), "+f"(d[79]),
      "+f"(d[80]), "+f"(d[81]), "+f"(d[82]), "+f"(d[83]), "+f"(d[84]), "+f"(d[85]), "+f"(d[86]), "+f"(d[87]),
      "+f"(d[88]), "+f"(d[89]), "+f"(d[90]), "+f"(d[91]), "+f"(d[92]), "+f"(d[93]), "+f"(d[94]), "+f"(d[95]),
      "+f"(d[96]), "+f"(d[97]), "+f"(d[98]), "+f"(d[99]), "+f"(d[100]), "+f"(d[101]), "+f"(d[102]), "+f"(d[103]),
      "+f"(d[104]), "+f"(d[105]), "+f"(d[106]), "+f"(d[107]), "+f"(d[108]), "+f"(d[109]), "+f"(d[110]), "+f"(d[111]),
      "+f"(d[112]), "+f"(d[113]), "+f"(d[114]), "+f"(d[115]), "+f"(d[116]), "+f"(d[117]), "+f"(d[118]), "+f"(d[119]),
      "+f"(d[120]), "+f"(d[121]), "+f"(d[122]), "+f"(d[123]), "+f"(d[124]), "+f"(d[125]), "+f"(d[126]), "+f"(d[127])
    : "l"(da), "l"(db), "r"(scale_d));
}
__device__ __forceinline__ void wgmma_rs_n128(float (&d)[64], const uint32_t* a, uint64_t db, int scale_d) {
  asm volatile("{\n.reg .pred p;\nsetp.ne.b32 p, %69, 0;\n"
    "wgmma.mma_async.sync.aligned.m64n128k16.f32.bf16.bf16 "
    "{%0, %1, %2, %3, %4, %5, %6, %7, %8, %9, %10, %11, %12, %13, %14, %15, "
    "%16, %17, %18, %19, %20, %21, %22, %23, %24, %25, %26, %27, %28, %29, %30, %31, "
    "%32, %33, %34, %35, %36, %37, %38, %39, %40, %41, %42, %43, %44, %45, %46, %47, "
    "%48, %49, %50, %51, %52, %53, %54, %55, %56, %57, %58, %59, %60, %61, %62, %63}, "
    "{%64, %65, %66, %67}, %68, p, 1, 1, 1;\n}\n"
    : "+f"(d[0]), "+f"(d[1]), "+f"(d[2]), "+f"(d[3]), "+f"(d[4]), "+f"(d[5]), "+f"(d[6]), "+f"(d[7]),
      "+f"(d[8]), "+f"(d[9]), "+f"(d[10]), "+f"(d[11]), "+f"(d[12]), "+f"(d[13]), "+f"(d[14]), "+f"(d[15]),
      "+f"(d[16]), "+f"(d[17]), "+f"(d[18]), "+f"(d[19]), "+f"(d[20]), "+f"(d[21]), "+f"(d[22]), "+f"(d[23]),
      "+f"(d[24]), "+f"(d[25]), "+f"(d[26]), "+f"(d[27]), "+f"(d[28]), "+f"(d[29]), "+f"(d[30]), "+f"(d[31]),
      "+f"(d[32]), "+f"(d[33]), "+f"(d[34]), "+f"(d[35]), "+f"(d[36]), "+f"(d[37]), "+f"(d[38]), "+f"(d[39]),
      "+f"(d[40]), "+f"(d[41]), "+f"(d[42]), "+f"(d[43]), "+f"(d[44]), "+f"(d[45]), "+f"(d[46]), "+f"(d[47]),
      "+f"(d[48]), "+f"(d[49]), "+f"(d[50]), "+f"(d[51]), "+f"(d[52]), "+f"(d[53]), "+f"(d[54]), "+f"(d[55]),
      "+f"(d[56]), "+f"(d[57]), "+f"(d[58]), "+f"(d[59]), "+f"(d[60]), "+f"(d[61]), "+f"(d[62]), "+f"(d[63])
    : "r"(a[0]), "r"(a[1]), "r"(a[2]), "r"(a[3]), "l"(db), "r"(scale_d));
}

template <int BN> __device__ __forceinline__ void wgmma(float (&d)[BN / 2], uint64_t a, uint64_t b, int s) {
  if constexpr (BN == 128) wgmma_n128(d, a, b, s);
  else wgmma_n256(d, a, b, s);
}

template <int N> __device__ __forceinline__ void acc_fence(float* a) {
#pragma unroll
  for (int i = 0; i < N; i++) asm volatile("" : "+f"(a[i]) :: "memory");
}

#define SELECT8(a, f) do { \
  if ((a) & 4) { if ((a) & 2) { if ((a) & 1) f(7); else f(6); } else { if ((a) & 1) f(5); else f(4); } } \
  else { if ((a) & 2) { if ((a) & 1) f(3); else f(2); } else { if ((a) & 1) f(1); else f(0); } } } while (0)
__device__ __forceinline__ uint32_t lane_now() { uint32_t l; asm volatile("mov.u32 %0, %%laneid;" : "=r"(l)); return l; }

struct Prod {
  uint32_t sb, n, tail, addr, pat, ready;
  uint32_t rank, flip; uint16_t mask;
  __device__ __forceinline__ void load_b(uint32_t dst, uint32_t half, const CUtensorMap* m, uint32_t mstep, uint32_t fb, int k, int ch, int cstep) {
    uint32_t h = rank;
    do { tma_ld3_mc(dst + h * half, ptr_add(m, h * mstep), fb, 0, k * 64, ch + h * cstep, mask); h ^= flip; } while (h != rank);
  }
  __device__ __forceinline__ void load_wide(const Params& P, int ffn, uint32_t dst, uint32_t fb, int k, int ch) {
    load_b(dst, PAGE, &P.map[ffn ? M_W1 : M_WKV], ffn ? 128 : 0, fb, k, ffn ? ch : ch + 16, ffn ? 0 : 16);
  }
  __device__ __forceinline__ void load_narrow(const Params& P, int ffn, uint32_t dst, uint32_t fb, int k, int j) {
    load_b(dst, 8192, &P.map[ffn ? M_W1H : M_WQ], ffn ? 128 : 0, fb, k, ffn ? 48 + j : 2 * j, ffn ? 0 : 1);
  }
  __device__ __forceinline__ void finish() {
#pragma unroll 1
    for (; tail < n; tail++) mbar_wait(sb + BAR_EMPTY + ((tail & 7) << 3), (tail >> 3) & 1);
  }
  template <int PAGES> __device__ __forceinline__ uint32_t acquire(uint32_t& fb) { return acquire_n(PAGES, fb); }
  __device__ __forceinline__ uint32_t acquire_n(uint32_t PAGES, uint32_t& fb) {
    uint32_t nw = pat & 3; pat = (pat >> 2) | 0x40000000u;
#pragma unroll 1
    for (; nw; nw--) { mbar_wait(sb + BAR_EMPTY + ((tail & 7) << 3), (tail >> 3) & 1); tail++; }
    ST(4, n);
    fb = sb + BAR_FULL + ((n & 7) << 3);
    mbar_expect_tx(fb, PAGES * PAGE);
    const uint32_t a = sb + addr;
    addr += PAGES * PAGE; if (addr >= NPAGE * PAGE) addr = 0;
    n++;
    return a;
  }
  const uint32_t* flag; uint32_t base, seen;
  __device__ __forceinline__ void acquire_fence() { asm volatile("fence.acquire.gpu;" ::: "memory"); fence_async_global(); }
  __device__ __forceinline__ void next() {
    uint32_t v, spins = 0;
    seen++;
    do { asm volatile("ld.acquire.cta.shared.u32 %0, [%1];" : "=r"(v) : "r"(sb + SM_SEEN) : "memory"); spin_check(++spins >> 4); } while (v < seen);
    fence_async_global();
  }
  __device__ __forceinline__ void need(uint32_t mask) {
    if ((ready & mask) != mask) {
      uint32_t spins = 0;
      do { ready = ld_relaxed(flag) - base; spin_check(++spins); } while ((ready & mask) != mask);
      acquire_fence();
    }
    ST(5, n - 1);
  }
};

struct Cons {
  uint32_t sb, n, off, prev;
  uint32_t ebar;
  uint32_t da0, db0;
  int lane;
  template <int PAGES> __device__ __forceinline__ void advance() {
    n++; off += PAGES << 10; if (off >= (NPAGE << 10)) off = 0;
    asm volatile("" : "+r"(n), "+r"(off));
  }
  template <int BN, int PAGES> __device__ __forceinline__ void step_ab(float (&acc)[BN / 2], uint32_t da, uint32_t db, int accumulate) {
    STA();
    mbar_wait_fast(sb + BAR_FULL + ((n & 7) << 3), (n >> 3) & 1);
    STB(n);
    const uint64_t da64 = desc64(da), db64 = desc64(db);
    wgmma_fence();
#pragma unroll
    for (int k = 0; k < 4; k++) wgmma<BN>(acc, da64 + 2 * k, db64 + 128 * k, k ? 1 : accumulate);
    wgmma_commit();
    wgmma_wait<1>();
    if (prev && lane < 2) mbar_arrive_cluster(ebar + prev);
    prev = 64 + ((n & 7) << 3);
    advance<PAGES>();
  }
  template <int BN> __device__ __forceinline__ void step(float (&acc)[BN / 2], int accumulate = 1) { step_ab<BN, BN / 128 + 1>(acc, da0 + off, db0 + 1024 + off, accumulate); }
  template <int BN> __device__ __forceinline__ void step_own(float (&acc)[BN / 2], uint32_t da, int accumulate) { step_ab<BN, BN / 128>(acc, da, db0 + off, accumulate); }
  __device__ __forceinline__ void wait_full(uint32_t i) { mbar_wait_fast(sb + BAR_FULL + (((n + i) & 7) << 3), ((n + i) >> 3) & 1); }
  template <int I, int N> __device__ __forceinline__ void issue_rs(float (&acc)[64], uint32_t (&a)[16], int accumulate = 1) {
    if (I == 0) { STA(); STB(n); }
    const uint64_t db64 = desc64(db0 + off) + 1024 * I;
    wgmma_fence();
#pragma unroll
    for (int k = 0; k < 4; k++) wgmma_rs_n128(acc, a + 4 * k, db64 + 128 * k, k ? 1 : accumulate);
    if (I == N - 1) {
      wgmma_commit();
      prev = 64 + ((n & 7) << 3);
      advance<N>();
    }
  }
  template <int BN> __device__ __forceinline__ void steps(float (&acc)[BN / 2], int cnt) {
#pragma unroll 1
    do { step<BN>(acc); } while (--cnt > 0);
  }
  __device__ __forceinline__ void steps_skip(float (&acc)[64], int at) {
    int i = 0;
#pragma unroll 1
    do { if (i == at) off += 2 << 10; step<128>(acc); } while (++i < 2);
  }
  __device__ __forceinline__ void drain() {
    wgmma_wait<0>();
    if (lane < 2) mbar_arrive_cluster(ebar + prev);
    prev = 0;
  }
};

#define MAPPING 2
__device__ __forceinline__ uint32_t role_of_sm(uint32_t smid) {
  const uint32_t t = smid >> 1;
  uint32_t q, i;
  if (t < 32) { q = t & 7; i = t >> 3; }
  else if (t < 60) { const uint32_t u = t - 32, d = (u * 37) >> 8; q = 1 + u - d * 7; i = 4 + d; }
  else if (t < 62) return 128 + smid - 120;
  else { q = 0; i = t - 58; }
  return (q * 2 + (smid & 1)) * 8 + i;
}

template <typename T> __device__ __forceinline__ T* scratch(const Params& P, uint32_t off) { return (T*)ptr_add(P.scratch, off); }
__device__ __forceinline__ uint32_t* epoch_ptr(const Params& P) { uint32_t b; asm volatile("mov.u32 %0, %%ctaid.x;" : "=r"(b)); return scratch<uint32_t>(P, G_EPOCH + b * 4u); }

__device__ __forceinline__ int o_chunk(int s, int j) { const int hf = s >= 9, m = s - 2 - 7 * hf; return s < 2 ? 2 * j + s : 2 * (m == j ? 7 : m) + hf; }

__global__ void __cluster_dims__(2, 1, 1) __launch_bounds__(384, 1) fused_kernel(const __grid_constant__ Params P) {
  extern __shared__ __align__(1024) uint8_t smem_raw[];
  SP(0);
  const uint32_t sb = __shfl_sync(0xffffffffu, smem_u32(smem_raw), 0);
  const int warp = __shfl_sync(0xffffffffu, threadIdx.x >> 5, 0);
  const int lane = threadIdx.x & 31;
  if (warp == 7 && elect_one()) { prefetch_map(&P.map[M_XIN64]); prefetch_map(&P.map[M_WKV]); prefetch_map(&P.map[M_XIN]); }
  uint32_t role = blockIdx.x < 128 ? ((blockIdx.x >> 4) * 2 + (blockIdx.x & 1)) * 8 + ((blockIdx.x >> 1) & 7) : blockIdx.x;
  if (P.use_smid) { uint32_t smid; asm volatile("mov.u32 %0, %%smid;" : "=r"(smid)); role = role_of_sm(smid); }
  const bool spare = role >= 128;
  const int g = role >> 3, j = role & 7;
  uint32_t rank; asm("mov.u32 %0, %%cluster_ctarank;" : "=r"(rank));
  auto shared_b = [&]() {
    uint32_t peer;
    asm volatile("ld.shared::cluster.u32 %0, [%1];" : "=r"(peer) : "r"(mapa(sb + SM_ROLE, rank ^ 1)) : "memory");
    return !spare && peer < 128 && (peer & 7) == (uint32_t)j;
  };
  SP(1);

  if (warp >= 8) {
    asm volatile("setmaxnreg.dec.sync.aligned.u32 40;");
    if (elect_one()) {
      if (warp == 8) {
#pragma unroll
        for (int i = 0; i < 6; i++) mbar_init(sb + BAR_FULL + 8 * i, 1);
        mbar_init(sb + BAR_XIN, 1);
      } else if (warp == 9) {
#pragma unroll
        for (int i = 0; i < 8; i++) mbar_init(sb + BAR_EMPTY + 8 * i, 16);
      } else if (warp == 10) {
#pragma unroll
        for (int i = 0; i < 4; i++) mbar_init(sb + BAR_SFULL + 8 * i, 4);
        mbar_init(sb + BAR_CLR, 1); mbar_init(sb + BAR_FULL + 48, 1); mbar_init(sb + BAR_FULL + 56, 1);
      } else {
        sts128(sb + SM_ROLE, role, 0, 0, 0);
        mbar_init(sb + BAR_TAG, 1); mbar_init(sb + BAR_XFULL, 8); mbar_init(sb + BAR_CSE, 8);
        mbar_init(sb + BAR_SEMPTY, 1); mbar_init(sb + BAR_CSF, 1); mbar_init(sb + BAR_CSF + 8, 2);
      }
      asm volatile("fence.mbarrier_init.release.cluster;\nfence.release.sync_restrict::shared::cta.cluster;" ::: "memory");
      fence_async_smem();
    }
    __syncwarp();
    SP(2);
    asm volatile("barrier.cluster.arrive.relaxed.aligned;" ::: "memory");
    if (warp == 8 && !spare) {
      if (elect_one()) {
        const int par = g & 1, row = (g >> 1) * 128;
        mbar_arrive(sb + BAR_FULL);
        {
          const int s = 1;
          const uint32_t xb = sb + BAR_XIN, fb = sb + BAR_FULL + 8;
          mbar_expect_tx(xb, PAGE); mbar_expect_tx(fb, 2 * PAGE);
#pragma unroll
          for (int h = 0; h < 2; h++) tma_ld3(sb + SM_STAGE + h * PAGE + s * 8192, &P.map[M_XIN64], xb, s * 64, par, row + h * 64);
#pragma unroll
          for (int h = 0; h < 2; h++) tma_ld3(sb + (2 * s + h) * PAGE, &P.map[M_WKV], fb, 0, s * 64, 16 + 16 * h + 2 * j);
        }
#pragma unroll 1
        for (int s = 0; s < 2; s++) {
          const uint32_t fb = sb + BAR_FULL + 16 + 8 * s;
          mbar_expect_tx(fb, PAGE);
          tma_ld3(sb + (4 + s) * PAGE, &P.map[M_WKV], fb, 0, s * 64, 2 * j);
        }
#pragma unroll 1
        for (int s = 0; s < 2; s++) {
          const uint32_t fb = sb + BAR_FULL + 32 + 8 * s, a = sb + (6 + 3 * s) * PAGE;
          const int k = (j == 1 ? 4 : 2) + s;
          mbar_expect_tx(fb, 3 * PAGE);
          tma_ld3(a, &P.map[M_XIN], fb, k * 64, par, row);
#pragma unroll
          for (int h = 0; h < 2; h++) tma_ld3(a + PAGE + h * PAGE, &P.map[M_WKV], fb, 0, k * 64, 16 + 16 * h + 2 * j);
        }
        spin_check((sb & 1023) << 22);
      }
      __syncwarp();
    }
    SP(3);
    asm volatile("barrier.cluster.wait.acquire.aligned;" ::: "memory");
    SP(4);
    if (warp == 8) {
      if (elect_one()) {
        Prod p; p.sb = sb; p.n = 0; p.tail = 0; p.ready = 0; p.addr = 0;
        { const bool mc = shared_b(); p.rank = rank; p.flip = !mc; p.mask = mc ? 3 : 1 << rank; }
        uint32_t fb;
        if (spare) {
          p.pat = 0x55555000u;
#pragma unroll 1
          for (int r = -1; r < 7; r++) {
            const int ch = r < 0 ? 4 * j : ((r < 2 ? r : r == 2 ? 6 : r - 1) * 4 + j) * 2;
#pragma unroll 1
            for (int k = 0; k < 16; k++) { const uint32_t a = p.acquire<2>(fb); p.load_b(a, PAGE, &P.map[r < 0 ? M_WKV : M_W1], r < 0 ? 0 : 128, fb, k, ch, r < 0 ? 2 : 0); }
          }
        } else {
          p.seen = 0;
          const int xpar = g & 1, xrow = (g >> 1) * 128;
          SP(5);
#pragma unroll 1
          for (int hl = 0; hl < 4; hl++) {
            const int ffn = hl & 1;
            const CUtensorMap* xmap = &P.map[hl ? M_OUT_LD : M_XIN];
            if (hl) {
              p.pat = ffn ? Pat<3>::v : Pat<8>::v;
#pragma unroll 1
              for (int s = 0; s < 2; s++) { const uint32_t a = p.acquire<2>(fb); p.load_wide(P, ffn, a, fb, 2 * j + s, 2 * j); }
#pragma unroll 1
              for (int s = 0; s < 2; s++) { const uint32_t a = p.acquire<1>(fb); p.load_narrow(P, ffn, a, fb, 2 * j + s, j); }
            } else { p.pat = (Pat<0>::v >> 12) | 0x55500000u; p.addr = 0; p.n = 6; }
            if (hl == 0) SP(6);
            uint32_t fb0 = 0;
#pragma unroll 1
            for (int m = hl ? 0 : 2; m < 14; m++) {
              const int hf = m >= 7, mm = m - 7 * hf, jj = mm == j ? 7 : mm;
              int k = 2 * jj + hf;
              if (hl == 0) {
                const int pr = (m >> 1) + 1;
                k = 2 * (j && pr == 2 ? j : pr == j ? 2 : pr) + (m & 1);
              }
              const uint32_t a = p.acquire<3>(fb);
              p.load_wide(P, ffn, a + PAGE, fb, k, 2 * j);
              if (hl) {
                if (m == 0) { fb0 = fb; continue; }
                if (m == 1) {
                  const int j0 = j ? 0 : 7;
                  p.flag = scratch<uint32_t>(P, g * G_BLOCK + G_FLAGS + (ffn ? (hl >> 1) * EV_N + EV_XA : EV_XB) * 128);
                  p.ready = 0; p.need((1u << j0) | (1u << j));
                  tma_ld3(a - 3 * PAGE, xmap, fb0, j0 * 128, xpar, xrow);
                }
                if (m < 7) p.need(1u << jj); else if (m == 7) p.next();
              }
              tma_ld3(a, xmap, fb, k * 64, xpar, xrow);
            }
            if (hl == 0) { mbar_wait(sb + BAR_TAG, 0); asm volatile("ld.shared.u32 %0, [%1];" : "=r"(p.base) : "r"(sb + SM_TAG) : "memory"); p.base = (p.base - 1) * 255; }
            p.pat = ffn ? Pat<4>::v : Pat<1>::v;
#pragma unroll 1
            for (int m = 0; m < 14; m++) {
              const int k = (m >> 1) == (hl ? j : 0) ? 14 + (m & 1) : m;
              if (ffn && m == 8) p.addr += 2 * PAGE;
              const uint32_t a = p.acquire<2>(fb);
              p.load_narrow(P, ffn, a + PAGE, fb, k, j);
              tma_ld3(a, xmap, fb, k * 64, xpar, xrow);
            }
            if (!ffn) {
              p.pat = Pat<2>::v;
              uint32_t a = 0;
#pragma unroll 1
              for (int s = 0; s < 16; s++) {
                if ((0x4925 >> s) & 1) a = p.acquire_n(s == 0 || s == 14 ? 2 : 3, fb); else a += PAGE;
                p.load_b(a, 8192, &P.map[M_WO], 0, fb, o_chunk(s, j), 2 * j, 1);
              }
              p.addr += 2 * PAGE;
              a = p.acquire<2>(fb);
              tma_ld3(a, xmap, fb, j * 128, xpar, xrow); tma_ld3(a + PAGE, xmap, fb, j * 128 + 64, xpar, xrow);
            } else {
              p.pat = Pat<5>::v;
#pragma unroll 1
              for (int s = 16; s < 48; s++) {
                const int pi = (s >> 1) & 7;
                const int k = (s < 32 ? pi : pi == 4 ? j : pi == j ? 4 : pi) * 2 + (s & 1);
                const uint32_t a = p.acquire<3>(fb);
                p.load_wide(P, 1, a + PAGE, fb, k, (s & 48) + 2 * j);
                tma_ld3(a, xmap, fb, k * 64, xpar, xrow);
              }
              p.pat = Pat<6>::v;
#pragma unroll 1
              for (int q = 0; q < 4; q++) {
                p.next();
                const int k0 = q == 0 ? 0 : q == 1 ? 48 : q * 16 - 16, k1 = k0 + (q == 1 ? 8 : 16);
#pragma unroll 1
                for (int k = k0; k < k1; k++) {
                  if (k == 24) { p.addr = 0; p.pat = Pat<7>::v; }
                  const uint32_t a = p.acquire<2>(fb);
                  p.load_b(a + PAGE, 8192, &P.map[M_W2], 0, fb, k, 2 * j, 1);
                  tma_ld3(a, &P.map[M_H_LD], fb, k * 64, g, 0);
                }
              }
            }
            TL(2, 1 + hl);
          }
        }
        p.finish();
      }
    } else if (!spare) {
      mbar_wait(sb + BAR_XIN, 0);
      if (elect_one()) {
#pragma unroll 1
        for (int i = warp - 9; i < 8; i += 3) prefetch_l2(ptr_add(P.wqkv, (i * 128 + role) * 6144u + 2048u), 4096);
      }
      uint32_t tag;
      {
        const uint32_t part = warp - 9, col = DM + role * 16 + (lane & 1) * 8;
        const int cnt = part ? 21 : 22;
        const uint4* wp = ptr_add((const uint4*)P.wqkv, ((part ? 16 + part * 336 : 0) + (lane >> 1)) * 6144u + col * 2);
        float s[8] = {0, 0, 0, 0, 0, 0, 0, 0};
        uint4 v[4];
#pragma unroll
        for (int i = 0; i < 4; i++) v[i] = ld_relaxed4(wp + i * (16 * 6144 / 16));
        tag = ld_relaxed(epoch_ptr(P)) + 1;
        if (warp == 10 && lane == 0) { asm volatile("st.shared.u32 [%0], %1;" :: "r"(sb + SM_TAG), "r"(tag) : "memory"); mbar_arrive(sb + BAR_TAG); }
#pragma unroll 1
        for (int b = 4; b < 28; b += 4) {
          wp += 64 * 6144 / 16;
#pragma unroll
          for (int i = 0; i < 4; i++) {
            s[0] += bf_lo(v[i].x); s[1] += bf_hi(v[i].x); s[2] += bf_lo(v[i].y); s[3] += bf_hi(v[i].y);
            s[4] += bf_lo(v[i].z); s[5] += bf_hi(v[i].z); s[6] += bf_lo(v[i].w); s[7] += bf_hi(v[i].w);
            v[i] = make_uint4(0, 0, 0, 0);
            if (b + i < cnt) v[i] = __ldcg(wp + i * (16 * 6144 / 16));
          }
        }
#pragma unroll
        for (int e = 0; e < 4; e++) { const bool h = lane & 16; const float t = __shfl_xor_sync(0xffffffffu, h ? s[e] : s[e + 4], 16); s[e] = (h ? s[e + 4] : s[e]) + t; }
#pragma unroll
        for (int e = 0; e < 2; e++) { const bool h = lane & 8; const float t = __shfl_xor_sync(0xffffffffu, h ? s[e] : s[e + 2], 8); s[e] = (h ? s[e + 2] : s[e]) + t; }
        { const bool h = lane & 4; const float t = __shfl_xor_sync(0xffffffffu, h ? s[0] : s[1], 4); s[0] = (h ? s[1] : s[0]) + t; }
        s[0] += __shfl_xor_sync(0xffffffffu, s[0], 2);
        if (!(lane & 2) || part == 0) st_relaxed(scratch<uint32_t>(P, G_CS + (col + (lane >> 2)) * 16 + ((lane & 2) ? 3 : part) * 4), tagf((lane & 2) ? 0.f : s[0], tag));
        __syncwarp();
      }
      if (warp == 11 && lane == 0) TL(2, 30);
      {
        const uint32_t cspos = sb + SM_CS + ((lane & 16) + ((lane >> 1) & 3) * 4 + ((lane >> 3) & 1) * 2 + (lane & 1)) * 4;
#pragma unroll 1
        for (int it = 0; it < (warp == 10 ? 8 : 1); it++) {
          const int t = it & 3;
          if (it) mbar_wait(sb + BAR_CSE, (it - 1) & 1);
          if (t == 1) mbar_wait(sb + BAR_SEMPTY, 0);
#pragma unroll 1
          for (int b = it ? 0 : warp - 9; b < (it == 0 ? warp - 8 : t < 2 ? 3 : 2); b++) {
            uint32_t c0, c1;
            if (b < 2) { c0 = (t ? 2048 + t * 1024 + b * FF : 1024 + b * 1024) + j * 128; c1 = c0 + 64; }
            else if (t) { c0 = 6144 + j * 64; c1 = c0 + FF; }
            else { c0 = j * 128; c1 = c0 + 64; }
            const uint4* p0 = scratch<uint4>(P, G_CS + (c0 + lane) * 16u);
            const uint4* p1 = scratch<uint4>(P, G_CS + (c1 + lane) * 16u);
            uint4 v[4]; uint32_t spins = 0; bool ok;
            do {
              if (spins) __nanosleep(200);
              v[0] = ld_relaxed4(p0); v[1] = ld_relaxed4(p0 + 32); v[2] = ld_relaxed4(p1); v[3] = ld_relaxed4(p1 + 32);
              ok = tag_ok4(v[0], tag) && tag_ok4(v[1], tag) && tag_ok4(v[2], tag) && tag_ok4(v[3], tag);
              spin_check(++spins);
            } while (__any_sync(0xffffffffu, !ok));
#pragma unroll
            for (int m = 0; m < 4; m++) sts32f(cspos + b * 512 + m * 128, (untag(v[m].x) + untag(v[m].y)) + (untag(v[m].z) + untag(v[m].w)));
            __syncwarp();
            if (lane == 0) mbar_arrive(sb + BAR_CSF + (b ? 8 : 0));
          }
          if (lane == 0) { if (t >= 2) mbar_arrive(sb + BAR_CSF + 8); TL(2, 16 + it + (warp == 11 ? 8 : warp == 9 ? 9 : 0)); }
          if (t == 3) {
            if (g >= 2) {
              uint4* op = scratch<uint4>(P, G_HALO + (((it >> 2) * 16 + g - 2) * 8 + j) * 4096u + lane * 16u);
#pragma unroll 1
              for (int i = 0; i < 8; i++) { st_b128(op, 0, 0, 0, 0); op += 32; }
            }
          }
        }
      }
      if (warp == 11) {
        if (elect_one()) prefetch_l2(ptr_add(P.wo, role * 16384u), 16384);
        uint32_t* const fl = scratch<uint32_t>(P, g * G_BLOCK + G_FLAGS);
        uint32_t seen = 0;
#pragma unroll 1
        for (int e = EV_XA; e < EV_N + EV_XB; e++) {
          if (e == EV_XB) continue;
          const bool clr = (e & 7) == EV_XA;
          uint32_t* const f = ptr_add(fl, (clr ? 16 + e : e) * 128u);
          if (clr) {
            uint4* op = scratch<uint4>(P, g * G_BLOCK + G_O + j * 32768u + lane * 16u);
#pragma unroll 1
            for (int i = 0; i < 64; i++) { st_b128(op, 0, 0, 0, 0); op += 32; if (e || (i & 1)) __nanosleep(10); }
            __syncwarp();
            if (lane == 0) red_release(f, 1u << j);
          }
          uint32_t spins = 0, m;
          while ((m = ld_relaxed(f) - (tag - 1) * 255) != 255) { __nanosleep(m ? 50 : 500); spin_check(++spins); }
          asm volatile("fence.acquire.gpu;" ::: "memory");
          if (lane == 0) {
            if (clr) mbar_arrive(sb + BAR_CLR);
            else asm volatile("st.release.cta.shared.u32 [%0], %1;" :: "r"(sb + SM_SEEN), "r"(++seen) : "memory");
          }
          if (e == EV_H3) {
#pragma unroll 1
            for (int i = 0; i < 7; i++) { if (elect_one()) prefetch_l2(ptr_add(P.w2, (i * 128 + role) * 8192u), 8192); __nanosleep(500); }
          }
          __syncwarp();
        }
      } else if (warp == 9) {
        if (elect_one()) {
          prefetch_map(&P.map[M_WQ]); prefetch_map(&P.map[M_OUT_LD]); prefetch_map(&P.map[M_WO]); prefetch_map(&P.map[M_W1 + rank]);
          prefetch_map(&P.map[M_H_ST]); prefetch_map(&P.map[M_H_LD]); prefetch_map(&P.map[M_W1H + rank]); prefetch_map(&P.map[M_W2]); prefetch_map(&P.map[M_OUT_ST]);
          uint32_t* fl = scratch<uint32_t>(P, g * G_BLOCK + G_FLAGS);
          int pe = 0;
#pragma unroll 1
          for (int e = 0; e < 2 * EV_N; e++) {
            const int q = e & 7;
            const bool is_h = q >= EV_H0 && q < EV_XB, last = e >= EV_N + EV_XB;
            const CUtensorMap* map = &P.map[is_h ? M_H_ST : M_OUT_ST];
            const int col = q == EV_H3 ? 3072 - 64 + j * 64 : (q == EV_H1 ? 1024 : q == EV_H2 ? 2048 : 0) + j * 128;
            const int row = is_h ? 0 : (g >> 1) * 128, par = is_h ? g : g & 1;
#pragma unroll 1
            for (int hb = is_h ? q == EV_H3 : q & 1; hb <= (is_h ? 1 : q & 1); hb++) {
#pragma unroll
              for (int w = 0; w < 2; w++) {
                const bool sw = last;
                const int wg = sw ? hb : w, h = sw ? w : hb, p = sw ? pe - hb + w : pe;
                mbar_wait(sb + BAR_SFULL + 16 * wg + 8 * (p & 1), (p >> 1) & 1);
                if (w == 0) TL(3, 20 + e);
                tma_st3(map, sb + SM_STAGE + wg * PAGE + h * 8192, col + h * 64, par, row + wg * 64);
              }
              pe++;
            }
            bulk_commit();
            if (e != EV_N + EV_XB) bulk_wait<0>();
            TL(3, 40 + e);
            if (is_h || (q & 1)) mbar_arrive(sb + BAR_SEMPTY);
            if (!last) red_release(fl, 1u << j);
            TL(3, e);
            fl += 32;
          }
          *epoch_ptr(P) = tag;
        }
      }
    }
  } else {
    if (!spare) {
      const uint32_t r = threadIdx.x >> 3, so = r * 128 + (((threadIdx.x ^ r) & 7) << 4);
      const uint8_t* xp = ptr_add((const uint8_t*)P.x, (2 * ((g >> 1) * 128 + r) + (g & 1)) * 2048u + (threadIdx.x & 7) * 16u);
      const uint8_t* wp = ptr_add((const uint8_t*)P.wqkv, r * 6144u + 2048u + j * 256u + (threadIdx.x & 7) * 16u);
#pragma unroll
      for (int i = 0; i < 4; i++) asm volatile("cp.async.cg.shared.global [%0], [%1], 16;" :: "r"(sb + SM_STAGE + (i >> 1) * PAGE + (i & 1) * 4096 + so), "l"(xp + i * 32 * 4096) : "memory");
#pragma unroll
      for (int i = 0; i < 8; i++) asm volatile("cp.async.cg.shared.global [%0], [%1], 16;" :: "r"(sb + i * 4096 + so), "l"(wp + (i & 1) * 32 * 6144 + ((i >> 1) & 1) * 128 + (i >> 2) * 2048) : "memory");
    }
    if (!spare) {
      if (warp == 0) asm volatile("prefetch.global.L2 [%0];" :: "l"(ptr_add(P.x, (2 * ((g >> 1) * 128 + j * 16 + (lane >> 1)) + (g & 1)) * 2048u + (lane & 1) * 128u)));
      else if (warp < 3 && (warp == 1 || lane < 16)) asm volatile("prefetch.global.L2 [%0];" :: "l"(ptr_add(P.wqkv, role * 6144u + (warp - 1) * 4096u + lane * 128u)));
      __syncwarp();
    }
    asm volatile("barrier.cluster.arrive.relaxed.aligned;" ::: "memory");
    asm volatile("setmaxnreg.inc.sync.aligned.u32 232;");
    SP(4);
    asm volatile("barrier.cluster.wait.acquire.aligned;" ::: "memory");
    SP(5);
    const int wg = warp >> 2;
    const int quad = lane & 3, gr = lane >> 2;
    Cons c; c.sb = sb; c.n = 0; c.off = 0; c.prev = 0; c.lane = lane;
    c.ebar = mapa(sb + BAR_EMPTY - 64, shared_b() ? lane & 1 : rank);
    const uint32_t stage = sb + SM_STAGE + wg * PAGE;
    const uint32_t dstage = desc_lo(stage, 16);
    if (spare) {
      const uint32_t tag = ld_relaxed(epoch_ptr(P)) + 1;
      const int tid = threadIdx.x & 127;
#pragma unroll
      for (int i = 0; i < 4; i++) sts128(stage + (i * 128 + tid) * 16, 0x3f803f80u, 0x3f803f80u, 0x3f803f80u, 0x3f803f80u);
      fence_async_smem();
      bar_sync(2 + wg, 128);
      c.db0 = desc_lo(sb + wg * PAGE, 8192);
#pragma unroll 1
      for (int r = -1; r < 7; r++) {
        float acc[64];
#pragma unroll 1
        for (int k = 0; k < 16; k++) c.step_ab<128, 2>(acc, dstage, c.db0 + c.off, k);
        c.drain();
        acc_fence<64>(acc);
        {
          float v = 0;
#pragma unroll
          for (int i = 0; i < 32; i++) asm("{\n.reg .pred p;\nsetp.eq.u32 p, %2, %3;\nselp.f32 %0, %1, %0, p;\n}" : "+f"(v) : "f"(acc[4 * (i >> 1) + (i & 1)]), "r"(tid >> 2), "r"(i));
          st_b128(scratch<uint4>(P, G_CS + (uint32_t)((r < 0 ? j * 256 + wg * 128 : 3 * DM + wg * FF + ((r < 2 ? r : r == 2 ? 6 : r - 1) * 4 + j) * 128) + (tid >> 3) * 8 + quad * 2 + (gr & 1)) * 16u),
                  tagf(v, tag), tag & 15u, tag & 15u, tag & 15u);
        }
        __syncwarp();
      }
      if (wg == 0) {
        const uint32_t* p = scratch<uint32_t>(P, (tid >> 3) * G_BLOCK + G_STATS + (tid & 7) * 8u);
        uint32_t spins = 0;
        while (__any_sync(0xffffffffu, (ld_relaxed(p) ^ tag) & 15u)) spin_check(++spins);
      }
      bar_sync(1, 256);
      if (threadIdx.x == 0) *epoch_ptr(P) = tag;
    } else {
    c.da0 = desc_lo(sb + wg * 8192, 16); c.db0 = desc_lo(sb, 8192);
    uint32_t sphase = 1, sfull = sb + BAR_SFULL + 16 * wg;
    const uint32_t maddr = stage + ((warp & 3) * 16 + (lane & 15)) * 128 + (((lane >> 4) ^ (lane & 7)) << 4);
    const uint32_t csaddr = sb + SM_CS + quad * 16;
    float st[8] = {0, 0, 0, 0, 0, 0, 0, 0};
    float* const mean = st; float* const rstd = st + 2;
    SP(6);

    auto stage_wait = [&]() { mbar_wait_fast(sb + BAR_SEMPTY, sphase); sphase ^= 1; };
    auto stage_publish = [&]() { fence_async_smem(); __syncwarp(); if (lane == 0) mbar_arrive(sfull); sfull ^= 8; };
    auto cs_load = [&](uint32_t (&cs)[16], int grp) {
#pragma unroll
      for (int i = 0; i < 4; i++) lds128(csaddr + grp * 256 + i * 64, cs[4 * i], cs[4 * i + 1], cs[4 * i + 2], cs[4 * i + 3]);
    };
    auto cs_apply = [&](float* acc, uint32_t (&cs)[16]) {
      acc_fence<32>(acc);
#pragma unroll
      for (int b = 0; b < 8; b++) {
        acc[4 * b] -= mean[0] * __uint_as_float(cs[2 * b]); acc[4 * b + 1] -= mean[0] * __uint_as_float(cs[2 * b + 1]);
        acc[4 * b + 2] -= mean[1] * __uint_as_float(cs[2 * b]); acc[4 * b + 3] -= mean[1] * __uint_as_float(cs[2 * b + 1]);
      }
      acc_fence<32>(acc);
    };
    auto glu_pair = [&](float g0, float g1, float u0, float u1, int r) {
      const float nl = -LOG2E * rstd[r], r2 = rstd[r] * rstd[r];
      return pack_bf16(g0 * u0 * r2 * rcp(1.0f + ex2(g0 * nl)), g1 * u1 * r2 * rcp(1.0f + ex2(g1 * nl)));
    };
    auto glu_slice = [&](uint32_t (&pk)[64], int i) {
      uint32_t hp[4];
#pragma unroll
      for (int e = 0; e < 4; e++) {
        asm volatile("" : "+r"(pk[4 * i + e]), "+r"(pk[32 + 4 * i + e]));
        const uint32_t pg = pk[4 * i + e], pu = pk[32 + 4 * i + e];
        hp[e] = glu_pair(bf_lo(pg), bf_hi(pg), bf_lo(pu), bf_hi(pu), e & 1);
      }
      stsm4((maddr ^ ((i & 3) << 5)) + (i >> 2) * 8192, hp[0], hp[1], hp[2], hp[3]);
    };
    auto glu_slice_acc = [&](float (&acc)[128], int i) {
      uint32_t hp[4];
      acc_fence<8>(acc + 8 * i);
#pragma unroll
      for (int e = 0; e < 4; e++) hp[e] = glu_pair(acc[8 * i + 2 * e], acc[8 * i + 2 * e + 1], acc[64 + 8 * i + 2 * e], acc[64 + 8 * i + 2 * e + 1], e & 1);
      stsm4((maddr ^ ((i & 3) << 5)) + (i >> 2) * 8192, hp[0], hp[1], hp[2], hp[3]);
    };
    auto stage_x = [&](uint32_t (&x)[32], int hf) {
#pragma unroll
      for (int i = 4 * hf; i < 4 * hf + 4; i++) stsm4((maddr ^ ((i & 3) << 5)) + hf * 8192, x[4 * i], x[4 * i + 1], x[4 * i + 2], x[4 * i + 3]);
    };

    float acc[128];
    asm volatile("cp.async.wait_all;" ::: "memory");
    fence_async_smem();
    bar_sync(1, 256);
    SP(7);
    c.step_own<256>(acc, dstage, 0);
    mbar_wait_fast(sb + BAR_XIN, 0);
    SP(8);
#pragma unroll 1
    for (int hl = 0;; hl++) {
      int t = hl & 1;
      float acc2[64];
      uint32_t res[32];
      c.step_own<256>(acc, dstage + 512, 1);
#pragma unroll
      for (int s = 0; s < 2; s++) c.step_own<128>(acc2, dstage + s * 512, s);
#pragma unroll 1
      for (int s = 2; s < 11; s++) {
        const uint32_t apage = (c.off << 4) - (SM_STAGE + wg * 8192);
        c.step<256>(acc);
        int act = s;
        asm volatile("" : "+r"(act));
        auto get_tag = [&]() { uint32_t tag; asm volatile("ld.shared.u32 %0, [%1];" : "=r"(tag) : "r"(sb + SM_TAG) : "memory"); return tag; };
        auto stat_ptr = [&]() { return scratch<uint2>(P, g * G_BLOCK + G_STATS + (hl * 128 + warp * 16 + (lane_now() >> 2)) * 64u); };
        auto stat_get = [&]() {
          const uint2* sp = ptr_add(stat_ptr(), (lane_now() & 3) * 16);
          const uint4 a = ld_relaxed4(sp), b = ld_relaxed4(sp + 64);
          st[0] = __uint_as_float(a.x); st[1] = __uint_as_float(a.y); st[2] = __uint_as_float(a.z); st[3] = __uint_as_float(a.w);
          st[4] = __uint_as_float(b.x); st[5] = __uint_as_float(b.y); st[6] = __uint_as_float(b.z); st[7] = __uint_as_float(b.w);
        };
        switch (act) {
          case 4: case 5: {
            const uint32_t ra = maddr + ((hl || j == 0) ? (s & 1) * 8192 : apage);
#pragma unroll
            for (int i = 0; i < 4; i++) {
              uint32_t v[4];
              ldsm4(ra ^ (i << 5), v[0], v[1], v[2], v[3]);
              if (i == 0 && s == 4) { st[0] = bf_lo(v[0]); st[1] = bf_lo(v[1]); st[2] = st[3] = st[4] = st[5] = 0; }
#pragma unroll
              for (int e = 0; e < 4; e++) {
                const float a = bf_lo(v[e]) - st[e & 1], b = bf_hi(v[e]) - st[e & 1];
                st[2 + (e & 1)] += a + b; st[4 + (e & 1)] += a * a; st[4 + (e & 1)] += b * b;
              }
            }
          } break;
          case 6: {
            mbar_wait_fast(sb + BAR_TAG, 0);
            const uint32_t tag = get_tag();
#pragma unroll
            for (int r = 0; r < 2; r++) {
              const float mt = st[r] + st[2 + r] * (1.0f / 32);
              float m = mt + __shfl_xor_sync(0xffffffffu, mt, 1); m += __shfl_xor_sync(0xffffffffu, m, 2); m *= 0.25f;
              float q = st[4 + r] - st[2 + r] * st[2 + r] * (1.0f / 32) + 32.0f * (mt - m) * (mt - m);
              q += __shfl_xor_sync(0xffffffffu, q, 1); q += __shfl_xor_sync(0xffffffffu, q, 2);
              if (quad == 0) st_relaxed2(ptr_add(stat_ptr(), r * 512 + j * 8), tagf(m, tag), tagf(q, tag));
            }
          } break;
          case 8: stat_get(); break;
          case 10: {
            const uint32_t tag = get_tag();
            uint32_t spins = 0;
            for (;;) {
              uint32_t bad = 0;
#pragma unroll
              for (int i = 0; i < 8; i++) bad |= __float_as_uint(st[i]) ^ tag;
              if (!__any_sync(0xffffffffu, bad & 15u)) break;
              stat_get(); spin_check(++spins);
            }
            float mr[4];
#pragma unroll
            for (int r = 0; r < 2; r++) {
              const float m0 = untag(__float_as_uint(st[4 * r])), m1 = untag(__float_as_uint(st[4 * r + 2]));
              float m = m0 + m1; m += __shfl_xor_sync(0xffffffffu, m, 1); m += __shfl_xor_sync(0xffffffffu, m, 2); m *= 0.125f;
              float q = untag(__float_as_uint(st[4 * r + 1])) + untag(__float_as_uint(st[4 * r + 3])) + 128.0f * ((m0 - m) * (m0 - m) + (m1 - m) * (m1 - m));
              q += __shfl_xor_sync(0xffffffffu, q, 1); q += __shfl_xor_sync(0xffffffffu, q, 2);
              mr[r] = m; mr[2 + r] = rsqrtf(fmaxf(q, 0.f) * (1.0f / DM) + LN_EPS);
            }
            st[0] = mr[0]; st[1] = mr[1]; st[2] = mr[2]; st[3] = mr[3];
          } break;
          default: break;
        }
      }
#pragma unroll 1
      for (;;) {
      const int it = (hl >> 1) * 4 + t;
#pragma unroll
      for (int s = 0; s < 4; s++) {
        uint32_t cs[16];
        c.step<256>(acc);
        if (!(s & 1)) mbar_wait_fast(sb + BAR_CSF + 4 * s, t & 1);
        if (s >= 2 && t <= 1) { cs_load(cs, 2 + s); cs_apply(acc2 + 32 * (s - 2), cs); }
        cs_load(cs, s);
        c.drain();
        cs_apply(acc + 32 * s, cs);
      }
      c.step<256>(acc);
      if (lane == 0) mbar_arrive(sb + BAR_CSE);
      c.drain();
      acc_fence<128>(acc);
      TLC(1 + it * 6);
      uint32_t pkB[64];
      if (t == 2) {
#pragma unroll
        for (int i = 0; i < 64; i++) pkB[i] = pack_bf16(acc[2 * i], acc[2 * i + 1]);
      } else if (t == 0) {
        uint32_t pkA[64];
        auto kv_pack = [&](int v, int r) {
#pragma unroll
          for (int i = 32 * v + r; i < 32 * v + 32; i += 2) { acc_fence<2>(acc + 2 * i); pkA[i] = pack_bf16(acc[2 * i] * rstd[r], acc[2 * i + 1] * rstd[r]); }
        };
        const uint32_t l16 = lane_now() * 16u;
        uint4* const xs = ptr_add((uint4*)smem_raw, SM_STAGE + l16);
        uint4* const hp = scratch<uint4>(P, G_HALO + (((hl >> 1) * 16 + g) * 8 + j) * 4096u + l16);
        {
          uint4* const dst = (warp == 7 && g < 14) ? hp : ptr_add(xs, warp * 4096u);
#pragma unroll
          for (int s = 0; s < 2; s++) {
            c.steps<128>(acc2, s ? 2 : 1 + wg);
            if (s == 0) stage_wait();
            kv_pack(s, 1);
#pragma unroll
            for (int i = 4 * s; i < 4 * s + 4; i++) { pkA[8 * i + 1] = pkt_head(pkA[8 * i + 1]); gen_store(dst + i * 32, pkA[8 * i + 1], pkA[8 * i + 3], pkA[8 * i + 5], pkA[8 * i + 7]); }
          }
        }
        __syncwarp();
        if (lane == 0) mbar_arrive(sb + BAR_XFULL);
#pragma unroll
        for (int s = 0; s < 2; s++) {
          c.steps<128>(acc2, 2);
#pragma unroll
          for (int i = 33 - s; i < 64; i += 2) pkA[i] = movm(pkA[i]);
          kv_pack(1 - s, 0);
        }
        uint32_t kvH[32];
        {
          const uint4* const src = (warp == 0 && g >= 2) ? hp - 2 * 8 * 256 : ptr_add(xs, (warp ? warp - 1 : 0) * 4096u);
          c.steps<128>(acc2, 2);
          mbar_wait_fast(sb + BAR_XFULL, hl >> 1);
#pragma unroll
          for (int i = 0; i < 8; i++) gen_load(src + i * 32, kvH + 4 * i);
          c.steps<128>(acc2, 3 - wg);
          uint32_t spins = 0;
          while (__any_sync(0xffffffffu, !(kvH[0] && kvH[4] && kvH[8] && kvH[12] && kvH[16] && kvH[20] && kvH[24] && kvH[28]))) {
#pragma unroll
            for (int i = 0; i < 8; i++) gen_load(src + i * 32, kvH + 4 * i);
            spin_check(++spins);
          }
        }
#pragma unroll
        for (int i = 16; i < 32; i++) kvH[i] = movm(kvH[i]);
        mbar_wait_fast(sb + BAR_CLR, hl >> 1);
        c.steps<128>(acc2, 2);
        AP(0);
        c.wait_full(0);
        AP(1);
        c.drain();
        AP(2);
        acc_fence<64>(acc2);
        TLC(2 + it * 6);
        uint32_t q[32];
#pragma unroll
        for (int i = 0; i < 32; i++) q[i] = pack_bf16(acc2[2 * i], acc2[2 * i + 1]);
        const uint32_t zm = bar_sync_zero(1, 256);
        AP(3);
        uint32_t ob[6][16];
        uint4* const omail = scratch<uint4>(P, g * G_BLOCK + G_O + warp * 2048u + l16);
        float o2[8][4], r2[4];
        {
          const float hv = (warp == 0 && g < 2) ? -INFINITY : 0.f;
          const float hinit[4] = {hv, hv, hv, hv};
          const bool c0 = (2 * quad <= gr), c1 = (2 * quad + 1 <= gr);
          const uint32_t lm = (c0 ? 0xffffu : 0u) | (c1 ? 0xffff0000u : 0u);
          const float sc[2] = {rstd[0] * (0.17677669529663687f * LOG2E), rstd[1] * (0.17677669529663687f * LOG2E)};
          float lg[4][4], mx[4][2];
#pragma unroll
          for (int h = 0; h < 4; h++) {
            const int b = h * 4;
            float sH[4], sL[4], sU[4];
            q[2 * b] |= zm;
            mma16816(sH, q[2 * b], q[2 * b + 1], q[2 * b + 2], q[2 * b + 3], kvH[b], kvH[b + 1], hinit);
            mma16816z(sL, q[2 * b], q[2 * b + 1], q[2 * b + 2], q[2 * b + 3], pkA[2 * b], pkA[2 * b + 2]);
            mma16816z(sU, q[2 * b], q[2 * b + 1], q[2 * b + 2], q[2 * b + 3], pkA[2 * b + 1], pkA[2 * b + 3]);
            mma16816(sH, q[2 * b + 4], q[2 * b + 5], q[2 * b + 6], q[2 * b + 7], kvH[b + 2], kvH[b + 3], sH);
            mma16816(sL, q[2 * b + 4], q[2 * b + 5], q[2 * b + 6], q[2 * b + 7], pkA[2 * b + 4], pkA[2 * b + 6], sL);
            mma16816(sU, q[2 * b + 4], q[2 * b + 5], q[2 * b + 6], q[2 * b + 7], pkA[2 * b + 5], pkA[2 * b + 7], sU);
            lg[h][0] = c0 ? sL[0] : sH[0]; lg[h][1] = c1 ? sL[1] : sH[1]; lg[h][2] = c0 ? sU[2] : sL[2]; lg[h][3] = c1 ? sU[3] : sL[3];
            mx[h][0] = fmaxf(lg[h][0], lg[h][1]); mx[h][1] = fmaxf(lg[h][2], lg[h][3]);
          }
#pragma unroll
          for (int o = 1; o < 4; o <<= 1) {
#pragma unroll
            for (int i = 0; i < 8; i++) mx[i >> 1][i & 1] = fmaxf(mx[i >> 1][i & 1], __shfl_xor_sync(0xffffffffu, mx[i >> 1][i & 1], o));
          }
          AP(4);
          uint32_t z = zm, pp[4][2];
          float rs[4][2];
          auto probs = [&](int h) {
            pp[h][0] = pack_bf16(ex2((lg[h][0] - mx[h][0]) * sc[0]), ex2((lg[h][1] - mx[h][0]) * sc[0]));
            pp[h][1] = pack_bf16(ex2((lg[h][2] - mx[h][1]) * sc[1]), ex2((lg[h][3] - mx[h][1]) * sc[1]));
            float sum[4];
            mma1688z(sum, pp[h][0], pp[h][1], 0x3f803f80u);
            rs[h][0] = rcp(sum[0]); rs[h][1] = rcp(sum[2]);
            asm volatile("" : "+f"(rs[h][0]), "+f"(rs[h][1]));
          };
          probs(0); probs(1); probs(2); probs(3);
#pragma unroll
          for (int hf = 0; hf < 2; hf++) {
#pragma unroll
            for (int hh = 0; hh < 2; hh++) {
              const int h = hf * 2 + hh, b = h * 4;
              const uint32_t pa = pp[h][0], pb = pp[h][1];
              const uint32_t p0 = pa & ~lm, p1 = pa & z, p2 = pa & lm, p3 = pb & ~lm, p4 = pb & z, p5 = pb & lm;
              const float ra = rs[h][0], rb = rs[h][1];
#pragma unroll
              for (int d = 0; d < 4; d++) {
                float o[4];
                mma16816z(o, p0, p1, p2, p3, kvH[16 + b + d], pkA[32 + 2 * (b + d)]);
                mma1688(o, p4, p5, pkA[32 + 2 * (b + d) + 1], o);
                if (hf == 0) { ob[0][(hh * 4 + d) * 2] = pack_bf16(o[0] * ra, o[1] * ra); ob[0][(hh * 4 + d) * 2 + 1] = pack_bf16(o[2] * rb, o[3] * rb); }
                else { o2[hh * 4 + d][0] = o[0]; o2[hh * 4 + d][1] = o[1]; o2[hh * 4 + d][2] = o[2]; o2[hh * 4 + d][3] = o[3]; }
              }
              if (hf) { r2[2 * hh] = ra; r2[2 * hh + 1] = rb; }
            }
            if (hf == 0) {
#pragma unroll
              for (int i = 0; i < 4; i++) ob[0][4 * i] = pkt_head(ob[0][4 * i]);
              AP(5);
              uint4* op = ptr_add(omail, j * 32768u);
#pragma unroll
              for (int i = 0; i < 4; i++) st_b128(op + i * 32, ob[0][4 * i], ob[0][4 * i + 1], ob[0][4 * i + 2], ob[0][4 * i + 3]);
              z = late_zero(zm);
              AP(6);
            }
          }
        }
        auto finish_o2 = [&](uint32_t z) {
#pragma unroll
          for (int i = 0; i < 4; i++) r2[i] = __uint_as_float(__float_as_uint(r2[i]) | z);
#pragma unroll
          for (int i = 0; i < 8; i++) {
            ob[1][2 * i] = pack_bf16(o2[i][0] * r2[(i >> 2) * 2], o2[i][1] * r2[(i >> 2) * 2]);
            ob[1][2 * i + 1] = pack_bf16(o2[i][2] * r2[(i >> 2) * 2 + 1], o2[i][3] * r2[(i >> 2) * 2 + 1]);
          }
#pragma unroll
          for (int i = 0; i < 4; i++) { ob[1][4 * i] = pkt_head(ob[1][4 * i]); sts128(stage + (warp & 3) * 2048 + i * 512 + l16, ob[1][4 * i], ob[1][4 * i + 1], ob[1][4 * i + 2], ob[1][4 * i + 3]); }
        };
        {
          uint32_t dep = __float_as_uint(r2[0]) | __float_as_uint(r2[2]);
#pragma unroll
          for (int i = 0; i < 8; i++) dep |= __float_as_uint(o2[i][3]);
          const uint32_t cnt = 256 | (dep & zm);
          AP(7);
          if (wg) { asm volatile("bar.arrive 1, %0;" :: "r"(cnt) : "memory"); bar_sync(6, 256); } else bar_sync(1, cnt);
        }
        TLC(3 + it * 6);
        AP(8);
        uint64_t todo;
        { const uint32_t o7 = 0x6543210u | (7u << (4 * j) & 0xfffffffu); todo = (uint64_t)(o7 * 2) | (uint64_t)(o7 * 2 + 0x1111111u) << 28; }
        const uint4* pf[3];
        auto next_ptrs = [&](const uint4* (&p)[3]) {
#pragma unroll
          for (int i = 0; i < 3; i++) p[i] = ptr_add(omail, (((uint32_t)todo >> (4 * i)) & 15u) << 14);
          asm volatile("" : "+l"(p[0]), "+l"(p[1]), "+l"(p[2]));
          todo >>= 12;
        };
        next_ptrs(pf);
        auto batch = [&](int b, bool first, bool three) {
          const int y = 3 - b;
          auto o_fetch = [&]() {
#pragma unroll
            for (int i = 0; i < 8; i++) pkt_load(pf[i >> 2] + (i & 3) * 32, ob[y + (i >> 2)] + 4 * (i & 3));
            if (three) {
#pragma unroll
              for (int i = 0; i < 4; i++) pkt_load(pf[2] + i * 32, ob[y + 2] + 4 * i);
            }
          };
          if (first) {
            c.issue_rs<0, 2>(acc2, ob[0], 0);
            finish_o2(late_zero(zm));
            o_fetch();
            c.issue_rs<1, 2>(acc2, ob[1]);
            if (!wg) asm volatile("bar.arrive 6, 256;" ::: "memory");
          } else {
            o_fetch();
            c.issue_rs<0, 3>(acc2, ob[b]); c.issue_rs<1, 3>(acc2, ob[b + 1]); c.issue_rs<2, 3>(acc2, ob[b + 2]);
          }
          const uint32_t z = late_zero(zm);
          const uint4* pn[3];
          next_ptrs(pn);
          c.wait_full(0);
          uint32_t spins = 0;
          for (;;) {
            bool bad[3];
#pragma unroll
            for (int i = 0; i < 3; i++) bad[i] = ob[y + i][0] == z || ob[y + i][4] == z || ob[y + i][8] == z || ob[y + i][12] == z;
            if (__builtin_expect(!__any_sync(0xffffffffu, bad[0] | bad[1] | bad[2]), 1)) break;
            o_fetch();
            spin_check(++spins);
          }
          if (first) {
            fence_async_smem();
            __syncwarp();
            if (elect_one()) {
              asm volatile("cp.async.bulk.global.shared::cta.bulk_group [%0], [%1], 2048;"
                           :: "l"(scratch<uint4>(P, g * G_BLOCK + G_O + (2 * j + 1) * 16384u + warp * 2048u)), "r"(stage + (warp & 3) * 2048) : "memory");
              bulk_commit();
            }
          }
          pf[0] = pn[0]; pf[1] = pn[1]; pf[2] = pn[2];
          c.drain();
        };
        batch(0, true, true);
#pragma unroll 1
        for (int i = 0; i < 2; i++) { batch(3, false, true); batch(0, false, i == 0); }
        c.issue_rs<0, 2>(acc2, ob[3]); c.issue_rs<1, 2>(acc2, ob[4]);
        if (elect_one()) bulk_wait<0>();
        __syncwarp();
        {
          c.off += 2 << 10;
          c.wait_full(0);
          const uint32_t ra = maddr - (SM_STAGE + wg * 8192) + (c.off << 4);
#pragma unroll
          for (int i = 0; i < 8; i++) ldsm4((ra ^ ((i & 3) << 5)) + (i >> 2) * PAGE, res[4 * i], res[4 * i + 1], res[4 * i + 2], res[4 * i + 3]);
          if (lane < 2) mbar_arrive_cluster(c.ebar + 64 + ((c.n & 7) << 3));
          c.advance<2>();
          c.drain();
        }
        break;
      } else {
        c.steps<128>(acc2, 1 + wg);
        stage_wait();
        glu_slice_acc(acc, 0);
#pragma unroll
        for (int s = 1; s < 8; s++) {
          if (s == 5) c.steps_skip(acc2, t == 1 ? 1 - wg : 2); else c.steps<128>(acc2, (s & 1) || t == 3 ? 2 : 1);
          if (s == 4) stage_publish();
          glu_slice_acc(acc, s);
        }
        c.steps<128>(acc2, 2 - wg);
        stage_publish();
        if (t == 3) {
#pragma unroll
          for (int i = 0; i < 32; i++) { res[i] = 0x80008000u; asm volatile("" : "+r"(res[i])); }
#pragma unroll 1
          for (int i = 0; i < 3; i++) {
            c.steps<128>(acc2, i == 0 ? 15 : i == 1 ? 24 - TAIL_LAG : TAIL_LAG);
            if (i == 0) c.off = 0;
            else if (LAG_ALL || hl == 3) { if (wg == 1 && i == 1) { c.drain(); bar_sync(5, 256); } else if (wg == 0 && i == 2) asm volatile("bar.arrive 5, 256;" ::: "memory"); }
          }
          stage_wait();
          c.drain();
          break;
        }
        c.drain();
        TLC(2 + it * 6);
        c.step<256>(acc, 0);
        acc_fence<64>(acc2);
#pragma unroll
        for (int i = 0; i < 16; i++) {
          pkB[16 + i] = pack_bf16(acc2[2 * i], acc2[2 * i + 1]); pkB[48 + i] = pack_bf16(acc2[32 + 2 * i], acc2[32 + 2 * i + 1]);
          pkB[i] = 0; pkB[32 + i] = 0;
        }
      }
      t++;
#pragma unroll 1
      for (int s = 3 - t; s < 8; s++) {
        c.step<256>(acc, s);
        int act = (t == 3 || s >= 4) ? s : 8;
        asm volatile("" : "+r"(act));
        if (act < 8) {
          if (!(act & 3)) { if (act && t == 3) stage_publish(); else stage_wait(); }
          auto f = [&](int i) { glu_slice(pkB, i); };
          SELECT8(act, f);
        }
      }
#pragma unroll
      for (int s = 0; s < 2; s++) {
        const uint32_t ra = maddr - (SM_STAGE + wg * 8192) + (c.off << 4);
        c.step<256>(acc);
        if (s == 0) stage_publish();
#pragma unroll
        for (int i = 0; i < 4; i++) {
          uint32_t v[4];
          ldsm4(ra ^ (i << 5), v[0], v[1], v[2], v[3]);
#pragma unroll
          for (int e = 0; e < 4; e++) { acc2[32 * s + 8 * i + 2 * e] = bf_lo(v[e]); acc2[32 * s + 8 * i + 2 * e + 1] = bf_hi(v[e]); }
        }
        acc_fence<32>(acc2 + 32 * s);
      }
      c.step<256>(acc);
      }
      const int it = (hl >> 1) * 4 + t;
      acc_fence<64>(acc2);
      TLC(4 + it * 6);
      uint32_t xn[32];
#pragma unroll
      for (int i = 0; i < 16; i++) xn[i] = add_bf16x2(res[i], pack_bf16(acc2[2 * i], acc2[2 * i + 1]));
      stage_x(xn, 0);
#pragma unroll
      for (int i = 16; i < 32; i++) { xn[i] = add_bf16x2(res[i], pack_bf16(acc2[2 * i], acc2[2 * i + 1])); asm volatile("" : "+r"(xn[i])); }
      stage_publish();
      if (hl == 3) { stage_x(xn, 1); stage_publish(); TLE(47); TLG(63); break; }
      bar_sync(2 + wg, 128);
      TLC(5 + it * 6);
      c.step_own<256>(acc, dstage, 0);
      stage_x(xn, 1);
      stage_publish();
      bar_sync(2 + wg, 128);
    }
    }
  }
}

typedef CUresult (*EncodeFn)(CUtensorMap*, CUtensorMapDataType, cuuint32_t, void*, const cuuint64_t*, const cuuint64_t*, const cuuint32_t*,
                             const cuuint32_t*, CUtensorMapInterleave, CUtensorMapSwizzle, CUtensorMapL2promotion, CUtensorMapFloatOOBfill);

void encode(EncodeFn fn, CUtensorMap* m, const void* ptr, int rank, const cuuint64_t* dims, const cuuint64_t* strides, const cuuint32_t* box) {
  cuuint32_t es[5] = {1, 1, 1, 1, 1};
  fn(m, CU_TENSOR_MAP_DATA_TYPE_BFLOAT16, rank, const_cast<void*>(ptr), dims, strides, box, es, CU_TENSOR_MAP_INTERLEAVE_NONE,
     CU_TENSOR_MAP_SWIZZLE_128B, CU_TENSOR_MAP_L2_PROMOTION_L2_128B, CU_TENSOR_MAP_FLOAT_OOB_FILL_NONE);
}

}

extern "C" void kernel_launch(void* const* d_in, const int* in_sizes, int n_in, void* d_out, int out_size) {
  const __nv_bfloat16* x = (const __nv_bfloat16*)d_in[0];
  const __nv_bfloat16* wqkv = (const __nv_bfloat16*)d_in[1];
  const __nv_bfloat16* wo = (const __nv_bfloat16*)d_in[2];
  const __nv_bfloat16* w1 = (const __nv_bfloat16*)d_in[4];
  const __nv_bfloat16* w3 = (const __nv_bfloat16*)d_in[5];
  const __nv_bfloat16* w2 = (const __nv_bfloat16*)d_in[6];

  void* fnp = nullptr; cudaDriverEntryPointQueryResult qr;
  cudaGetDriverEntryPoint("cuTensorMapEncodeTiled", &fnp, cudaEnableDefault, &qr);
  EncodeFn fn = (EncodeFn)fnp;
  void* sym;
  cudaGetSymbolAddress(&sym, g_scratch);
  uint8_t* scr = (uint8_t*)(((uintptr_t)sym + G_PAGE - 1) / G_PAGE * G_PAGE);

  Params P = {};
  { cuuint64_t d[3] = {DM, 2, SEQ / 2}, s[2] = {DM * 2, DM * 4}; cuuint32_t b[3] = {64, 1, 128}, b2[3] = {64, 1, 64};
    encode(fn, &P.map[M_XIN], x, 3, d, s, b); encode(fn, &P.map[M_XIN64], x, 3, d, s, b2);
    encode(fn, &P.map[M_OUT_LD], d_out, 3, d, s, b); encode(fn, &P.map[M_OUT_ST], d_out, 3, d, s, b2); }
  { cuuint64_t d[3] = {FF, 16, 128}, s[2] = {G_BLOCK, FF * 2}; cuuint32_t b[3] = {64, 1, 128}, b2[3] = {64, 1, 64};
    encode(fn, &P.map[M_H_LD], scr + G_H, 3, d, s, b); encode(fn, &P.map[M_H_ST], scr + G_H, 3, d, s, b2); }
  { const cuuint32_t b2[3] = {64, 64, 2}, b1[3] = {64, 64, 1};
    { cuuint64_t d[3] = {64, DM, 48}, s[2] = {3 * DM * 2, 128}; encode(fn, &P.map[M_WKV], wqkv, 3, d, s, b2); encode(fn, &P.map[M_WQ], wqkv, 3, d, s, b1); }
    { cuuint64_t d[3] = {64, DM, 16}, s[2] = {DM * 2, 128}; encode(fn, &P.map[M_WO], wo, 3, d, s, b1); }
    { cuuint64_t d[3] = {64, FF, 16}, s[2] = {DM * 2, 128}; encode(fn, &P.map[M_W2], w2, 3, d, s, b1); }
    { cuuint64_t d[3] = {64, DM, FF / 64}, s[2] = {FF * 2, 128};
      encode(fn, &P.map[M_W1], w1, 3, d, s, b2); encode(fn, &P.map[M_W3], w3, 3, d, s, b2);
      encode(fn, &P.map[M_W1H], w1, 3, d, s, b1); encode(fn, &P.map[M_W3H], w3, 3, d, s, b1); }
  }
  P.scratch = scr; P.x = x; P.wqkv = wqkv; P.wo = wo; P.w2 = w2;
  int dev = 0, sms = 0;
  cudaGetDevice(&dev);
  cudaDeviceGetAttribute(&sms, cudaDevAttrMultiProcessorCount, dev);
  P.use_smid = (sms == 132);
  cudaFuncSetAttribute(fused_kernel, cudaFuncAttributeMaxDynamicSharedMemorySize, SM_ALLOC);
  fused_kernel<<<132, 384, SM_ALLOC>>>(P);
}
```

```cpp
#include <cuda_runtime.h>
#include <cuda_bf16.h>
#include <cuda.h>
#include <stdint.h>
#include <math.h>

namespace {

constexpr int SEQ = 2048, DM = 1024, FF = 3584;
constexpr float LN_EPS = 1e-5f;
constexpr float LOG2E = 1.4426950408889634f;

#define G_SKEW 4096
constexpr uint32_t G_PAGE = 2u << 20, G_BLOCK = G_PAGE + G_SKEW;
constexpr uint32_t G_H = 0;
constexpr uint32_t G_O = G_H + 128 * FF * 2;
constexpr uint32_t G_STATS = G_O + 128 * DM * 2;
constexpr uint32_t G_FLAGS = G_STATS + 4 * 128 * 64;
static_assert(G_FLAGS + 4096 + 15 * G_SKEW <= G_PAGE, "");
constexpr uint32_t G_HALO = 16 * G_PAGE;
constexpr uint32_t G_CS = G_HALO + 2 * 16 * 8 * 4096;
constexpr uint32_t G_EPOCH = G_CS + (3 * DM + 2 * FF) * 16;
__device__ __align__(1024) uint8_t g_scratch[18 * G_PAGE];

enum { M_XIN, M_XIN64, M_H_LD, M_H_ST, M_OUT_LD, M_OUT_ST, M_WKV, M_WQ, M_WO, M_W1, M_W3, M_W1H, M_W3H, M_W2, M_COUNT };
struct alignas(64) Params {
  CUtensorMap map[M_COUNT];
  uint8_t* scratch;
  const __nv_bfloat16* x;
  const __nv_bfloat16* wqkv;
  const __nv_bfloat16* wo;
  const __nv_bfloat16* w2;
  int use_smid;
};

constexpr uint32_t PAGE = 16384, NPAGE = 12;
constexpr uint32_t SM_STAGE = NPAGE * PAGE;
constexpr uint32_t SM_BAR = SM_STAGE + 2 * PAGE;
constexpr uint32_t SM_CS = SM_BAR + 256;
constexpr uint32_t SM_TOTAL = SM_CS + 1536;
constexpr uint32_t SM_ALLOC = SM_TOTAL;
static_assert(SM_ALLOC <= 232448, "shared memory");
constexpr uint32_t BAR_FULL = SM_BAR, BAR_EMPTY = SM_BAR + 64, BAR_SFULL = SM_BAR + 128;
constexpr uint32_t BAR_XFULL = SM_BAR + 160, BAR_CSE = SM_BAR + 168;
constexpr uint32_t BAR_SEMPTY = SM_BAR + 176, BAR_CSF = SM_BAR + 184, BAR_XIN = SM_BAR + 200;
constexpr uint32_t BAR_CLR = SM_BAR + 240, BAR_TAG = SM_BAR + 216, SM_ROLE = SM_BAR + 224, SM_TAG = SM_BAR + 228, SM_SEEN = SM_BAR + 232;
enum { EV_XA, EV_XA2, EV_H0, EV_H3, EV_H1, EV_H2, EV_XB, EV_XB2, EV_N };

struct Sched { uint32_t pat[16]; uint32_t page0[16]; bool ok; };
constexpr int seg_steps(int seg) { return seg == 0 || seg == 3 ? 18 : seg == 1 || seg == 4 ? 14 : seg == 2 ? 7 : seg == 7 ? 24 : 32; }
constexpr int step_pages(int seg, int i) {
  return seg == 0 || seg == 3 ? (i < 2 ? 2 : i < 4 ? 1 : 3) : seg == 5 || (seg == 2 && i >= 1 && i <= 4) ? 3 : 2;
}
constexpr Sched make_sched() {
  Sched s = {};
  int owner[NPAGE] = {-1, -1, -1, -1, -1, -1, -1, -1, -1, -1, -1, -1};
  int n = 0, tail = 0, page = 0;
  s.ok = true;
  for (int sg = 0; sg < 16; sg++) {
    const int seg = sg % 8;
    s.page0[sg] = page;
    for (int i = 0; i < seg_steps(seg); i++) {
      const int p = step_pages(seg, i);
      if ((seg == 2 && i == 6) || (seg == 4 && i == 8) || (seg == 7 && i == 0)) page = (page + 2) % NPAGE;
      if (page + p > (int)NPAGE) { s.ok = false; return s; }
      int need = n - 8;
      for (int q = 0; q < p; q++) { if (owner[page + q] > need) need = owner[page + q]; owner[page + q] = n; }
      int nw = need + 1 - tail; if (nw < 0) nw = 0;
      tail += nw;
      if (i < 16) s.pat[sg] |= (uint32_t)nw << (2 * i); else if (nw != 1) s.ok = false;
      if (nw > 3) s.ok = false;
      page = (page + p) % NPAGE; n++;
    }
  }
  for (int sg = 0; sg < 8; sg++) if (s.page0[sg] != s.page0[sg + 8] || (sg && s.pat[sg] != s.pat[sg + 8])) s.ok = false;
  return s;
}
constexpr Sched SCHED = make_sched();
static_assert(SCHED.ok && SCHED.page0[0] == 0 && SCHED.page0[3] == 0 && SCHED.page0[5] == 6 && SCHED.page0[2] == 4 && SCHED.page0[7] == 10 && (SCHED.pat[0] & 0xfff) == 0, "ring schedule");
template <int SEG> struct Pat { static constexpr uint32_t v = SCHED.pat[SEG]; };

#define TAIL_LAG 3
__device__ __forceinline__ uint32_t smem_u32(const void* p) { return (uint32_t)__cvta_generic_to_shared(p); }
__device__ __forceinline__ void mbar_init(uint32_t bar, uint32_t cnt) { asm volatile("mbarrier.init.shared::cta.b64 [%0], %1;" :: "r"(bar), "r"(cnt)); }
__device__ __forceinline__ void mbar_expect_tx(uint32_t bar, uint32_t bytes) { asm volatile("mbarrier.arrive.expect_tx.shared::cta.b64 _, [%0], %1;" :: "r"(bar), "r"(bytes) : "memory"); }
__device__ __forceinline__ void mbar_arrive(uint32_t bar) { asm volatile("mbarrier.arrive.shared::cta.b64 _, [%0];" :: "r"(bar) : "memory"); }
__device__ __forceinline__ void mbar_wait(uint32_t bar, uint32_t parity) {
  asm volatile("{\n.reg .pred p;\n.reg .u32 n;\nmov.u32 n, 0;\nLAB_WAIT:\n"
               "mbarrier.try_wait.parity.shared::cta.b64 p, [%0], %1;\n@p bra LAB_DONE;\n"
               "add.u32 n, n, 1;\nsetp.lt.u32 p, n, 4194304;\n@p bra LAB_WAIT;\ntrap;\nLAB_DONE:\n}" :: "r"(bar), "r"(parity) : "memory");
}
__device__ __forceinline__ void mbar_wait_fast(uint32_t bar, uint32_t parity) {
  asm volatile("{\n.reg .pred p;\nLAB_WAIT:\nmbarrier.try_wait.parity.shared::cta.b64 p, [%0], %1;\n@!p bra LAB_WAIT;\n}" :: "r"(bar), "r"(parity) : "memory");
}
__device__ __forceinline__ void spin_check(uint32_t n) { asm volatile("{\n.reg .pred p;\nsetp.ge.u32 p, %0, 4194304;\n@p st.volatile.global.u32 [%1], %0;\n}" :: "r"(n), "l"(0ull)); }
__device__ __forceinline__ void tma_ld3(uint32_t dst, const CUtensorMap* m, uint32_t bar, int c0, int c1, int c2) {
  asm volatile("cp.async.bulk.tensor.3d.shared::cluster.global.mbarrier::complete_tx::bytes [%0], [%1, {%3, %4, %5}], [%2];" :: "r"(dst), "l"(m), "r"(bar), "r"(c0), "r"(c1), "r"(c2) : "memory");
}
__device__ __forceinline__ void tma_ld3_mc(uint32_t dst, const CUtensorMap* m, uint32_t bar, int c0, int c1, int c2, uint16_t mask) {
  asm volatile("cp.async.bulk.tensor.3d.shared::cluster.global.mbarrier::complete_tx::bytes.multicast::cluster [%0], [%1, {%3, %4, %5}], [%2], %6;"
               :: "r"(dst), "l"(m), "r"(bar), "r"(c0), "r"(c1), "r"(c2), "h"(mask) : "memory");
}
__device__ __forceinline__ uint32_t mapa(uint32_t addr, uint32_t cta) { uint32_t r; asm("mapa.shared::cluster.u32 %0, %1, %2;" : "=r"(r) : "r"(addr), "r"(cta)); return r; }
__device__ __forceinline__ void mbar_arrive_cluster(uint32_t bar) { asm volatile("mbarrier.arrive.shared::cluster.b64 _, [%0];" :: "r"(bar) : "memory"); }
__device__ __forceinline__ void tma_st3(const CUtensorMap* m, uint32_t src, int c0, int c1, int c2) {
  asm volatile("cp.async.bulk.tensor.3d.global.shared::cta.bulk_group [%0, {%2, %3, %4}], [%1];" :: "l"(m), "r"(src), "r"(c0), "r"(c1), "r"(c2) : "memory");
}
__device__ __forceinline__ void bulk_commit() { asm volatile("cp.async.bulk.commit_group;" ::: "memory"); }
template <int N> __device__ __forceinline__ void bulk_wait() { asm volatile("cp.async.bulk.wait_group %0;" :: "n"(N) : "memory"); }
__device__ __forceinline__ void fence_async_smem() { asm volatile("fence.proxy.async.shared::cta;" ::: "memory"); }
__device__ __forceinline__ void fence_async_global() { asm volatile("fence.proxy.async.global;" ::: "memory"); }
__device__ __forceinline__ bool elect_one() { uint32_t p; asm volatile("{\n.reg .pred P;\nelect.sync _|P, 0xffffffff;\nselp.u32 %0, 1, 0, P;\n}" : "=r"(p)); return p; }
__device__ __forceinline__ void prefetch_map(const CUtensorMap* m) { asm volatile("prefetch.tensormap [%0];" :: "l"(m) : "memory"); }
__device__ __forceinline__ void prefetch_l2(const void* p, uint32_t bytes) { asm volatile("cp.async.bulk.prefetch.L2.global [%0], %1;" :: "l"(p), "r"(bytes) : "memory"); }
__device__ __forceinline__ void wgmma_fence() { asm volatile("wgmma.fence.sync.aligned;" ::: "memory"); }
__device__ __forceinline__ void wgmma_commit() { asm volatile("wgmma.commit_group.sync.aligned;" ::: "memory"); }
template <int N> __device__ __forceinline__ void wgmma_wait() { asm volatile("wgmma.wait_group.sync.aligned %0;" :: "n"(N) : "memory"); }
__device__ __forceinline__ uint32_t desc_lo(uint32_t addr, uint32_t lbo) { return ((addr & 0x3FFFF) >> 4) | ((lbo >> 4) << 16); }
__device__ __forceinline__ uint64_t desc64(uint32_t lo) { uint64_t r; asm("mov.b64 %0, {%1, %2};" : "=l"(r) : "r"(lo), "r"(0x40000040u)); return r; }
__device__ __forceinline__ void bar_sync(int id, int n) { asm volatile("bar.sync %0, %1;" :: "r"(id), "r"(n) : "memory"); }
__device__ __forceinline__ uint32_t pack_bf16(float lo, float hi) { uint32_t r; asm("cvt.rn.bf16x2.f32 %0, %1, %2;" : "=r"(r) : "f"(hi), "f"(lo)); return r; }
__device__ __forceinline__ float bf_lo(uint32_t v) { return __uint_as_float(v << 16); }
__device__ __forceinline__ float bf_hi(uint32_t v) { return __uint_as_float(v & 0xffff0000u); }
__device__ __forceinline__ float ex2(float x) { float r; asm("ex2.approx.ftz.f32 %0, %1;" : "=f"(r) : "f"(x)); return r; }
__device__ __forceinline__ float rcp(float x) { float r; asm("rcp.approx.ftz.f32 %0, %1;" : "=f"(r) : "f"(x)); return r; }
__device__ __forceinline__ void stsm4(uint32_t a, uint32_t r0, uint32_t r1, uint32_t r2, uint32_t r3) {
  asm volatile("stmatrix.sync.aligned.m8n8.x4.shared.b16 [%0], {%1, %2, %3, %4};" :: "r"(a), "r"(r0), "r"(r1), "r"(r2), "r"(r3) : "memory");
}
__device__ __forceinline__ void ldsm4(uint32_t a, uint32_t& r0, uint32_t& r1, uint32_t& r2, uint32_t& r3) {
  asm volatile("ldmatrix.sync.aligned.m8n8.x4.shared.b16 {%0, %1, %2, %3}, [%4];" : "=r"(r0), "=r"(r1), "=r"(r2), "=r"(r3) : "r"(a) : "memory");
}
__device__ __forceinline__ uint32_t movm(uint32_t v) { uint32_t r; asm volatile("movmatrix.sync.aligned.m8n8.trans.b16 %0, %1;" : "=r"(r) : "r"(v)); return r; }
__device__ __forceinline__ void sts128(uint32_t a, uint32_t r0, uint32_t r1, uint32_t r2, uint32_t r3) {
  asm volatile("st.shared.v4.b32 [%0], {%1, %2, %3, %4};" :: "r"(a), "r"(r0), "r"(r1), "r"(r2), "r"(r3) : "memory");
}
__device__ __forceinline__ void lds128(uint32_t a, uint32_t& r0, uint32_t& r1, uint32_t& r2, uint32_t& r3) {
  asm volatile("ld.shared.v4.b32 {%0, %1, %2, %3}, [%4];" : "=r"(r0), "=r"(r1), "=r"(r2), "=r"(r3) : "r"(a) : "memory");
}
__device__ __forceinline__ uint32_t add_bf16x2(uint32_t a, uint32_t b) { uint32_t r; asm("add.rn.bf16x2 %0, %1, %2;" : "=r"(r) : "r"(a), "r"(b)); return r; }
__device__ __forceinline__ void sts32f(uint32_t a, float v) { asm volatile("st.shared.f32 [%0], %1;" :: "r"(a), "f"(v) : "memory"); }
__device__ __forceinline__ void mma16816(float (&d)[4], uint32_t a0, uint32_t a1, uint32_t a2, uint32_t a3, uint32_t b0, uint32_t b1, const float (&c)[4]) {
  asm("mma.sync.aligned.m16n8k16.row.col.f32.bf16.bf16.f32 {%0, %1, %2, %3}, {%4, %5, %6, %7}, {%8, %9}, {%10, %11, %12, %13};"
      : "=f"(d[0]), "=f"(d[1]), "=f"(d[2]), "=f"(d[3]) : "r"(a0), "r"(a1), "r"(a2), "r"(a3), "r"(b0), "r"(b1), "f"(c[0]), "f"(c[1]), "f"(c[2]), "f"(c[3]));
}
__device__ __forceinline__ void mma1688(float (&d)[4], uint32_t a0, uint32_t a1, uint32_t b0, const float (&c)[4]) {
  asm("mma.sync.aligned.m16n8k8.row.col.f32.bf16.bf16.f32 {%0, %1, %2, %3}, {%4, %5}, {%6}, {%7, %8, %9, %10};"
      : "=f"(d[0]), "=f"(d[1]), "=f"(d[2]), "=f"(d[3]) : "r"(a0), "r"(a1), "r"(b0), "f"(c[0]), "f"(c[1]), "f"(c[2]), "f"(c[3]));
}
__device__ __forceinline__ void mma16816z(float (&d)[4], uint32_t a0, uint32_t a1, uint32_t a2, uint32_t a3, uint32_t b0, uint32_t b1) {
  asm("mma.sync.aligned.m16n8k16.row.col.f32.bf16.bf16.f32 {%0, %1, %2, %3}, {%4, %5, %6, %7}, {%8, %9}, {0f00000000, 0f00000000, 0f00000000, 0f00000000};"
      : "=f"(d[0]), "=f"(d[1]), "=f"(d[2]), "=f"(d[3]) : "r"(a0), "r"(a1), "r"(a2), "r"(a3), "r"(b0), "r"(b1));
}
__device__ __forceinline__ void mma1688z(float (&d)[4], uint32_t a0, uint32_t a1, uint32_t b0) {
  asm("mma.sync.aligned.m16n8k8.row.col.f32.bf16.bf16.f32 {%0, %1, %2, %3}, {%4, %5}, {%6}, {0f00000000, 0f00000000, 0f00000000, 0f00000000};"
      : "=f"(d[0]), "=f"(d[1]), "=f"(d[2]), "=f"(d[3]) : "r"(a0), "r"(a1), "r"(b0));
}
__device__ __forceinline__ uint32_t bar_sync_zero(int id, int n) {
  uint32_t r;
  asm volatile("{\n.reg .pred p;\nsetp.eq.u32 p, %1, 0;\nbarrier.cta.red.popc.aligned.u32 %0, %1, %2, p;\n}" : "=r"(r) : "r"(id), "r"(n) : "memory");
  return r;
}
__device__ __forceinline__ uint32_t late_zero(uint32_t zm) { uint32_t c; asm volatile("mov.u32 %0, %%clock;" : "=r"(c) :: "memory"); return c & zm; }
__device__ __forceinline__ void st_b128(uint4* p, uint32_t a, uint32_t b, uint32_t c, uint32_t d) {
  asm volatile("{\n.reg .b128 t;\n.reg .b64 lo, hi;\nmov.b64 lo, {%0, %1};\nmov.b64 hi, {%2, %3};\nmov.b128 t, {lo, hi};\nst.relaxed.gpu.global.b128 [%4], t;\n}"
               :: "r"(a), "r"(b), "r"(c), "r"(d), "l"(p) : "memory");
}
__device__ __forceinline__ uint32_t pkt_head(uint32_t a) { return a ? a : 0x8000u; }
__device__ __forceinline__ void gen_store(uint4* p, uint32_t a, uint32_t b, uint32_t c, uint32_t d) {
  asm volatile("{\n.reg .b128 t;\n.reg .b64 lo, hi;\nmov.b64 lo, {%0, %1};\nmov.b64 hi, {%2, %3};\nmov.b128 t, {lo, hi};\nst.relaxed.gpu.b128 [%4], t;\n}"
               :: "r"(a), "r"(b), "r"(c), "r"(d), "l"(p) : "memory");
}
__device__ __forceinline__ void gen_load(const uint4* p, uint32_t* v) {
  asm volatile("{\n.reg .b128 t;\n.reg .b64 lo, hi;\nld.relaxed.gpu.b128 t, [%4];\nmov.b128 {lo, hi}, t;\nmov.b64 {%0, %1}, lo;\nmov.b64 {%2, %3}, hi;\n}"
               : "=r"(v[0]), "=r"(v[1]), "=r"(v[2]), "=r"(v[3]) : "l"(p) : "memory");
}
__device__ __forceinline__ void pkt_load(const uint4* p, uint32_t* v) {
  asm volatile("{\n.reg .b128 t;\n.reg .b64 lo, hi;\nld.relaxed.gpu.global.b128 t, [%4];\nmov.b128 {lo, hi}, t;\nmov.b64 {%0, %1}, lo;\nmov.b64 {%2, %3}, hi;\n}"
               : "=r"(v[0]), "=r"(v[1]), "=r"(v[2]), "=r"(v[3]) : "l"(p) : "memory");
}
__device__ __forceinline__ uint32_t ld_relaxed(const uint32_t* p) { uint32_t v; asm volatile("ld.relaxed.gpu.global.u32 %0, [%1];" : "=r"(v) : "l"(p) : "memory"); return v; }
__device__ __forceinline__ uint4 ld_relaxed4(const void* p) { uint4 v; asm volatile("ld.relaxed.gpu.global.v4.u32 {%0, %1, %2, %3}, [%4];" : "=r"(v.x), "=r"(v.y), "=r"(v.z), "=r"(v.w) : "l"(p) : "memory"); return v; }
__device__ __forceinline__ void st_relaxed(uint32_t* p, uint32_t v) { asm volatile("st.relaxed.gpu.global.u32 [%0], %1;" :: "l"(p), "r"(v) : "memory"); }
__device__ __forceinline__ void st_relaxed2(void* p, uint32_t a, uint32_t b) { asm volatile("st.relaxed.gpu.global.v2.u32 [%0], {%1, %2};" :: "l"(p), "r"(a), "r"(b) : "memory"); }
__device__ __forceinline__ void red_release(uint32_t* p, uint32_t v) { asm volatile("red.release.gpu.global.add.u32 [%0], %1;" :: "l"(p), "r"(v) : "memory"); }
__device__ __forceinline__ uint32_t tagf(float v, uint32_t tag) { return (__float_as_uint(v) & ~15u) | (tag & 15u); }
__device__ __forceinline__ bool tag_ok4(const uint4& v, uint32_t tag) { return (((v.x ^ tag) | (v.y ^ tag) | (v.z ^ tag) | (v.w ^ tag)) & 15u) == 0; }
__device__ __forceinline__ float untag(uint32_t v) { return __uint_as_float(v & ~15u); }
template <typename T> __device__ __forceinline__ T* ptr_add(T* p, uint32_t bytes) {
  uint64_t r;
  asm("{\n.reg .u32 lo, hi;\nmov.b64 {lo, hi}, %1;\nadd.cc.u32 lo, lo, %2;\naddc.u32 hi, hi, 0;\nmov.b64 %0, {lo, hi};\n}" : "=l"(r) : "l"(p), "r"(bytes));
  return (T*)r;
}
#define TL(who, slot) do {} while (0)
#define TLC(slot) do {} while (0)
#define TLE(slot) do {} while (0)
#define ST(who, n) do {} while (0)
#define AP(i) do {} while (0)
#define SP(v) do {} while (0)
#define TLG(slot) do {} while (0)
#define STA() do {} while (0)
#define STB(n) do {} while (0)

__device__ __forceinline__ void wgmma_n128(float (&d)[64], uint64_t da, uint64_t db, int scale_d) {
  asm volatile("{\n.reg .pred p;\nsetp.ne.b32 p, %66, 0;\n"
    "wgmma.mma_async.sync.aligned.m64n128k16.f32.bf16.bf16 "
    "{%0, %1, %2, %3, %4, %5, %6, %7, %8, %9, %10, %11, %12, %13, %14, %15, "
    "%16, %17, %18, %19, %20, %21, %22, %23, %24, %25, %26, %27, %28, %29, %30, %31, "
    "%32, %33, %34, %35, %36, %37, %38, %39, %40, %41, %42, %43, %44, %45, %46, %47, "
    "%48, %49, %50, %51, %52, %53, %54, %55, %56, %57, %58, %59, %60, %61, %62, %63}, "
    "%64, %65, p, 1, 1, 0, 1;\n}\n"
    : "+f"(d[0]), "+f"(d[1]), "+f"(d[2]), "+f"(d[3]), "+f"(d[4]), "+f"(d[5]), "+f"(d[6]), "+f"(d[7]),
      "+f"(d[8]), "+f"(d[9]), "+f"(d[10]), "+f"(d[11]), "+f"(d[12]), "+f"(d[13]), "+f"(d[14]), "+f"(d[15]),
      "+f"(d[16]), "+f"(d[17]), "+f"(d[18]), "+f"(d[19]), "+f"(d[20]), "+f"(d[21]), "+f"(d[22]), "+f"(d[23]),
      "+f"(d[24]), "+f"(d[25]), "+f"(d[26]), "+f"(d[27]), "+f"(d[28]), "+f"(d[29]), "+f"(d[30]), "+f"(d[31]),
      "+f"(d[32]), "+f"(d[33]), "+f"(d[34]), "+f"(d[35]), "+f"(d[36]), "+f"(d[37]), "+f"(d[38]), "+f"(d[39]),
      "+f"(d[40]), "+f"(d[41]), "+f"(d[42]), "+f"(d[43]), "+f"(d[44]), "+f"(d[45]), "+f"(d[46]), "+f"(d[47]),
      "+f"(d[48]), "+f"(d[49]), "+f"(d[50]), "+f"(d[51]), "+f"(d[52]), "+f"(d[53]), "+f"(d[54]), "+f"(d[55]),
      "+f"(d[56]), "+f"(d[57]), "+f"(d[58]), "+f"(d[59]), "+f"(d[60]), "+f"(d[61]), "+f"(d[62]), "+f"(d[63])
    : "l"(da), "l"(db), "r"(scale_d));
}
__device__ __forceinline__ void wgmma_n256(float (&d)[128], uint64_t da, uint64_t db, int scale_d) {
  asm volatile("{\n.reg .pred p;\nsetp.ne.b32 p, %130, 0;\n"
    "wgmma.mma_async.sync.aligned.m64n256k16.f32.bf16.bf16 "
    "{%0, %1, %2, %3, %4, %5, %6, %7, %8, %9, %10, %11, %12, %13, %14, %15, "
    "%16, %17, %18, %19, %20, %21, %22, %23, %24, %25, %26, %27, %28, %29, %30, %31, "
    "%32, %33, %34, %35, %36, %37, %38, %39, %40, %41, %42, %43, %44, %45, %46, %47, "
    "%48, %49, %50, %51, %52, %53, %54, %55, %56, %57, %58, %59, %60, %61, %62, %63, "
    "%64, %65, %66, %67, %68, %69, %70, %71, %72, %73, %74, %75, %76, %77, %78, %79, "
    "%80, %81, %82, %83, %84, %85, %86, %87, %88, %89, %90, %91, %92, %93, %94, %95, "
    "%96, %97, %98, %99, %100, %101, %102, %103, %104, %105, %106, %107, %108, %109, %110, %111, "
    "%112, %113, %114, %115, %116, %117, %118, %119, %120, %121, %122, %123, %124, %125, %126, %127}, "
    "%128, %129, p, 1, 1, 0, 1;\n}\n"
    : "+f"(d[0]), "+f"(d[1]), "+f"(d[2]), "+f"(d[3]), "+f"(d[4]), "+f"(d[5]), "+f"(d[6]), "+f"(d[7]),
      "+f"(d[8]), "+f"(d[9]), "+f"(d[10]), "+f"(d[11]), "+f"(d[12]), "+f"(d[13]), "+f"(d[14]), "+f"(d[15]),
      "+f"(d[16]), "+f"(d[17]), "+f"(d[18]), "+f"(d[19]), "+f"(d[20]), "+f"(d[21]), "+f"(d[22]), "+f"(d[23]),
      "+f"(d[24]), "+f"(d[25]), "+f"(d[26]), "+f"(d[27]), "+f"(d[28]), "+f"(d[29]), "+f"(d[30]), "+f"(d[31]),
      "+f"(d[32]), "+f"(d[33]), "+f"(d[34]), "+f"(d[35]), "+f"(d[36]), "+f"(d[37]), "+f"(d[38]), "+f"(d[39]),
      "+f"(d[40]), "+f"(d[41]), "+f"(d[42]), "+f"(d[43]), "+f"(d[44]), "+f"(d[45]), "+f"(d[46]), "+f"(d[47]),
      "+f"(d[48]), "+f"(d[49]), "+f"(d[50]), "+f"(d[51]), "+f"(d[52]), "+f"(d[53]), "+f"(d[54]), "+f"(d[55]),
      "+f"(d[56]), "+f"(d[57]), "+f"(d[58]), "+f"(d[59]), "+f"(d[60]), "+f"(d[61]), "+f"(d[62]), "+f"(d[63]),
      "+f"(d[64]), "+f"(d[65]), "+f"(d[66]), "+f"(d[67]), "+f"(d[68]), "+f"(d[69]), "+f"(d[70]), "+f"(d[71]),
      "+f"(d[72]), "+f"(d[73]), "+f"(d[74]), "+f"(d[75]), "+f"(d[76]), "+f"(d[77]), "+f"(d[78]), "+f"(d[79]),
      "+f"(d[80]), "+f"(d[81]), "+f"(d[82]), "+f"(d[83]), "+f"(d[84]), "+f"(d[85]), "+f"(d[86]), "+f"(d[87]),
      "+f"(d[88]), "+f"(d[89]), "+f"(d[90]), "+f"(d[91]), "+f"(d[92]), "+f"(d[93]), "+f"(d[94]), "+f"(d[95]),
      "+f"(d[96]), "+f"(d[97]), "+f"(d[98]), "+f"(d[99]), "+f"(d[100]), "+f"(d[101]), "+f"(d[102]), "+f"(d[103]),
      "+f"(d[104]), "+f"(d[105]), "+f"(d[106]), "+f"(d[107]), "+f"(d[108]), "+f"(d[109]), "+f"(d[110]), "+f"(d[111]),
      "+f"(d[112]), "+f"(d[113]), "+f"(d[114]), "+f"(d[115]), "+f"(d[116]), "+f"(d[117]), "+f"(d[118]), "+f"(d[119]),
      "+f"(d[120]), "+f"(d[121]), "+f"(d[122]), "+f"(d[123]), "+f"(d[124]), "+f"(d[125]), "+f"(d[126]), "+f"(d[127])
    : "l"(da), "l"(db), "r"(scale_d));
}
__device__ __forceinline__ void wgmma_rs_n128(float (&d)[64], const uint32_t* a, uint64_t db, int scale_d) {
  asm volatile("{\n.reg .pred p;\nsetp.ne.b32 p, %69, 0;\n"
    "wgmma.mma_async.sync.aligned.m64n128k16.f32.bf16.bf16 "
    "{%0, %1, %2, %3, %4, %5, %6, %7, %8, %9, %10, %11, %12, %13, %14, %15, "
    "%16, %17, %18, %19, %20, %21, %22, %23, %24, %25, %26, %27, %28, %29, %30, %31, "
    "%32, %33, %34, %35, %36, %37, %38, %39, %40, %41, %42, %43, %44, %45, %46, %47, "
    "%48, %49, %50, %51, %52, %53, %54, %55, %56, %57, %58, %59, %60, %61, %62, %63}, "
    "{%64, %65, %66, %67}, %68, p, 1, 1, 1;\n}\n"
    : "+f"(d[0]), "+f"(d[1]), "+f"(d[2]), "+f"(d[3]), "+f"(d[4]), "+f"(d[5]), "+f"(d[6]), "+f"(d[7]),
      "+f"(d[8]), "+f"(d[9]), "+f"(d[10]), "+f"(d[11]), "+f"(d[12]), "+f"(d[13]), "+f"(d[14]), "+f"(d[15]),
      "+f"(d[16]), "+f"(d[17]), "+f"(d[18]), "+f"(d[19]), "+f"(d[20]), "+f"(d[21]), "+f"(d[22]), "+f"(d[23]),
      "+f"(d[24]), "+f"(d[25]), "+f"(d[26]), "+f"(d[27]), "+f"(d[28]), "+f"(d[29]), "+f"(d[30]), "+f"(d[31]),
      "+f"(d[32]), "+f"(d[33]), "+f"(d[34]), "+f"(d[35]), "+f"(d[36]), "+f"(d[37]), "+f"(d[38]), "+f"(d[39]),
      "+f"(d[40]), "+f"(d[41]), "+f"(d[42]), "+f"(d[43]), "+f"(d[44]), "+f"(d[45]), "+f"(d[46]), "+f"(d[47]),
      "+f"(d[48]), "+f"(d[49]), "+f"(d[50]), "+f"(d[51]), "+f"(d[52]), "+f"(d[53]), "+f"(d[54]), "+f"(d[55]),
      "+f"(d[56]), "+f"(d[57]), "+f"(d[58]), "+f"(d[59]), "+f"(d[60]), "+f"(d[61]), "+f"(d[62]), "+f"(d[63])
    : "r"(a[0]), "r"(a[1]), "r"(a[2]), "r"(a[3]), "l"(db), "r"(scale_d));
}
__device__ __forceinline__ void wgmma_n64(float* d, uint64_t da, uint64_t db, int scale_d) {
  asm volatile("{\n.reg .pred p;\nsetp.ne.b32 p, %34, 0;\n"
    "wgmma.mma_async.sync.aligned.m64n64k16.f32.bf16.bf16 "
    "{%0, %1, %2, %3, %4, %5, %6, %7, %8, %9, %10, %11, %12, %13, %14, %15, "
    "%16, %17, %18, %19, %20, %21, %22, %23, %24, %25, %26, %27, %28, %29, %30, %31}, "
    "%32, %33, p, 1, 1, 0, 1;\n}\n"
    : "+f"(d[0]), "+f"(d[1]), "+f"(d[2]), "+f"(d[3]), "+f"(d[4]), "+f"(d[5]), "+f"(d[6]), "+f"(d[7]),
      "+f"(d[8]), "+f"(d[9]), "+f"(d[10]), "+f"(d[11]), "+f"(d[12]), "+f"(d[13]), "+f"(d[14]), "+f"(d[15]),
      "+f"(d[16]), "+f"(d[17]), "+f"(d[18]), "+f"(d[19]), "+f"(d[20]), "+f"(d[21]), "+f"(d[22]), "+f"(d[23]),
      "+f"(d[24]), "+f"(d[25]), "+f"(d[26]), "+f"(d[27]), "+f"(d[28]), "+f"(d[29]), "+f"(d[30]), "+f"(d[31])
    : "l"(da), "l"(db), "r"(scale_d));
}
__device__ __forceinline__ void wgmma_rs_n64(float* d, const uint32_t* a, uint64_t db, int scale_d) {
  asm volatile("{\n.reg .pred p;\nsetp.ne.b32 p, %37, 0;\n"
    "wgmma.mma_async.sync.aligned.m64n64k16.f32.bf16.bf16 "
    "{%0, %1, %2, %3, %4, %5, %6, %7, %8, %9, %10, %11, %12, %13, %14, %15, "
    "%16, %17, %18, %19, %20, %21, %22, %23, %24, %25, %26, %27, %28, %29, %30, %31}, "
    "{%32, %33, %34, %35}, %36, p, 1, 1, 1;\n}\n"
    : "+f"(d[0]), "+f"(d[1]), "+f"(d[2]), "+f"(d[3]), "+f"(d[4]), "+f"(d[5]), "+f"(d[6]), "+f"(d[7]),
      "+f"(d[8]), "+f"(d[9]), "+f"(d[10]), "+f"(d[11]), "+f"(d[12]), "+f"(d[13]), "+f"(d[14]), "+f"(d[15]),
      "+f"(d[16]), "+f"(d[17]), "+f"(d[18]), "+f"(d[19]), "+f"(d[20]), "+f"(d[21]), "+f"(d[22]), "+f"(d[23]),
      "+f"(d[24]), "+f"(d[25]), "+f"(d[26]), "+f"(d[27]), "+f"(d[28]), "+f"(d[29]), "+f"(d[30]), "+f"(d[31])
    : "r"(a[0]), "r"(a[1]), "r"(a[2]), "r"(a[3]), "l"(db), "r"(scale_d));
}

template <int BN> __device__ __forceinline__ void wgmma(float (&d)[BN / 2], uint64_t a, uint64_t b, int s) {
  if constexpr (BN == 128) wgmma_n128(d, a, b, s);
  else wgmma_n256(d, a, b, s);
}

template <int N> __device__ __forceinline__ void acc_fence(float* a) {
#pragma unroll
  for (int i = 0; i < N; i++) asm volatile("" : "+f"(a[i]) :: "memory");
}

#define SELECT8(a, f) do { \
  if ((a) & 4) { if ((a) & 2) { if ((a) & 1) f(7); else f(6); } else { if ((a) & 1) f(5); else f(4); } } \
  else { if ((a) & 2) { if ((a) & 1) f(3); else f(2); } else { if ((a) & 1) f(1); else f(0); } } } while (0)
__device__ __forceinline__ uint32_t lane_now() { uint32_t l; asm volatile("mov.u32 %0, %%laneid;" : "=r"(l)); return l; }

struct Prod {
  uint32_t sb, n, tail, addr, pat, ready;
  uint32_t rank, flip; uint16_t mask;
  __device__ __forceinline__ void load_b(uint32_t dst, uint32_t half, const CUtensorMap* m, uint32_t mstep, uint32_t fb, int k, int ch, int cstep) {
    uint32_t h = rank;
    do { tma_ld3_mc(dst + h * half, ptr_add(m, h * mstep), fb, 0, k * 64, ch + h * cstep, mask); h ^= flip; } while (h != rank);
  }
  __device__ __forceinline__ void load_wide(const Params& P, int ffn, uint32_t dst, uint32_t fb, int k, int ch) {
    load_b(dst, PAGE, &P.map[ffn ? M_W1 : M_WKV], ffn ? 128 : 0, fb, k, ffn ? ch : ch + 16, ffn ? 0 : 16);
  }
  __device__ __forceinline__ void load_narrow(const Params& P, int ffn, uint32_t dst, uint32_t fb, int k, int j) {
    load_b(dst, 8192, &P.map[ffn ? M_W1H : M_WQ], ffn ? 128 : 0, fb, k, ffn ? 48 + j : 2 * j, ffn ? 0 : 1);
  }
  __device__ __forceinline__ void finish() {
#pragma unroll 1
    for (; tail < n; tail++) mbar_wait(sb + BAR_EMPTY + ((tail & 7) << 3), (tail >> 3) & 1);
  }
  template <int PAGES> __device__ __forceinline__ uint32_t acquire(uint32_t& fb) { return acquire_n(PAGES, fb); }
  __device__ __forceinline__ uint32_t acquire_n(uint32_t PAGES, uint32_t& fb) {
    uint32_t nw = pat & 3; pat = (pat >> 2) | 0x40000000u;
#pragma unroll 1
    for (; nw; nw--) { mbar_wait(sb + BAR_EMPTY + ((tail & 7) << 3), (tail >> 3) & 1); tail++; }
    ST(4, n);
    fb = sb + BAR_FULL + ((n & 7) << 3);
    mbar_expect_tx(fb, PAGES * PAGE);
    const uint32_t a = sb + addr;
    addr += PAGES * PAGE; if (addr >= NPAGE * PAGE) addr = 0;
    n++;
    return a;
  }
  const uint32_t* flag; uint32_t base, seen;
  __device__ __forceinline__ void acquire_fence() { asm volatile("fence.acquire.gpu;" ::: "memory"); fence_async_global(); }
  __device__ __forceinline__ void next() {
    uint32_t v, spins = 0;
    seen++;
    do { asm volatile("ld.acquire.cta.shared.u32 %0, [%1];" : "=r"(v) : "r"(sb + SM_SEEN) : "memory"); spin_check(++spins >> 4); } while (v < seen);
    fence_async_global();
  }
  __device__ __forceinline__ void need(uint32_t mask) {
    if ((ready & mask) != mask) {
      uint32_t spins = 0;
      do { ready = ld_relaxed(flag) - base; spin_check(++spins); } while ((ready & mask) != mask);
      acquire_fence();
    }
    ST(5, n - 1);
  }
};

struct Cons {
  uint32_t sb, n, off, prev;
  uint32_t ebar;
  uint32_t da0, db0;
  int lane;
  template <int PAGES> __device__ __forceinline__ void advance() {
    n++; off += PAGES << 10; if (off >= (NPAGE << 10)) off = 0;
    asm volatile("" : "+r"(n), "+r"(off));
  }
  template <int BN, int PAGES> __device__ __forceinline__ void step_ab(float (&acc)[BN / 2], uint32_t da, uint32_t db, int accumulate) {
    STA();
    mbar_wait_fast(sb + BAR_FULL + ((n & 7) << 3), (n >> 3) & 1);
    STB(n);
    const uint64_t da64 = desc64(da), db64 = desc64(db);
    wgmma_fence();
#pragma unroll
    for (int k = 0; k < 4; k++) wgmma<BN>(acc, da64 + 2 * k, db64 + 128 * k, k ? 1 : accumulate);
    wgmma_commit();
    wgmma_wait<1>();
    if (prev && lane < 2) mbar_arrive_cluster(ebar + prev);
    prev = 64 + ((n & 7) << 3);
    advance<PAGES>();
  }
  template <int BN> __device__ __forceinline__ void step(float (&acc)[BN / 2], int accumulate = 1) { step_ab<BN, BN / 128 + 1>(acc, da0 + off, db0 + 1024 + off, accumulate); }
  template <int BN> __device__ __forceinline__ void step_own(float (&acc)[BN / 2], uint32_t da, int accumulate) { step_ab<BN, BN / 128>(acc, da, db0 + off, accumulate); }
  __device__ __forceinline__ void wait_full(uint32_t i) { mbar_wait_fast(sb + BAR_FULL + (((n + i) & 7) << 3), ((n + i) >> 3) & 1); }
  template <int I, int N> __device__ __forceinline__ void issue_rs(float (&acc)[64], uint32_t (&a)[16], int accumulate = 1) {
    if (I == 0) { STA(); STB(n); }
    const uint64_t db64 = desc64(db0 + off) + 1024 * I;
    wgmma_fence();
#pragma unroll
    for (int k = 0; k < 4; k++) wgmma_rs_n128(acc, a + 4 * k, db64 + 128 * k, k ? 1 : accumulate);
    if (I == N - 1) {
      wgmma_commit();
      prev = 64 + ((n & 7) << 3);
      advance<N>();
    }
  }
  template <int BN> __device__ __forceinline__ void steps(float (&acc)[BN / 2], int cnt) {
#pragma unroll 1
    do { step<BN>(acc); } while (--cnt > 0);
  }
  __device__ __forceinline__ void steps_skip(float (&acc)[64], int at) {
    int i = 0;
#pragma unroll 1
    do { if (i == at) off += 2 << 10; step<128>(acc); } while (++i < 2);
  }
  __device__ __forceinline__ void drain() {
    wgmma_wait<0>();
    if (lane < 2) mbar_arrive_cluster(ebar + prev);
    prev = 0;
  }
};

#define MAPPING 2
__device__ __forceinline__ uint32_t role_of_sm(uint32_t smid) {
  const uint32_t t = smid >> 1;
  uint32_t q, i;
  if (t < 32) { q = t & 7; i = t >> 3; }
  else if (t < 60) { const uint32_t u = t - 32, d = (u * 37) >> 8; q = 1 + u - d * 7; i = 4 + d; }
  else if (t < 62) return 128 + smid - 120;
  else { q = 0; i = t - 58; }
  return (q * 2 + (smid & 1)) * 8 + i;
}

template <typename T> __device__ __forceinline__ T* scratch(const Params& P, uint32_t off) { return (T*)ptr_add(P.scratch, off); }
__device__ __forceinline__ uint32_t* epoch_ptr(const Params& P) { uint32_t b; asm volatile("mov.u32 %0, %%ctaid.x;" : "=r"(b)); return scratch<uint32_t>(P, G_EPOCH + b * 4u); }

__device__ __forceinline__ int o_chunk(int s, int j) { const int hf = s >= 9, m = s - 2 - 7 * hf; return s < 2 ? 2 * j + s : 2 * (m == j ? 7 : m) + hf; }

__global__ void __cluster_dims__(2, 1, 1) __launch_bounds__(384, 1) fused_kernel(const __grid_constant__ Params P) {
  extern __shared__ __align__(1024) uint8_t smem_raw[];
  SP(0);
  const uint32_t sb = __shfl_sync(0xffffffffu, smem_u32(smem_raw), 0);
  const int warp = __shfl_sync(0xffffffffu, threadIdx.x >> 5, 0);
  const int lane = threadIdx.x & 31;
  if (warp == 7 && elect_one()) { prefetch_map(&P.map[M_XIN64]); prefetch_map(&P.map[M_WKV]); prefetch_map(&P.map[M_XIN]); }
  uint32_t role = blockIdx.x < 128 ? ((blockIdx.x >> 4) * 2 + (blockIdx.x & 1)) * 8 + ((blockIdx.x >> 1) & 7) : blockIdx.x;
  if (P.use_smid) { uint32_t smid; asm volatile("mov.u32 %0, %%smid;" : "=r"(smid)); role = role_of_sm(smid); }
  const bool spare = role >= 128;
  const int g = role >> 3, j = role & 7;
  uint32_t rank; asm("mov.u32 %0, %%cluster_ctarank;" : "=r"(rank));
  auto shared_b = [&]() {
    uint32_t peer;
    asm volatile("ld.shared::cluster.u32 %0, [%1];" : "=r"(peer) : "r"(mapa(sb + SM_ROLE, rank ^ 1)) : "memory");
    return !spare && peer < 128 && (peer & 7) == (uint32_t)j;
  };
  SP(1);

  if (warp >= 8) {
    asm volatile("setmaxnreg.dec.sync.aligned.u32 40;");
    if (elect_one()) {
      if (warp == 8) {
#pragma unroll
        for (int i = 0; i < 6; i++) mbar_init(sb + BAR_FULL + 8 * i, 1);
        mbar_init(sb + BAR_XIN, 1);
      } else if (warp == 9) {
#pragma unroll
        for (int i = 0; i < 8; i++) mbar_init(sb + BAR_EMPTY + 8 * i, 16);
      } else if (warp == 10) {
#pragma unroll
        for (int i = 0; i < 4; i++) mbar_init(sb + BAR_SFULL + 8 * i, 4);
        mbar_init(sb + BAR_CLR, 1); mbar_init(sb + BAR_FULL + 48, 1); mbar_init(sb + BAR_FULL + 56, 1);
      } else {
        sts128(sb + SM_ROLE, role, 0, 0, 0);
        mbar_init(sb + BAR_TAG, 1); mbar_init(sb + BAR_XFULL, 8); mbar_init(sb + BAR_CSE, 8);
        mbar_init(sb + BAR_SEMPTY, 1); mbar_init(sb + BAR_CSF, 1); mbar_init(sb + BAR_CSF + 8, 2);
      }
      asm volatile("fence.mbarrier_init.release.cluster;\nfence.release.sync_restrict::shared::cta.cluster;" ::: "memory");
      fence_async_smem();
    }
    __syncwarp();
    SP(2);
    asm volatile("barrier.cluster.arrive.relaxed.aligned;" ::: "memory");
    if (warp == 8 && !spare) {
      if (elect_one()) {
        const int par = g & 1, row = (g >> 1) * 128;
        mbar_arrive(sb + BAR_FULL);
        {
          const int s = 1;
          const uint32_t xb = sb + BAR_XIN, fb = sb + BAR_FULL + 8;
          mbar_expect_tx(xb, PAGE); mbar_expect_tx(fb, 2 * PAGE);
#pragma unroll
          for (int h = 0; h < 2; h++) tma_ld3(sb + SM_STAGE + h * PAGE + s * 8192, &P.map[M_XIN64], xb, s * 64, par, row + h * 64);
#pragma unroll
          for (int h = 0; h < 2; h++) tma_ld3(sb + (2 * s + h) * PAGE, &P.map[M_WKV], fb, 0, s * 64, 16 + 16 * h + 2 * j);
        }
#pragma unroll 1
        for (int s = 0; s < 2; s++) {
          const uint32_t fb = sb + BAR_FULL + 16 + 8 * s;
          mbar_expect_tx(fb, PAGE);
          tma_ld3(sb + (4 + s) * PAGE, &P.map[M_WKV], fb, 0, s * 64, 2 * j);
        }
#pragma unroll 1
        for (int s = 0; s < 2; s++) {
          const uint32_t fb = sb + BAR_FULL + 32 + 8 * s, a = sb + (6 + 3 * s) * PAGE;
          const int k = (j == 1 ? 4 : 2) + s;
          mbar_expect_tx(fb, 3 * PAGE);
          tma_ld3(a, &P.map[M_XIN], fb, k * 64, par, row);
#pragma unroll
          for (int h = 0; h < 2; h++) tma_ld3(a + PAGE + h * PAGE, &P.map[M_WKV], fb, 0, k * 64, 16 + 16 * h + 2 * j);
        }
        spin_check((sb & 1023) << 22);
      }
      __syncwarp();
    }
    SP(3);
    asm volatile("barrier.cluster.wait.acquire.aligned;" ::: "memory");
    SP(4);
    if (warp == 8) {
      if (elect_one()) {
        Prod p; p.sb = sb; p.n = 0; p.tail = 0; p.ready = 0; p.addr = 0;
        { const bool mc = shared_b(); p.rank = rank; p.flip = !mc; p.mask = mc ? 3 : 1 << rank; }
        uint32_t fb;
        if (spare) {
          p.pat = 0x55555000u;
#pragma unroll 1
          for (int r = -1; r < 7; r++) {
            const int ch = r < 0 ? 4 * j : ((r < 2 ? r : r == 2 ? 6 : r - 1) * 4 + j) * 2;
#pragma unroll 1
            for (int k = 0; k < 16; k++) { const uint32_t a = p.acquire<2>(fb); p.load_b(a, PAGE, &P.map[r < 0 ? M_WKV : M_W1], r < 0 ? 0 : 128, fb, k, ch, r < 0 ? 2 : 0); }
          }
        } else {
          p.seen = 0;
          const int xpar = g & 1, xrow = (g >> 1) * 128;
          SP(5);
#pragma unroll 1
          for (int hl = 0; hl < 4; hl++) {
            const int ffn = hl & 1;
            const CUtensorMap* xmap = &P.map[hl ? M_OUT_LD : M_XIN];
            if (hl) {
              p.pat = ffn ? Pat<3>::v : Pat<8>::v;
#pragma unroll 1
              for (int s = 0; s < 2; s++) { const uint32_t a = p.acquire<2>(fb); p.load_wide(P, ffn, a, fb, 2 * j + s, 2 * j); }
#pragma unroll 1
              for (int s = 0; s < 2; s++) { const uint32_t a = p.acquire<1>(fb); p.load_narrow(P, ffn, a, fb, 2 * j + s, j); }
            } else { p.pat = (Pat<0>::v >> 12) | 0x55500000u; p.addr = 0; p.n = 6; }
            if (hl == 0) SP(6);
            uint32_t fb0 = 0;
#pragma unroll 1
            for (int m = hl ? 0 : 2; m < 14; m++) {
              const int hf = m >= 7, mm = m - 7 * hf, jj = mm == j ? 7 : mm;
              int k = 2 * jj + hf;
              if (hl == 0) {
                const int pr = (m >> 1) + 1;
                k = 2 * (j && pr == 2 ? j : pr == j ? 2 : pr) + (m & 1);
              }
              const uint32_t a = p.acquire<3>(fb);
              p.load_wide(P, ffn, a + PAGE, fb, k, 2 * j);
              if (hl) {
                if (m == 0) { fb0 = fb; continue; }
                if (m == 1) {
                  const int j0 = j ? 0 : 7;
                  p.flag = scratch<uint32_t>(P, g * G_BLOCK + G_FLAGS + (ffn ? (hl >> 1) * EV_N + EV_XA : EV_XB) * 128);
                  p.ready = 0; p.need(1u << j0);
                  tma_ld3(a - 3 * PAGE, xmap, fb0, j0 * 128, xpar, xrow);
                }
                if (m < 7) p.need(1u << jj); else if (m == 7) p.next();
              }
              tma_ld3(a, xmap, fb, k * 64, xpar, xrow);
            }
            if (hl == 0) { mbar_wait(sb + BAR_TAG, 0); asm volatile("ld.shared.u32 %0, [%1];" : "=r"(p.base) : "r"(sb + SM_TAG) : "memory"); p.base = (p.base - 1) * 255; }
            p.pat = ffn ? Pat<4>::v : Pat<1>::v;
#pragma unroll 1
            for (int m = 0; m < 14; m++) {
              const int k = (m >> 1) == (hl ? j : 0) ? 14 + (m & 1) : m;
              if (ffn && m == 8) p.addr += 2 * PAGE;
              const uint32_t a = p.acquire<2>(fb);
              p.load_narrow(P, ffn, a + PAGE, fb, k, j);
              tma_ld3(a, xmap, fb, k * 64, xpar, xrow);
            }
            if (!ffn) {
              p.pat = Pat<2>::v;
              uint32_t a = 0;
#pragma unroll 1
              for (int s = 0; s < 16; s++) {
                if ((0x4925 >> s) & 1) a = p.acquire_n(s == 0 || s == 14 ? 2 : 3, fb); else a += PAGE;
                p.load_b(a, 8192, &P.map[M_WO], 0, fb, o_chunk(s, j), 2 * j, 1);
              }
              p.addr += 2 * PAGE;
              a = p.acquire<2>(fb);
              tma_ld3(a, xmap, fb, j * 128, xpar, xrow); tma_ld3(a + PAGE, xmap, fb, j * 128 + 64, xpar, xrow);
            } else {
              p.pat = Pat<5>::v;
#pragma unroll 1
              for (int s = 16; s < 48; s++) {
                const int pi = (s >> 1) & 7;
                const int k = (s < 32 ? pi : pi == 4 ? j : pi == j ? 4 : pi) * 2 + (s & 1);
                const uint32_t a = p.acquire<3>(fb);
                p.load_wide(P, 1, a + PAGE, fb, k, (s & 48) + 2 * j);
                tma_ld3(a, xmap, fb, k * 64, xpar, xrow);
              }
              p.pat = Pat<6>::v;
#pragma unroll 1
              for (int q = 0; q < 4; q++) {
                p.next();
                const int k0 = q == 0 ? 0 : q == 1 ? 48 : q * 16 - 16, k1 = k0 + (q == 1 ? 8 : 16);
#pragma unroll 1
                for (int k = k0; k < k1; k++) {
                  if (k == 24) { p.addr = 0; p.pat = Pat<7>::v; }
                  const uint32_t a = p.acquire<2>(fb);
                  p.load_b(a + PAGE, 8192, &P.map[M_W2], 0, fb, k, 2 * j, 1);
                  tma_ld3(a, &P.map[M_H_LD], fb, k * 64, g, 0);
                }
              }
            }
            TL(2, 1 + hl);
          }
        }
        p.finish();
      }
    } else if (!spare) {
      mbar_wait(sb + BAR_XIN, 0);
      if (elect_one()) {
#pragma unroll 1
        for (int i = warp - 9; i < 8; i += 3) prefetch_l2(ptr_add(P.wqkv, (i * 128 + role) * 6144u + 2048u), 4096);
      }
      uint32_t tag;
      {
        const uint32_t part = warp - 9, col = DM + role * 16 + (lane & 1) * 8;
        const int cnt = part ? 21 : 22;
        const uint4* wp = ptr_add((const uint4*)P.wqkv, ((part ? 16 + part * 336 : 0) + (lane >> 1)) * 6144u + col * 2);
        float s[8] = {0, 0, 0, 0, 0, 0, 0, 0};
        uint4 v[4];
#pragma unroll
        for (int i = 0; i < 4; i++) v[i] = ld_relaxed4(wp + i * (16 * 6144 / 16));
        tag = ld_relaxed(epoch_ptr(P)) + 1;
        if (warp == 10 && lane == 0) { asm volatile("st.shared.u32 [%0], %1;" :: "r"(sb + SM_TAG), "r"(tag) : "memory"); mbar_arrive(sb + BAR_TAG); }
#pragma unroll 1
        for (int b = 4; b < 28; b += 4) {
          wp += 64 * 6144 / 16;
#pragma unroll
          for (int i = 0; i < 4; i++) {
            s[0] += bf_lo(v[i].x); s[1] += bf_hi(v[i].x); s[2] += bf_lo(v[i].y); s[3] += bf_hi(v[i].y);
            s[4] += bf_lo(v[i].z); s[5] += bf_hi(v[i].z); s[6] += bf_lo(v[i].w); s[7] += bf_hi(v[i].w);
            v[i] = make_uint4(0, 0, 0, 0);
            if (b + i < cnt) v[i] = __ldcg(wp + i * (16 * 6144 / 16));
          }
        }
#pragma unroll
        for (int e = 0; e < 4; e++) { const bool h = lane & 16; const float t = __shfl_xor_sync(0xffffffffu, h ? s[e] : s[e + 4], 16); s[e] = (h ? s[e + 4] : s[e]) + t; }
#pragma unroll
        for (int e = 0; e < 2; e++) { const bool h = lane & 8; const float t = __shfl_xor_sync(0xffffffffu, h ? s[e] : s[e + 2], 8); s[e] = (h ? s[e + 2] : s[e]) + t; }
        { const bool h = lane & 4; const float t = __shfl_xor_sync(0xffffffffu, h ? s[0] : s[1], 4); s[0] = (h ? s[1] : s[0]) + t; }
        s[0] += __shfl_xor_sync(0xffffffffu, s[0], 2);
        if (!(lane & 2) || part == 0) st_relaxed(scratch<uint32_t>(P, G_CS + (col + (lane >> 2)) * 16 + ((lane & 2) ? 3 : part) * 4), tagf((lane & 2) ? 0.f : s[0], tag));
        __syncwarp();
      }
      if (warp == 11 && lane == 0) TL(2, 30);
      {
        const uint32_t cspos = sb + SM_CS + ((lane & 16) + ((lane >> 1) & 3) * 4 + ((lane >> 3) & 1) * 2 + (lane & 1)) * 4;
#pragma unroll 1
        for (int it = 0; it < (warp == 10 ? 8 : 1); it++) {
          const int t = it & 3;
          if (it) mbar_wait(sb + BAR_CSE, (it - 1) & 1);
          if (t == 1) mbar_wait(sb + BAR_SEMPTY, 0);
#pragma unroll 1
          for (int b = it ? 0 : warp - 9; b < (it == 0 ? warp - 8 : t < 2 ? 3 : 2); b++) {
            uint32_t c0, c1;
            if (b < 2) { c0 = (t ? 2048 + t * 1024 + b * FF : 1024 + b * 1024) + j * 128; c1 = c0 + 64; }
            else if (t) { c0 = 6144 + j * 64; c1 = c0 + FF; }
            else { c0 = j * 128; c1 = c0 + 64; }
            const uint4* p0 = scratch<uint4>(P, G_CS + (c0 + lane) * 16u);
            const uint4* p1 = scratch<uint4>(P, G_CS + (c1 + lane) * 16u);
            uint4 v[4]; uint32_t spins = 0; bool ok;
            do {
              if (spins) __nanosleep(200);
              v[0] = ld_relaxed4(p0); v[1] = ld_relaxed4(p0 + 32); v[2] = ld_relaxed4(p1); v[3] = ld_relaxed4(p1 + 32);
              ok = tag_ok4(v[0], tag) && tag_ok4(v[1], tag) && tag_ok4(v[2], tag) && tag_ok4(v[3], tag);
              spin_check(++spins);
            } while (__any_sync(0xffffffffu, !ok));
#pragma unroll
            for (int m = 0; m < 4; m++) sts32f(cspos + b * 512 + m * 128, (untag(v[m].x) + untag(v[m].y)) + (untag(v[m].z) + untag(v[m].w)));
            __syncwarp();
            if (lane == 0) mbar_arrive(sb + BAR_CSF + (b ? 8 : 0));
          }
          if (lane == 0) { if (t >= 2) mbar_arrive(sb + BAR_CSF + 8); TL(2, 16 + it + (warp == 11 ? 8 : warp == 9 ? 9 : 0)); }
          if (t == 3) {
            if (g >= 2) {
              uint4* op = scratch<uint4>(P, G_HALO + (((it >> 2) * 16 + g - 2) * 8 + j) * 4096u + lane * 16u);
#pragma unroll 1
              for (int i = 0; i < 8; i++) { st_b128(op, 0, 0, 0, 0); op += 32; }
            }
          }
        }
      }
      if (warp == 11) {
        if (elect_one()) prefetch_l2(ptr_add(P.wo, role * 16384u), 16384);
        uint32_t* const fl = scratch<uint32_t>(P, g * G_BLOCK + G_FLAGS);
        uint32_t seen = 0;
#pragma unroll 1
        for (int e = EV_XA; e < EV_N + EV_XB; e++) {
          if (e == EV_XB) continue;
          const bool clr = (e & 7) == EV_XA;
          uint32_t* const f = ptr_add(fl, (clr ? 16 + e : e) * 128u);
          if (clr) {
            uint4* op = scratch<uint4>(P, g * G_BLOCK + G_O + j * 32768u + lane * 16u);
#pragma unroll 1
            for (int i = 0; i < 64; i++) { st_b128(op, 0, 0, 0, 0); op += 32; if (e || (i & 1)) __nanosleep(10); }
            __syncwarp();
            if (lane == 0) red_release(f, 1u << j);
          }
          uint32_t spins = 0, m;
          while ((m = ld_relaxed(f) - (tag - 1) * 255) != 255) { __nanosleep(m ? 50 : 500); spin_check(++spins); }
          asm volatile("fence.acquire.gpu;" ::: "memory");
          if (lane == 0) {
            if (clr) mbar_arrive(sb + BAR_CLR);
            else asm volatile("st.release.cta.shared.u32 [%0], %1;" :: "r"(sb + SM_SEEN), "r"(++seen) : "memory");
          }
          if (e == EV_H3) {
#pragma unroll 1
            for (int i = 0; i < 7; i++) { if (elect_one()) prefetch_l2(ptr_add(P.w2, (i * 128 + role) * 8192u), 8192); __nanosleep(500); }
          }
          __syncwarp();
        }
      } else if (warp == 9) {
        if (elect_one()) {
          prefetch_map(&P.map[M_WQ]); prefetch_map(&P.map[M_OUT_LD]); prefetch_map(&P.map[M_WO]); prefetch_map(&P.map[M_W1 + rank]);
          prefetch_map(&P.map[M_H_ST]); prefetch_map(&P.map[M_H_LD]); prefetch_map(&P.map[M_W1H + rank]); prefetch_map(&P.map[M_W2]); prefetch_map(&P.map[M_OUT_ST]);
          uint32_t* fl = scratch<uint32_t>(P, g * G_BLOCK + G_FLAGS);
          int pe = 0;
#pragma unroll 1
          for (int e = 0; e < 2 * EV_N; e++) {
            const int q = e & 7;
            const bool is_h = q >= EV_H0 && q < EV_XB, last = e >= EV_N + EV_XB;
            const CUtensorMap* map = &P.map[is_h ? M_H_ST : M_OUT_ST];
            const int col = q == EV_H3 ? 3072 - 64 + j * 64 : (q == EV_H1 ? 1024 : q == EV_H2 ? 2048 : 0) + j * 128;
            const int row = is_h ? 0 : (g >> 1) * 128, par = is_h ? g : g & 1;
#pragma unroll 1
            for (int hb = is_h ? q == EV_H3 : q & 1; hb <= (is_h ? 1 : q & 1); hb++) {
#pragma unroll
              for (int w = 0; w < 2; w++) {
                const bool sw = last;
                const int wg = sw ? hb : w, h = sw ? w : hb, p = sw ? pe - hb + w : pe;
                mbar_wait(sb + BAR_SFULL + 16 * wg + 8 * (p & 1), (p >> 1) & 1);
                if (w == 0) TL(3, 20 + e);
                tma_st3(map, sb + SM_STAGE + wg * PAGE + h * 8192, col + h * 64, par, row + wg * 64);
              }
              pe++;
            }
            bulk_commit();
            if (e != EV_N + EV_XB) bulk_wait<0>();
            TL(3, 40 + e);
            if (is_h || (q & 1)) mbar_arrive(sb + BAR_SEMPTY);
            if (!last) red_release(fl, 1u << j);
            TL(3, e);
            fl += 32;
          }
          *epoch_ptr(P) = tag;
        }
      }
    }
  } else {
    if (!spare) {
      const uint32_t r = threadIdx.x >> 3, so = r * 128 + (((threadIdx.x ^ r) & 7) << 4);
      const uint8_t* xp = ptr_add((const uint8_t*)P.x, (2 * ((g >> 1) * 128 + r) + (g & 1)) * 2048u + (threadIdx.x & 7) * 16u);
      const uint8_t* wp = ptr_add((const uint8_t*)P.wqkv, r * 6144u + 2048u + j * 256u + (threadIdx.x & 7) * 16u);
#pragma unroll
      for (int i = 0; i < 4; i++) asm volatile("cp.async.cg.shared.global [%0], [%1], 16;" :: "r"(sb + SM_STAGE + (i >> 1) * PAGE + (i & 1) * 4096 + so), "l"(xp + i * 32 * 4096) : "memory");
#pragma unroll
      for (int i = 0; i < 8; i++) asm volatile("cp.async.cg.shared.global [%0], [%1], 16;" :: "r"(sb + i * 4096 + so), "l"(wp + (i & 1) * 32 * 6144 + ((i >> 1) & 1) * 128 + (i >> 2) * 2048) : "memory");
    }
    if (!spare) {
      if (warp == 0) asm volatile("prefetch.global.L2 [%0];" :: "l"(ptr_add(P.x, (2 * ((g >> 1) * 128 + j * 16 + (lane >> 1)) + (g & 1)) * 2048u + (lane & 1) * 128u)));
      else if (warp < 3 && (warp == 1 || lane < 16)) asm volatile("prefetch.global.L2 [%0];" :: "l"(ptr_add(P.wqkv, role * 6144u + (warp - 1) * 4096u + lane * 128u)));
      __syncwarp();
    }
    asm volatile("barrier.cluster.arrive.relaxed.aligned;" ::: "memory");
    asm volatile("setmaxnreg.inc.sync.aligned.u32 232;");
    SP(4);
    asm volatile("barrier.cluster.wait.acquire.aligned;" ::: "memory");
    SP(5);
    const int wg = warp >> 2;
    const int quad = lane & 3, gr = lane >> 2;
    Cons c; c.sb = sb; c.n = 0; c.off = 0; c.prev = 0; c.lane = lane;
    c.ebar = mapa(sb + BAR_EMPTY - 64, shared_b() ? lane & 1 : rank);
    const uint32_t stage = sb + SM_STAGE + wg * PAGE;
    const uint32_t dstage = desc_lo(stage, 16);
    if (spare) {
      const uint32_t tag = ld_relaxed(epoch_ptr(P)) + 1;
      const int tid = threadIdx.x & 127;
#pragma unroll
      for (int i = 0; i < 4; i++) sts128(stage + (i * 128 + tid) * 16, 0x3f803f80u, 0x3f803f80u, 0x3f803f80u, 0x3f803f80u);
      fence_async_smem();
      bar_sync(2 + wg, 128);
      c.db0 = desc_lo(sb + wg * PAGE, 8192);
#pragma unroll 1
      for (int r = -1; r < 7; r++) {
        float acc[64];
#pragma unroll 1
        for (int k = 0; k < 16; k++) c.step_ab<128, 2>(acc, dstage, c.db0 + c.off, k);
        c.drain();
        acc_fence<64>(acc);
        {
          float v = 0;
#pragma unroll
          for (int i = 0; i < 32; i++) asm("{\n.reg .pred p;\nsetp.eq.u32 p, %2, %3;\nselp.f32 %0, %1, %0, p;\n}" : "+f"(v) : "f"(acc[4 * (i >> 1) + (i & 1)]), "r"(tid >> 2), "r"(i));
          st_b128(scratch<uint4>(P, G_CS + (uint32_t)((r < 0 ? j * 256 + wg * 128 : 3 * DM + wg * FF + ((r < 2 ? r : r == 2 ? 6 : r - 1) * 4 + j) * 128) + (tid >> 3) * 8 + quad * 2 + (gr & 1)) * 16u),
                  tagf(v, tag), tag & 15u, tag & 15u, tag & 15u);
        }
        __syncwarp();
      }
      if (wg == 0) {
        const uint32_t* p = scratch<uint32_t>(P, (tid >> 3) * G_BLOCK + G_STATS + (tid & 7) * 8u);
        uint32_t spins = 0;
        while (__any_sync(0xffffffffu, (ld_relaxed(p) ^ tag) & 15u)) spin_check(++spins);
      }
      bar_sync(1, 256);
      if (threadIdx.x == 0) *epoch_ptr(P) = tag;
    } else {
    c.da0 = desc_lo(sb + wg * 8192, 16); c.db0 = desc_lo(sb, 8192);
    uint32_t sphase = 1, sfull = sb + BAR_SFULL + 16 * wg;
    const uint32_t maddr = stage + ((warp & 3) * 16 + (lane & 15)) * 128 + (((lane >> 4) ^ (lane & 7)) << 4);
    const uint32_t csaddr = sb + SM_CS + quad * 16;
    float st[8] = {0, 0, 0, 0, 0, 0, 0, 0};
    float* const mean = st; float* const rstd = st + 2;
    SP(6);

    auto stage_wait = [&]() { mbar_wait_fast(sb + BAR_SEMPTY, sphase); sphase ^= 1; };
    auto stage_publish = [&]() { fence_async_smem(); __syncwarp(); if (lane == 0) mbar_arrive(sfull); sfull ^= 8; };
    auto cs_load = [&](uint32_t (&cs)[16], int grp) {
#pragma unroll
      for (int i = 0; i < 4; i++) lds128(csaddr + grp * 256 + i * 64, cs[4 * i], cs[4 * i + 1], cs[4 * i + 2], cs[4 * i + 3]);
    };
    auto cs_apply = [&](float* acc, uint32_t (&cs)[16]) {
      acc_fence<32>(acc);
#pragma unroll
      for (int b = 0; b < 8; b++) {
        acc[4 * b] -= mean[0] * __uint_as_float(cs[2 * b]); acc[4 * b + 1] -= mean[0] * __uint_as_float(cs[2 * b + 1]);
        acc[4 * b + 2] -= mean[1] * __uint_as_float(cs[2 * b]); acc[4 * b + 3] -= mean[1] * __uint_as_float(cs[2 * b + 1]);
      }
      acc_fence<32>(acc);
    };
    auto glu_pair = [&](float g0, float g1, float u0, float u1, int r) {
      const float nl = -LOG2E * rstd[r], r2 = rstd[r] * rstd[r];
      return pack_bf16(g0 * u0 * r2 * rcp(1.0f + ex2(g0 * nl)), g1 * u1 * r2 * rcp(1.0f + ex2(g1 * nl)));
    };
    auto glu_slice = [&](uint32_t (&pk)[64], int i) {
      uint32_t hp[4];
#pragma unroll
      for (int e = 0; e < 4; e++) {
        asm volatile("" : "+r"(pk[4 * i + e]), "+r"(pk[32 + 4 * i + e]));
        const uint32_t pg = pk[4 * i + e], pu = pk[32 + 4 * i + e];
        hp[e] = glu_pair(bf_lo(pg), bf_hi(pg), bf_lo(pu), bf_hi(pu), e & 1);
      }
      stsm4((maddr ^ ((i & 3) << 5)) + (i >> 2) * 8192, hp[0], hp[1], hp[2], hp[3]);
    };
    auto glu_slice_acc = [&](float (&acc)[128], int i) {
      uint32_t hp[4];
      acc_fence<8>(acc + 8 * i);
#pragma unroll
      for (int e = 0; e < 4; e++) hp[e] = glu_pair(acc[8 * i + 2 * e], acc[8 * i + 2 * e + 1], acc[64 + 8 * i + 2 * e], acc[64 + 8 * i + 2 * e + 1], e & 1);
      stsm4((maddr ^ ((i & 3) << 5)) + (i >> 2) * 8192, hp[0], hp[1], hp[2], hp[3]);
    };
    auto stage_x = [&](uint32_t (&x)[32], int hf) {
#pragma unroll
      for (int i = 4 * hf; i < 4 * hf + 4; i++) stsm4((maddr ^ ((i & 3) << 5)) + hf * 8192, x[4 * i], x[4 * i + 1], x[4 * i + 2], x[4 * i + 3]);
    };

    float acc[128];
    asm volatile("cp.async.wait_all;" ::: "memory");
    fence_async_smem();
    bar_sync(1, 256);
    SP(7);
    c.step_own<256>(acc, dstage, 0);
    mbar_wait_fast(sb + BAR_XIN, 0);
    SP(8);
#pragma unroll 1
    for (int hl = 0;; hl++) {
      int t = hl & 1;
      float acc2[64];
      uint32_t res[32];
      c.step_own<256>(acc, dstage + 512, 1);
#pragma unroll
      for (int s = 0; s < 2; s++) c.step_own<128>(acc2, dstage + s * 512, s);
#pragma unroll 1
      for (int s = 2; s < 11; s++) {
        const uint32_t apage = (c.off << 4) - (SM_STAGE + wg * 8192);
        c.step<256>(acc);
        int act = s;
        asm volatile("" : "+r"(act));
        auto get_tag = [&]() { uint32_t tag; asm volatile("ld.shared.u32 %0, [%1];" : "=r"(tag) : "r"(sb + SM_TAG) : "memory"); return tag; };
        auto stat_ptr = [&]() { return scratch<uint2>(P, g * G_BLOCK + G_STATS + (hl * 128 + warp * 16 + (lane_now() >> 2)) * 64u); };
        auto stat_get = [&]() {
          const uint2* sp = ptr_add(stat_ptr(), (lane_now() & 3) * 16);
          const uint4 a = ld_relaxed4(sp), b = ld_relaxed4(sp + 64);
          st[0] = __uint_as_float(a.x); st[1] = __uint_as_float(a.y); st[2] = __uint_as_float(a.z); st[3] = __uint_as_float(a.w);
          st[4] = __uint_as_float(b.x); st[5] = __uint_as_float(b.y); st[6] = __uint_as_float(b.z); st[7] = __uint_as_float(b.w);
        };
        switch (act) {
          case 4: case 5: {
            const uint32_t ra = maddr + ((hl || j == 0) ? (s & 1) * 8192 : apage);
#pragma unroll
            for (int i = 0; i < 4; i++) {
              uint32_t v[4];
              ldsm4(ra ^ (i << 5), v[0], v[1], v[2], v[3]);
              if (i == 0 && s == 4) { st[0] = bf_lo(v[0]); st[1] = bf_lo(v[1]); st[2] = st[3] = st[4] = st[5] = 0; }
#pragma unroll
              for (int e = 0; e < 4; e++) {
                const float a = bf_lo(v[e]) - st[e & 1], b = bf_hi(v[e]) - st[e & 1];
                st[2 + (e & 1)] += a + b; st[4 + (e & 1)] += a * a; st[4 + (e & 1)] += b * b;
              }
            }
          } break;
          case 6: {
            mbar_wait_fast(sb + BAR_TAG, 0);
            const uint32_t tag = get_tag();
#pragma unroll
            for (int r = 0; r < 2; r++) {
              const float mt = st[r] + st[2 + r] * (1.0f / 32);
              float m = mt + __shfl_xor_sync(0xffffffffu, mt, 1); m += __shfl_xor_sync(0xffffffffu, m, 2); m *= 0.25f;
              float q = st[4 + r] - st[2 + r] * st[2 + r] * (1.0f / 32) + 32.0f * (mt - m) * (mt - m);
              q += __shfl_xor_sync(0xffffffffu, q, 1); q += __shfl_xor_sync(0xffffffffu, q, 2);
              if (quad == 0) st_relaxed2(ptr_add(stat_ptr(), r * 512 + j * 8), tagf(m, tag), tagf(q, tag));
            }
          } break;
          case 8: stat_get(); break;
          case 10: {
            const uint32_t tag = get_tag();
            uint32_t spins = 0;
            for (;;) {
              uint32_t bad = 0;
#pragma unroll
              for (int i = 0; i < 8; i++) bad |= __float_as_uint(st[i]) ^ tag;
              if (!__any_sync(0xffffffffu, bad & 15u)) break;
              stat_get(); spin_check(++spins);
            }
            float mr[4];
#pragma unroll
            for (int r = 0; r < 2; r++) {
              const float m0 = untag(__float_as_uint(st[4 * r])), m1 = untag(__float_as_uint(st[4 * r + 2]));
              float m = m0 + m1; m += __shfl_xor_sync(0xffffffffu, m, 1); m += __shfl_xor_sync(0xffffffffu, m, 2); m *= 0.125f;
              float q = untag(__float_as_uint(st[4 * r + 1])) + untag(__float_as_uint(st[4 * r + 3])) + 128.0f * ((m0 - m) * (m0 - m) + (m1 - m) * (m1 - m));
              q += __shfl_xor_sync(0xffffffffu, q, 1); q += __shfl_xor_sync(0xffffffffu, q, 2);
              mr[r] = m; mr[2 + r] = rsqrtf(fmaxf(q, 0.f) * (1.0f / DM) + LN_EPS);
            }
            st[0] = mr[0]; st[1] = mr[1]; st[2] = mr[2]; st[3] = mr[3];
          } break;
          default: break;
        }
      }
#pragma unroll 1
      for (;;) {
      const int it = (hl >> 1) * 4 + t;
#pragma unroll
      for (int s = 0; s < 4; s++) {
        uint32_t cs[16];
        c.step<256>(acc);
        if (!(s & 1)) mbar_wait_fast(sb + BAR_CSF + 4 * s, t & 1);
        if (s >= 2 && t <= 1) { cs_load(cs, 2 + s); cs_apply(acc2 + 32 * (s - 2), cs); }
        cs_load(cs, s);
        c.drain();
        cs_apply(acc + 32 * s, cs);
      }
      c.step<256>(acc);
      if (lane == 0) mbar_arrive(sb + BAR_CSE);
      c.drain();
      acc_fence<128>(acc);
      TLC(1 + it * 6);
      uint32_t pkB[64];
      if (t == 2) {
#pragma unroll
        for (int i = 0; i < 64; i++) pkB[i] = pack_bf16(acc[2 * i], acc[2 * i + 1]);
      } else if (t == 0) {
        uint32_t pkA[64];
        auto kv_pack = [&](int v, int r) {
#pragma unroll
          for (int i = 32 * v + r; i < 32 * v + 32; i += 2) { acc_fence<2>(acc + 2 * i); pkA[i] = pack_bf16(acc[2 * i] * rstd[r], acc[2 * i + 1] * rstd[r]); }
        };
        const uint32_t l16 = lane_now() * 16u;
        uint4* const xs = ptr_add((uint4*)smem_raw, SM_STAGE + l16);
        uint4* const hp = scratch<uint4>(P, G_HALO + (((hl >> 1) * 16 + g) * 8 + j) * 4096u + l16);
        {
          uint4* const dst = (warp == 7 && g < 14) ? hp : ptr_add(xs, warp * 4096u);
#pragma unroll
          for (int s = 0; s < 2; s++) {
            c.steps<128>(acc2, s ? 2 : 1 + wg);
            if (s == 0) stage_wait();
            kv_pack(s, 1);
#pragma unroll
            for (int i = 4 * s; i < 4 * s + 4; i++) { pkA[8 * i + 1] = pkt_head(pkA[8 * i + 1]); gen_store(dst + i * 32, pkA[8 * i + 1], pkA[8 * i + 3], pkA[8 * i + 5], pkA[8 * i + 7]); }
          }
        }
        __syncwarp();
        if (lane == 0) mbar_arrive(sb + BAR_XFULL);
#pragma unroll
        for (int s = 0; s < 2; s++) {
          c.steps<128>(acc2, 2);
#pragma unroll
          for (int i = 33 - s; i < 64; i += 2) pkA[i] = movm(pkA[i]);
          kv_pack(1 - s, 0);
        }
        uint32_t kvH[32];
        {
          const uint4* const src = (warp == 0 && g >= 2) ? hp - 2 * 8 * 256 : ptr_add(xs, (warp ? warp - 1 : 0) * 4096u);
          c.steps<128>(acc2, 2);
          mbar_wait_fast(sb + BAR_XFULL, hl >> 1);
#pragma unroll
          for (int i = 0; i < 8; i++) gen_load(src + i * 32, kvH + 4 * i);
          c.steps<128>(acc2, 3 - wg);
          uint32_t spins = 0;
          while (__any_sync(0xffffffffu, !(kvH[0] && kvH[4] && kvH[8] && kvH[12] && kvH[16] && kvH[20] && kvH[24] && kvH[28]))) {
#pragma unroll
            for (int i = 0; i < 8; i++) gen_load(src + i * 32, kvH + 4 * i);
            spin_check(++spins);
          }
        }
#pragma unroll
        for (int i = 16; i < 32; i++) kvH[i] = movm(kvH[i]);
        mbar_wait_fast(sb + BAR_CLR, hl >> 1);
        c.steps<128>(acc2, 2);
        AP(0);
        c.wait_full(0);
        AP(1);
        c.drain();
        AP(2);
        acc_fence<64>(acc2);
        TLC(2 + it * 6);
        uint32_t q[32];
#pragma unroll
        for (int i = 0; i < 32; i++) q[i] = pack_bf16(acc2[2 * i], acc2[2 * i + 1]);
        const uint32_t zm = bar_sync_zero(1, 256);
        AP(3);
        uint32_t ob[6][16];
        uint4* const omail = scratch<uint4>(P, g * G_BLOCK + G_O + warp * 2048u + l16);
        float o2[8][4], r2[4];
        {
          const float hv = (warp == 0 && g < 2) ? -INFINITY : 0.f;
          const float hinit[4] = {hv, hv, hv, hv};
          const bool c0 = (2 * quad <= gr), c1 = (2 * quad + 1 <= gr);
          const uint32_t lm = (c0 ? 0xffffu : 0u) | (c1 ? 0xffff0000u : 0u);
          const float sc[2] = {rstd[0] * (0.17677669529663687f * LOG2E), rstd[1] * (0.17677669529663687f * LOG2E)};
          float lg[4][4], mx[4][2];
#pragma unroll
          for (int h = 0; h < 4; h++) {
            const int b = h * 4;
            float sH[4], sL[4], sU[4];
            q[2 * b] |= zm;
            mma16816(sH, q[2 * b], q[2 * b + 1], q[2 * b + 2], q[2 * b + 3], kvH[b], kvH[b + 1], hinit);
            mma16816z(sL, q[2 * b], q[2 * b + 1], q[2 * b + 2], q[2 * b + 3], pkA[2 * b], pkA[2 * b + 2]);
            mma16816z(sU, q[2 * b], q[2 * b + 1], q[2 * b + 2], q[2 * b + 3], pkA[2 * b + 1], pkA[2 * b + 3]);
            mma16816(sH, q[2 * b + 4], q[2 * b + 5], q[2 * b + 6], q[2 * b + 7], kvH[b + 2], kvH[b + 3], sH);
            mma16816(sL, q[2 * b + 4], q[2 * b + 5], q[2 * b + 6], q[2 * b + 7], pkA[2 * b + 4], pkA[2 * b + 6], sL);
            mma16816(sU, q[2 * b + 4], q[2 * b + 5], q[2 * b + 6], q[2 * b + 7], pkA[2 * b + 5], pkA[2 * b + 7], sU);
            lg[h][0] = c0 ? sL[0] : sH[0]; lg[h][1] = c1 ? sL[1] : sH[1]; lg[h][2] = c0 ? sU[2] : sL[2]; lg[h][3] = c1 ? sU[3] : sL[3];
            mx[h][0] = fmaxf(lg[h][0], lg[h][1]); mx[h][1] = fmaxf(lg[h][2], lg[h][3]);
          }
#pragma unroll
          for (int o = 1; o < 4; o <<= 1) {
#pragma unroll
            for (int i = 0; i < 8; i++) mx[i >> 1][i & 1] = fmaxf(mx[i >> 1][i & 1], __shfl_xor_sync(0xffffffffu, mx[i >> 1][i & 1], o));
          }
          AP(4);
          uint32_t z = zm, pp[4][2];
          float rs[4][2];
          auto probs = [&](int h) {
            pp[h][0] = pack_bf16(ex2((lg[h][0] - mx[h][0]) * sc[0]), ex2((lg[h][1] - mx[h][0]) * sc[0]));
            pp[h][1] = pack_bf16(ex2((lg[h][2] - mx[h][1]) * sc[1]), ex2((lg[h][3] - mx[h][1]) * sc[1]));
            float sum[4];
            mma1688z(sum, pp[h][0], pp[h][1], 0x3f803f80u);
            rs[h][0] = rcp(sum[0]); rs[h][1] = rcp(sum[2]);
            asm volatile("" : "+f"(rs[h][0]), "+f"(rs[h][1]));
          };
          probs(0); probs(1); probs(2); probs(3);
#pragma unroll
          for (int hf = 0; hf < 2; hf++) {
#pragma unroll
            for (int hh = 0; hh < 2; hh++) {
              const int h = hf * 2 + hh, b = h * 4;
              const uint32_t pa = pp[h][0], pb = pp[h][1];
              const uint32_t p0 = pa & ~lm, p1 = pa & z, p2 = pa & lm, p3 = pb & ~lm, p4 = pb & z, p5 = pb & lm;
              const float ra = rs[h][0], rb = rs[h][1];
#pragma unroll
              for (int d = 0; d < 4; d++) {
                float o[4];
                mma16816z(o, p0, p1, p2, p3, kvH[16 + b + d], pkA[32 + 2 * (b + d)]);
                mma1688(o, p4, p5, pkA[32 + 2 * (b + d) + 1], o);
                if (hf == 0) { ob[0][(hh * 4 + d) * 2] = pack_bf16(o[0] * ra, o[1] * ra); ob[0][(hh * 4 + d) * 2 + 1] = pack_bf16(o[2] * rb, o[3] * rb); }
                else { o2[hh * 4 + d][0] = o[0]; o2[hh * 4 + d][1] = o[1]; o2[hh * 4 + d][2] = o[2]; o2[hh * 4 + d][3] = o[3]; }
              }
              if (hf) { r2[2 * hh] = ra; r2[2 * hh + 1] = rb; }
            }
            if (hf == 0) {
#pragma unroll
              for (int i = 0; i < 4; i++) ob[0][4 * i] = pkt_head(ob[0][4 * i]);
              AP(5);
              uint4* op = ptr_add(omail, j * 32768u);
#pragma unroll
              for (int i = 0; i < 4; i++) st_b128(op + i * 32, ob[0][4 * i], ob[0][4 * i + 1], ob[0][4 * i + 2], ob[0][4 * i + 3]);
              z = late_zero(zm);
              AP(6);
            }
          }
        }
        auto finish_o2 = [&](uint32_t z) {
#pragma unroll
          for (int i = 0; i < 4; i++) r2[i] = __uint_as_float(__float_as_uint(r2[i]) | z);
#pragma unroll
          for (int i = 0; i < 8; i++) {
            ob[1][2 * i] = pack_bf16(o2[i][0] * r2[(i >> 2) * 2], o2[i][1] * r2[(i >> 2) * 2]);
            ob[1][2 * i + 1] = pack_bf16(o2[i][2] * r2[(i >> 2) * 2 + 1], o2[i][3] * r2[(i >> 2) * 2 + 1]);
          }
#pragma unroll
          for (int i = 0; i < 4; i++) { ob[1][4 * i] = pkt_head(ob[1][4 * i]); sts128(stage + (warp & 3) * 2048 + i * 512 + l16, ob[1][4 * i], ob[1][4 * i + 1], ob[1][4 * i + 2], ob[1][4 * i + 3]); }
        };
        {
          uint32_t dep = __float_as_uint(r2[0]) | __float_as_uint(r2[2]);
#pragma unroll
          for (int i = 0; i < 8; i++) dep |= __float_as_uint(o2[i][3]);
          const uint32_t cnt = 256 | (dep & zm);
          AP(7);
          if (wg) { asm volatile("bar.arrive 1, %0;" :: "r"(cnt) : "memory"); bar_sync(6, 256); } else bar_sync(1, cnt);
        }
        TLC(3 + it * 6);
        AP(8);
        uint64_t todo;
        { const uint32_t o7 = 0x6543210u | (7u << (4 * j) & 0xfffffffu); todo = (uint64_t)(o7 * 2) | (uint64_t)(o7 * 2 + 0x1111111u) << 28; }
        const uint4* pf[3];
        auto next_ptrs = [&](const uint4* (&p)[3]) {
#pragma unroll
          for (int i = 0; i < 3; i++) p[i] = ptr_add(omail, (((uint32_t)todo >> (4 * i)) & 15u) << 14);
          asm volatile("" : "+l"(p[0]), "+l"(p[1]), "+l"(p[2]));
          todo >>= 12;
        };
        next_ptrs(pf);
        auto batch = [&](int b, bool first, bool three) {
          const int y = 3 - b;
          auto o_fetch = [&]() {
#pragma unroll
            for (int i = 0; i < 8; i++) pkt_load(pf[i >> 2] + (i & 3) * 32, ob[y + (i >> 2)] + 4 * (i & 3));
            if (three) {
#pragma unroll
              for (int i = 0; i < 4; i++) pkt_load(pf[2] + i * 32, ob[y + 2] + 4 * i);
            }
          };
          if (first) {
            c.issue_rs<0, 2>(acc2, ob[0], 0);
            finish_o2(late_zero(zm));
            o_fetch();
            c.issue_rs<1, 2>(acc2, ob[1]);
            if (!wg) asm volatile("bar.arrive 6, 256;" ::: "memory");
          } else {
            o_fetch();
            c.issue_rs<0, 3>(acc2, ob[b]); c.issue_rs<1, 3>(acc2, ob[b + 1]); c.issue_rs<2, 3>(acc2, ob[b + 2]);
          }
          const uint32_t z = late_zero(zm);
          const uint4* pn[3];
          next_ptrs(pn);
          c.wait_full(0);
          uint32_t spins = 0;
          for (;;) {
            bool bad[3];
#pragma unroll
            for (int i = 0; i < 3; i++) bad[i] = ob[y + i][0] == z || ob[y + i][4] == z || ob[y + i][8] == z || ob[y + i][12] == z;
            if (__builtin_expect(!__any_sync(0xffffffffu, bad[0] | bad[1] | bad[2]), 1)) break;
            o_fetch();
            spin_check(++spins);
          }
          if (first) {
            fence_async_smem();
            __syncwarp();
            if (elect_one()) {
              asm volatile("cp.async.bulk.global.shared::cta.bulk_group [%0], [%1], 2048;"
                           :: "l"(scratch<uint4>(P, g * G_BLOCK + G_O + (2 * j + 1) * 16384u + warp * 2048u)), "r"(stage + (warp & 3) * 2048) : "memory");
              bulk_commit();
            }
          }
          pf[0] = pn[0]; pf[1] = pn[1]; pf[2] = pn[2];
          c.drain();
        };
        batch(0, true, true);
#pragma unroll 1
        for (int i = 0; i < 2; i++) { batch(3, false, true); batch(0, false, i == 0); }
        c.issue_rs<0, 2>(acc2, ob[3]); c.issue_rs<1, 2>(acc2, ob[4]);
        if (elect_one()) bulk_wait<0>();
        __syncwarp();
        {
          c.off += 2 << 10;
          c.wait_full(0);
          const uint32_t ra = maddr - (SM_STAGE + wg * 8192) + (c.off << 4);
#pragma unroll
          for (int i = 0; i < 8; i++) ldsm4((ra ^ ((i & 3) << 5)) + (i >> 2) * PAGE, res[4 * i], res[4 * i + 1], res[4 * i + 2], res[4 * i + 3]);
          if (lane < 2) mbar_arrive_cluster(c.ebar + 64 + ((c.n & 7) << 3));
          c.advance<2>();
          c.drain();
        }
        break;
      } else {
        c.steps<128>(acc2, 1 + wg);
        stage_wait();
        glu_slice_acc(acc, 0);
#pragma unroll
        for (int s = 1; s < 8; s++) {
          if (s == 5) c.steps_skip(acc2, t == 1 ? 1 - wg : 2); else c.steps<128>(acc2, (s & 1) || t == 3 ? 2 : 1);
          if (s == 4) stage_publish();
          glu_slice_acc(acc, s);
        }
        c.steps<128>(acc2, 2 - wg);
        stage_publish();
        if (t == 3) {
#pragma unroll
          for (int i = 0; i < 32; i++) { res[i] = 0x80008000u; asm volatile("" : "+r"(res[i])); }
#pragma unroll 1
          for (int i = 0; i < 3; i++) {
            c.steps<128>(acc2, i == 0 ? 15 : i == 1 ? 24 - TAIL_LAG : TAIL_LAG);
            if (i == 0) c.off = 0;
            else if (hl == 3) { if (wg == 1 && i == 1) { c.drain(); bar_sync(5, 256); } else if (wg == 0 && i == 2) asm volatile("bar.arrive 5, 256;" ::: "memory"); }
          }
          stage_wait();
          c.drain();
          break;
        }
        c.drain();
        TLC(2 + it * 6);
        c.step<256>(acc, 0);
        acc_fence<64>(acc2);
#pragma unroll
        for (int i = 0; i < 16; i++) {
          pkB[16 + i] = pack_bf16(acc2[2 * i], acc2[2 * i + 1]); pkB[48 + i] = pack_bf16(acc2[32 + 2 * i], acc2[32 + 2 * i + 1]);
          pkB[i] = 0; pkB[32 + i] = 0;
        }
      }
      t++;
#pragma unroll 1
      for (int s = 3 - t; s < 8; s++) {
        c.step<256>(acc, s);
        int act = (t == 3 || s >= 4) ? s : 8;
        asm volatile("" : "+r"(act));
        if (act < 8) {
          if (!(act & 3)) { if (act && t == 3) stage_publish(); else stage_wait(); }
          auto f = [&](int i) { glu_slice(pkB, i); };
          SELECT8(act, f);
        }
      }
#pragma unroll
      for (int s = 0; s < 2; s++) {
        const uint32_t ra = maddr - (SM_STAGE + wg * 8192) + (c.off << 4);
        c.step<256>(acc);
        if (s == 0) stage_publish();
#pragma unroll
        for (int i = 0; i < 4; i++) {
          uint32_t v[4];
          ldsm4(ra ^ (i << 5), v[0], v[1], v[2], v[3]);
#pragma unroll
          for (int e = 0; e < 4; e++) { acc2[32 * s + 8 * i + 2 * e] = bf_lo(v[e]); acc2[32 * s + 8 * i + 2 * e + 1] = bf_hi(v[e]); }
        }
        acc_fence<32>(acc2 + 32 * s);
      }
      c.step<256>(acc);
      }
      const int it = (hl >> 1) * 4 + t;
      acc_fence<64>(acc2);
      TLC(4 + it * 6);
      uint32_t xn[32];
#pragma unroll
      for (int i = 0; i < 16; i++) xn[i] = add_bf16x2(res[i], pack_bf16(acc2[2 * i], acc2[2 * i + 1]));
      stage_x(xn, 0);
#pragma unroll
      for (int i = 16; i < 32; i++) { xn[i] = add_bf16x2(res[i], pack_bf16(acc2[2 * i], acc2[2 * i + 1])); asm volatile("" : "+r"(xn[i])); }
      stage_publish();
      if (hl == 3) { stage_x(xn, 1); stage_publish(); TLE(47); TLG(63); break; }
      bar_sync(2 + wg, 128);
      TLC(5 + it * 6);
      c.step_own<256>(acc, dstage, 0);
      stage_x(xn, 1);
      stage_publish();
      bar_sync(2 + wg, 128);
    }
    }
  }
}

typedef CUresult (*EncodeFn)(CUtensorMap*, CUtensorMapDataType, cuuint32_t, void*, const cuuint64_t*, const cuuint64_t*, const cuuint32_t*,
                             const cuuint32_t*, CUtensorMapInterleave, CUtensorMapSwizzle, CUtensorMapL2promotion, CUtensorMapFloatOOBfill);

void encode(EncodeFn fn, CUtensorMap* m, const void* ptr, int rank, const cuuint64_t* dims, const cuuint64_t* strides, const cuuint32_t* box) {
  cuuint32_t es[5] = {1, 1, 1, 1, 1};
  fn(m, CU_TENSOR_MAP_DATA_TYPE_BFLOAT16, rank, const_cast<void*>(ptr), dims, strides, box, es, CU_TENSOR_MAP_INTERLEAVE_NONE,
     CU_TENSOR_MAP_SWIZZLE_128B, CU_TENSOR_MAP_L2_PROMOTION_L2_128B, CU_TENSOR_MAP_FLOAT_OOB_FILL_NONE);
}

}

extern "C" void kernel_launch(void* const* d_in, const int* in_sizes, int n_in, void* d_out, int out_size) {
  const __nv_bfloat16* x = (const __nv_bfloat16*)d_in[0];
  const __nv_bfloat16* wqkv = (const __nv_bfloat16*)d_in[1];
  const __nv_bfloat16* wo = (const __nv_bfloat16*)d_in[2];
  const __nv_bfloat16* w1 = (const __nv_bfloat16*)d_in[4];
  const __nv_bfloat16* w3 = (const __nv_bfloat16*)d_in[5];
  const __nv_bfloat16* w2 = (const __nv_bfloat16*)d_in[6];

  void* fnp = nullptr; cudaDriverEntryPointQueryResult qr;
  cudaGetDriverEntryPoint("cuTensorMapEncodeTiled", &fnp, cudaEnableDefault, &qr);
  EncodeFn fn = (EncodeFn)fnp;
  void* sym;
  cudaGetSymbolAddress(&sym, g_scratch);
  uint8_t* scr = (uint8_t*)(((uintptr_t)sym + G_PAGE - 1) / G_PAGE * G_PAGE);

  Params P = {};
  { cuuint64_t d[3] = {DM, 2, SEQ / 2}, s[2] = {DM * 2, DM * 4}; cuuint32_t b[3] = {64, 1, 128}, b2[3] = {64, 1, 64};
    encode(fn, &P.map[M_XIN], x, 3, d, s, b); encode(fn, &P.map[M_XIN64], x, 3, d, s, b2);
    encode(fn, &P.map[M_OUT_LD], d_out, 3, d, s, b); encode(fn, &P.map[M_OUT_ST], d_out, 3, d, s, b2); }
  { cuuint64_t d[3] = {FF, 16, 128}, s[2] = {G_BLOCK, FF * 2}; cuuint32_t b[3] = {64, 1, 128}, b2[3] = {64, 1, 64};
    encode(fn, &P.map[M_H_LD], scr + G_H, 3, d, s, b); encode(fn, &P.map[M_H_ST], scr + G_H, 3, d, s, b2); }
  { const cuuint32_t b2[3] = {64, 64, 2}, b1[3] = {64, 64, 1};
    { cuuint64_t d[3] = {64, DM, 48}, s[2] = {3 * DM * 2, 128}; encode(fn, &P.map[M_WKV], wqkv, 3, d, s, b2); encode(fn, &P.map[M_WQ], wqkv, 3, d, s, b1); }
    { cuuint64_t d[3] = {64, DM, 16}, s[2] = {DM * 2, 128}; encode(fn, &P.map[M_WO], wo, 3, d, s, b1); }
    { cuuint64_t d[3] = {64, FF, 16}, s[2] = {DM * 2, 128}; encode(fn, &P.map[M_W2], w2, 3, d, s, b1); }
    { cuuint64_t d[3] = {64, DM, FF / 64}, s[2] = {FF * 2, 128};
      encode(fn, &P.map[M_W1], w1, 3, d, s, b2); encode(fn, &P.map[M_W3], w3, 3, d, s, b2);
      encode(fn, &P.map[M_W1H], w1, 3, d, s, b1); encode(fn, &P.map[M_W3H], w3, 3, d, s, b1); }
  }
  P.scratch = scr; P.x = x; P.wqkv = wqkv; P.wo = wo; P.w2 = w2;
  int dev = 0, sms = 0;
  cudaGetDevice(&dev);
  cudaDeviceGetAttribute(&sms, cudaDevAttrMultiProcessorCount, dev);
  P.use_smid = (sms == 132);
  cudaFuncSetAttribute(fused_kernel, cudaFuncAttributeMaxDynamicSharedMemorySize, SM_ALLOC);
  fused_kernel<<<132, 384, SM_ALLOC>>>(P);
}
```

```cpp
#include <cuda_runtime.h>
#include <cuda_bf16.h>
#include <cuda.h>
#include <stdint.h>
#include <math.h>

namespace {

constexpr int SEQ = 2048, DM = 1024, FF = 3584;
constexpr float LN_EPS = 1e-5f;
constexpr float LOG2E = 1.4426950408889634f;

#define G_SKEW 4096
constexpr uint32_t G_PAGE = 2u << 20, G_BLOCK = G_PAGE + G_SKEW;
constexpr uint32_t G_H = 0;
constexpr uint32_t G_O = G_H + 128 * FF * 2;
constexpr uint32_t G_STATS = G_O + 128 * DM * 2;
constexpr uint32_t G_FLAGS = G_STATS + 4 * 128 * 64;
static_assert(G_FLAGS + 4096 + 15 * G_SKEW <= G_PAGE, "");
constexpr uint32_t G_HALO = 16 * G_PAGE;
constexpr uint32_t G_CS = G_HALO + 2 * 16 * 8 * 4096;
constexpr uint32_t G_EPOCH = G_CS + (3 * DM + 2 * FF) * 16;
__device__ __align__(1024) uint8_t g_scratch[18 * G_PAGE];

enum { M_XIN, M_XIN64, M_H_LD, M_H_ST, M_OUT_LD, M_OUT_ST, M_WKV, M_WQ, M_WO, M_W1, M_W3, M_W1H, M_W3H, M_W2, M_COUNT };
struct alignas(64) Params {
  CUtensorMap map[M_COUNT];
  uint8_t* scratch;
  const __nv_bfloat16* x;
  const __nv_bfloat16* wqkv;
  const __nv_bfloat16* wo;
  const __nv_bfloat16* w2;
  int use_smid;
};

constexpr uint32_t PAGE = 16384, NPAGE = 12;
constexpr uint32_t SM_STAGE = NPAGE * PAGE;
constexpr uint32_t SM_BAR = SM_STAGE + 2 * PAGE;
constexpr uint32_t SM_CS = SM_BAR + 256;
constexpr uint32_t SM_TOTAL = SM_CS + 1536;
constexpr uint32_t SM_ALLOC = SM_TOTAL;
static_assert(SM_ALLOC <= 232448, "shared memory");
constexpr uint32_t BAR_FULL = SM_BAR, BAR_EMPTY = SM_BAR + 64, BAR_SFULL = SM_BAR + 128;
constexpr uint32_t BAR_XFULL = SM_BAR + 160, BAR_CSE = SM_BAR + 168;
constexpr uint32_t BAR_SEMPTY = SM_BAR + 176, BAR_CSF = SM_BAR + 184, BAR_XIN = SM_BAR + 200;
constexpr uint32_t BAR_CLR = SM_BAR + 240, BAR_TAG = SM_BAR + 216, SM_ROLE = SM_BAR + 224, SM_TAG = SM_BAR + 228, SM_SEEN = SM_BAR + 232;
enum { EV_XA, EV_XA2, EV_H0, EV_H3, EV_H1, EV_H2, EV_XB, EV_XB2, EV_N };

struct Sched { uint32_t pat[16]; uint32_t page0[16]; bool ok; };
constexpr int seg_steps(int seg) { return seg == 0 || seg == 3 ? 18 : seg == 1 || seg == 4 ? 14 : seg == 2 ? 7 : seg == 7 ? 24 : 32; }
constexpr int step_pages(int seg, int i) {
  return seg == 0 || seg == 3 ? (i < 2 ? 2 : i < 4 ? 1 : 3) : seg == 5 || (seg == 2 && i >= 1 && i <= 4) ? 3 : 2;
}
constexpr Sched make_sched() {
  Sched s = {};
  int owner[NPAGE] = {-1, -1, -1, -1, -1, -1, -1, -1, -1, -1, -1, -1};
  int n = 0, tail = 0, page = 0;
  s.ok = true;
  for (int sg = 0; sg < 16; sg++) {
    const int seg = sg % 8;
    s.page0[sg] = page;
    for (int i = 0; i < seg_steps(seg); i++) {
      const int p = step_pages(seg, i);
      if ((seg == 2 && i == 6) || (seg == 4 && i == 8) || (seg == 7 && i == 0)) page = (page + 2) % NPAGE;
      if (page + p > (int)NPAGE) { s.ok = false; return s; }
      int need = n - 8;
      for (int q = 0; q < p; q++) { if (owner[page + q] > need) need = owner[page + q]; owner[page + q] = n; }
      int nw = need + 1 - tail; if (nw < 0) nw = 0;
      tail += nw;
      if (i < 16) s.pat[sg] |= (uint32_t)nw << (2 * i); else if (nw != 1) s.ok = false;
      if (nw > 3) s.ok = false;
      page = (page + p) % NPAGE; n++;
    }
  }
  for (int sg = 0; sg < 8; sg++) if (s.page0[sg] != s.page0[sg + 8] || (sg && s.pat[sg] != s.pat[sg + 8])) s.ok = false;
  return s;
}
constexpr Sched SCHED = make_sched();
static_assert(SCHED.ok && SCHED.page0[0] == 0 && SCHED.page0[3] == 0 && SCHED.page0[5] == 6 && SCHED.page0[2] == 4 && SCHED.page0[7] == 10 && (SCHED.pat[0] & 0xfff) == 0, "ring schedule");
template <int SEG> struct Pat { static constexpr uint32_t v = SCHED.pat[SEG]; };

#define TAIL_LAG 3
__device__ __forceinline__ uint32_t smem_u32(const void* p) { return (uint32_t)__cvta_generic_to_shared(p); }
__device__ __forceinline__ void mbar_init(uint32_t bar, uint32_t cnt) { asm volatile("mbarrier.init.shared::cta.b64 [%0], %1;" :: "r"(bar), "r"(cnt)); }
__device__ __forceinline__ void mbar_expect_tx(uint32_t bar, uint32_t bytes) { asm volatile("mbarrier.arrive.expect_tx.shared::cta.b64 _, [%0], %1;" :: "r"(bar), "r"(bytes) : "memory"); }
__device__ __forceinline__ void mbar_arrive(uint32_t bar) { asm volatile("mbarrier.arrive.shared::cta.b64 _, [%0];" :: "r"(bar) : "memory"); }
__device__ __forceinline__ void mbar_wait(uint32_t bar, uint32_t parity) {
  asm volatile("{\n.reg .pred p;\n.reg .u32 n;\nmov.u32 n, 0;\nLAB_WAIT:\n"
               "mbarrier.try_wait.parity.shared::cta.b64 p, [%0], %1;\n@p bra LAB_DONE;\n"
               "add.u32 n, n, 1;\nsetp.lt.u32 p, n, 4194304;\n@p bra LAB_WAIT;\ntrap;\nLAB_DONE:\n}" :: "r"(bar), "r"(parity) : "memory");
}
__device__ __forceinline__ void mbar_wait_fast(uint32_t bar, uint32_t parity) {
  asm volatile("{\n.reg .pred p;\nLAB_WAIT:\nmbarrier.try_wait.parity.shared::cta.b64 p, [%0], %1;\n@!p bra LAB_WAIT;\n}" :: "r"(bar), "r"(parity) : "memory");
}
__device__ __forceinline__ void spin_check(uint32_t n) { asm volatile("{\n.reg .pred p;\nsetp.ge.u32 p, %0, 4194304;\n@p st.volatile.global.u32 [%1], %0;\n}" :: "r"(n), "l"(0ull)); }
__device__ __forceinline__ void tma_ld3(uint32_t dst, const CUtensorMap* m, uint32_t bar, int c0, int c1, int c2) {
  asm volatile("cp.async.bulk.tensor.3d.shared::cluster.global.mbarrier::complete_tx::bytes [%0], [%1, {%3, %4, %5}], [%2];" :: "r"(dst), "l"(m), "r"(bar), "r"(c0), "r"(c1), "r"(c2) : "memory");
}
__device__ __forceinline__ void tma_ld3_mc(uint32_t dst, const CUtensorMap* m, uint32_t bar, int c0, int c1, int c2, uint16_t mask) {
  asm volatile("cp.async.bulk.tensor.3d.shared::cluster.global.mbarrier::complete_tx::bytes.multicast::cluster [%0], [%1, {%3, %4, %5}], [%2], %6;"
               :: "r"(dst), "l"(m), "r"(bar), "r"(c0), "r"(c1), "r"(c2), "h"(mask) : "memory");
}
__device__ __forceinline__ uint32_t mapa(uint32_t addr, uint32_t cta) { uint32_t r; asm("mapa.shared::cluster.u32 %0, %1, %2;" : "=r"(r) : "r"(addr), "r"(cta)); return r; }
__device__ __forceinline__ void mbar_arrive_cluster(uint32_t bar) { asm volatile("mbarrier.arrive.shared::cluster.b64 _, [%0];" :: "r"(bar) : "memory"); }
__device__ __forceinline__ void tma_st3(const CUtensorMap* m, uint32_t src, int c0, int c1, int c2) {
  asm volatile("cp.async.bulk.tensor.3d.global.shared::cta.bulk_group [%0, {%2, %3, %4}], [%1];" :: "l"(m), "r"(src), "r"(c0), "r"(c1), "r"(c2) : "memory");
}
__device__ __forceinline__ void bulk_commit() { asm volatile("cp.async.bulk.commit_group;" ::: "memory"); }
template <int N> __device__ __forceinline__ void bulk_wait() { asm volatile("cp.async.bulk.wait_group %0;" :: "n"(N) : "memory"); }
__device__ __forceinline__ void fence_async_smem() { asm volatile("fence.proxy.async.shared::cta;" ::: "memory"); }
__device__ __forceinline__ void fence_async_global() { asm volatile("fence.proxy.async.global;" ::: "memory"); }
__device__ __forceinline__ bool elect_one() { uint32_t p; asm volatile("{\n.reg .pred P;\nelect.sync _|P, 0xffffffff;\nselp.u32 %0, 1, 0, P;\n}" : "=r"(p)); return p; }
__device__ __forceinline__ void prefetch_map(const CUtensorMap* m) { asm volatile("prefetch.tensormap [%0];" :: "l"(m) : "memory"); }
__device__ __forceinline__ void prefetch_l2(const void* p, uint32_t bytes) { asm volatile("cp.async.bulk.prefetch.L2.global [%0], %1;" :: "l"(p), "r"(bytes) : "memory"); }
__device__ __forceinline__ void wgmma_fence() { asm volatile("wgmma.fence.sync.aligned;" ::: "memory"); }
__device__ __forceinline__ void wgmma_commit() { asm volatile("wgmma.commit_group.sync.aligned;" ::: "memory"); }
template <int N> __device__ __forceinline__ void wgmma_wait() { asm volatile("wgmma.wait_group.sync.aligned %0;" :: "n"(N) : "memory"); }
__device__ __forceinline__ uint32_t desc_lo(uint32_t addr, uint32_t lbo) { return ((addr & 0x3FFFF) >> 4) | ((lbo >> 4) << 16); }
__device__ __forceinline__ uint64_t desc64(uint32_t lo) { uint64_t r; asm("mov.b64 %0, {%1, %2};" : "=l"(r) : "r"(lo), "r"(0x40000040u)); return r; }
__device__ __forceinline__ void bar_sync(int id, int n) { asm volatile("bar.sync %0, %1;" :: "r"(id), "r"(n) : "memory"); }
__device__ __forceinline__ uint32_t pack_bf16(float lo, float hi) { uint32_t r; asm("cvt.rn.bf16x2.f32 %0, %1, %2;" : "=r"(r) : "f"(hi), "f"(lo)); return r; }
__device__ __forceinline__ float bf_lo(uint32_t v) { return __uint_as_float(v << 16); }
__device__ __forceinline__ float bf_hi(uint32_t v) { return __uint_as_float(v & 0xffff0000u); }
__device__ __forceinline__ float ex2(float x) { float r; asm("ex2.approx.ftz.f32 %0, %1;" : "=f"(r) : "f"(x)); return r; }
__device__ __forceinline__ float rcp(float x) { float r; asm("rcp.approx.ftz.f32 %0, %1;" : "=f"(r) : "f"(x)); return r; }
__device__ __forceinline__ void stsm4(uint32_t a, uint32_t r0, uint32_t r1, uint32_t r2, uint32_t r3) {
  asm volatile("stmatrix.sync.aligned.m8n8.x4.shared.b16 [%0], {%1, %2, %3, %4};" :: "r"(a), "r"(r0), "r"(r1), "r"(r2), "r"(r3) : "memory");
}
__device__ __forceinline__ void ldsm4(uint32_t a, uint32_t& r0, uint32_t& r1, uint32_t& r2, uint32_t& r3) {
  asm volatile("ldmatrix.sync.aligned.m8n8.x4.shared.b16 {%0, %1, %2, %3}, [%4];" : "=r"(r0), "=r"(r1), "=r"(r2), "=r"(r3) : "r"(a) : "memory");
}
__device__ __forceinline__ uint32_t movm(uint32_t v) { uint32_t r; asm volatile("movmatrix.sync.aligned.m8n8.trans.b16 %0, %1;" : "=r"(r) : "r"(v)); return r; }
__device__ __forceinline__ void sts128(uint32_t a, uint32_t r0, uint32_t r1, uint32_t r2, uint32_t r3) {
  asm volatile("st.shared.v4.b32 [%0], {%1, %2, %3, %4};" :: "r"(a), "r"(r0), "r"(r1), "r"(r2), "r"(r3) : "memory");
}
__device__ __forceinline__ void lds128(uint32_t a, uint32_t& r0, uint32_t& r1, uint32_t& r2, uint32_t& r3) {
  asm volatile("ld.shared.v4.b32 {%0, %1, %2, %3}, [%4];" : "=r"(r0), "=r"(r1), "=r"(r2), "=r"(r3) : "r"(a) : "memory");
}
__device__ __forceinline__ uint32_t add_bf16x2(uint32_t a, uint32_t b) { uint32_t r; asm("add.rn.bf16x2 %0, %1, %2;" : "=r"(r) : "r"(a), "r"(b)); return r; }
__device__ __forceinline__ void sts32f(uint32_t a, float v) { asm volatile("st.shared.f32 [%0], %1;" :: "r"(a), "f"(v) : "memory"); }
__device__ __forceinline__ void mma16816(float (&d)[4], uint32_t a0, uint32_t a1, uint32_t a2, uint32_t a3, uint32_t b0, uint32_t b1, const float (&c)[4]) {
  asm("mma.sync.aligned.m16n8k16.row.col.f32.bf16.bf16.f32 {%0, %1, %2, %3}, {%4, %5, %6, %7}, {%8, %9}, {%10, %11, %12, %13};"
      : "=f"(d[0]), "=f"(d[1]), "=f"(d[2]), "=f"(d[3]) : "r"(a0), "r"(a1), "r"(a2), "r"(a3), "r"(b0), "r"(b1), "f"(c[0]), "f"(c[1]), "f"(c[2]), "f"(c[3]));
}
__device__ __forceinline__ void mma1688(float (&d)[4], uint32_t a0, uint32_t a1, uint32_t b0, const float (&c)[4]) {
  asm("mma.sync.aligned.m16n8k8.row.col.f32.bf16.bf16.f32 {%0, %1, %2, %3}, {%4, %5}, {%6}, {%7, %8, %9, %10};"
      : "=f"(d[0]), "=f"(d[1]), "=f"(d[2]), "=f"(d[3]) : "r"(a0), "r"(a1), "r"(b0), "f"(c[0]), "f"(c[1]), "f"(c[2]), "f"(c[3]));
}
__device__ __forceinline__ void mma16816z(float (&d)[4], uint32_t a0, uint32_t a1, uint32_t a2, uint32_t a3, uint32_t b0, uint32_t b1) {
  asm("mma.sync.aligned.m16n8k16.row.col.f32.bf16.bf16.f32 {%0, %1, %2, %3}, {%4, %5, %6, %7}, {%8, %9}, {0f00000000, 0f00000000, 0f00000000, 0f00000000};"
      : "=f"(d[0]), "=f"(d[1]), "=f"(d[2]), "=f"(d[3]) : "r"(a0), "r"(a1), "r"(a2), "r"(a3), "r"(b0), "r"(b1));
}
__device__ __forceinline__ void mma1688z(float (&d)[4], uint32_t a0, uint32_t a1, uint32_t b0) {
  asm("mma.sync.aligned.m16n8k8.row.col.f32.bf16.bf16.f32 {%0, %1, %2, %3}, {%4, %5}, {%6}, {0f00000000, 0f00000000, 0f00000000, 0f00000000};"
      : "=f"(d[0]), "=f"(d[1]), "=f"(d[2]), "=f"(d[3]) : "r"(a0), "r"(a1), "r"(b0));
}
__device__ __forceinline__ uint32_t bar_sync_zero(int id, int n) {
  uint32_t r;
  asm volatile("{\n.reg .pred p;\nsetp.eq.u32 p, %1, 0;\nbarrier.cta.red.popc.aligned.u32 %0, %1, %2, p;\n}" : "=r"(r) : "r"(id), "r"(n) : "memory");
  return r;
}
__device__ __forceinline__ uint32_t late_zero(uint32_t zm) { uint32_t c; asm volatile("mov.u32 %0, %%clock;" : "=r"(c) :: "memory"); return c & zm; }
__device__ __forceinline__ void st_b128(uint4* p, uint32_t a, uint32_t b, uint32_t c, uint32_t d) {
  asm volatile("{\n.reg .b128 t;\n.reg .b64 lo, hi;\nmov.b64 lo, {%0, %1};\nmov.b64 hi, {%2, %3};\nmov.b128 t, {lo, hi};\nst.relaxed.gpu.global.b128 [%4], t;\n}"
               :: "r"(a), "r"(b), "r"(c), "r"(d), "l"(p) : "memory");
}
__device__ __forceinline__ uint32_t pkt_head(uint32_t a) { return a ? a : 0x8000u; }
__device__ __forceinline__ void gen_store(uint4* p, uint32_t a, uint32_t b, uint32_t c, uint32_t d) {
  asm volatile("{\n.reg .b128 t;\n.reg .b64 lo, hi;\nmov.b64 lo, {%0, %1};\nmov.b64 hi, {%2, %3};\nmov.b128 t, {lo, hi};\nst.relaxed.gpu.b128 [%4], t;\n}"
               :: "r"(a), "r"(b), "r"(c), "r"(d), "l"(p) : "memory");
}
__device__ __forceinline__ void gen_load(const uint4* p, uint32_t* v) {
  asm volatile("{\n.reg .b128 t;\n.reg .b64 lo, hi;\nld.relaxed.gpu.b128 t, [%4];\nmov.b128 {lo, hi}, t;\nmov.b64 {%0, %1}, lo;\nmov.b64 {%2, %3}, hi;\n}"
               : "=r"(v[0]), "=r"(v[1]), "=r"(v[2]), "=r"(v[3]) : "l"(p) : "memory");
}
__device__ __forceinline__ void pkt_load(const uint4* p, uint32_t* v) {
  asm volatile("{\n.reg .b128 t;\n.reg .b64 lo, hi;\nld.relaxed.gpu.global.b128 t, [%4];\nmov.b128 {lo, hi}, t;\nmov.b64 {%0, %1}, lo;\nmov.b64 {%2, %3}, hi;\n}"
               : "=r"(v[0]), "=r"(v[1]), "=r"(v[2]), "=r"(v[3]) : "l"(p) : "memory");
}
__device__ __forceinline__ uint32_t ld_relaxed(const uint32_t* p) { uint32_t v; asm volatile("ld.relaxed.gpu.global.u32 %0, [%1];" : "=r"(v) : "l"(p) : "memory"); return v; }
__device__ __forceinline__ uint4 ld_relaxed4(const void* p) { uint4 v; asm volatile("ld.relaxed.gpu.global.v4.u32 {%0, %1, %2, %3}, [%4];" : "=r"(v.x), "=r"(v.y), "=r"(v.z), "=r"(v.w) : "l"(p) : "memory"); return v; }
__device__ __forceinline__ void st_relaxed(uint32_t* p, uint32_t v) { asm volatile("st.relaxed.gpu.global.u32 [%0], %1;" :: "l"(p), "r"(v) : "memory"); }
__device__ __forceinline__ void st_relaxed2(void* p, uint32_t a, uint32_t b) { asm volatile("st.relaxed.gpu.global.v2.u32 [%0], {%1, %2};" :: "l"(p), "r"(a), "r"(b) : "memory"); }
__device__ __forceinline__ void red_release(uint32_t* p, uint32_t v) { asm volatile("red.release.gpu.global.add.u32 [%0], %1;" :: "l"(p), "r"(v) : "memory"); }
__device__ __forceinline__ uint32_t tagf(float v, uint32_t tag) { return (__float_as_uint(v) & ~15u) | (tag & 15u); }
__device__ __forceinline__ bool tag_ok4(const uint4& v, uint32_t tag) { return (((v.x ^ tag) | (v.y ^ tag) | (v.z ^ tag) | (v.w ^ tag)) & 15u) == 0; }
__device__ __forceinline__ float untag(uint32_t v) { return __uint_as_float(v & ~15u); }
template <typename T> __device__ __forceinline__ T* ptr_add(T* p, uint32_t bytes) {
  uint64_t r;
  asm("{\n.reg .u32 lo, hi;\nmov.b64 {lo, hi}, %1;\nadd.cc.u32 lo, lo, %2;\naddc.u32 hi, hi, 0;\nmov.b64 %0, {lo, hi};\n}" : "=l"(r) : "l"(p), "r"(bytes));
  return (T*)r;
}
#define TL(who, slot) do {} while (0)
#define TLC(slot) do {} while (0)
#define TLE(slot) do {} while (0)
#define ST(who, n) do {} while (0)
#define AP(i) do {} while (0)
#define SP(v) do {} while (0)
#define TLG(slot) do {} while (0)
#define STA() do {} while (0)
#define STB(n) do {} while (0)

__device__ __forceinline__ void wgmma_n128(float (&d)[64], uint64_t da, uint64_t db, int scale_d) {
  asm volatile("{\n.reg .pred p;\nsetp.ne.b32 p, %66, 0;\n"
    "wgmma.mma_async.sync.aligned.m64n128k16.f32.bf16.bf16 "
    "{%0, %1, %2, %3, %4, %5, %6, %7, %8, %9, %10, %11, %12, %13, %14, %15, "
    "%16, %17, %18, %19, %20, %21, %22, %23, %24, %25, %26, %27, %28, %29, %30, %31, "
    "%32, %33, %34, %35, %36, %37, %38, %39, %40, %41, %42, %43, %44, %45, %46, %47, "
    "%48, %49, %50, %51, %52, %53, %54, %55, %56, %57, %58, %59, %60, %61, %62, %63}, "
    "%64, %65, p, 1, 1, 0, 1;\n}\n"
    : "+f"(d[0]), "+f"(d[1]), "+f"(d[2]), "+f"(d[3]), "+f"(d[4]), "+f"(d[5]), "+f"(d[6]), "+f"(d[7]),
      "+f"(d[8]), "+f"(d[9]), "+f"(d[10]), "+f"(d[11]), "+f"(d[12]), "+f"(d[13]), "+f"(d[14]), "+f"(d[15]),
      "+f"(d[16]), "+f"(d[17]), "+f"(d[18]), "+f"(d[19]), "+f"(d[20]), "+f"(d[21]), "+f"(d[22]), "+f"(d[23]),
      "+f"(d[24]), "+f"(d[25]), "+f"(d[26]), "+f"(d[27]), "+f"(d[28]), "+f"(d[29]), "+f"(d[30]), "+f"(d[31]),
      "+f"(d[32]), "+f"(d[33]), "+f"(d[34]), "+f"(d[35]), "+f"(d[36]), "+f"(d[37]), "+f"(d[38]), "+f"(d[39]),
      "+f"(d[40]), "+f"(d[41]), "+f"(d[42]), "+f"(d[43]), "+f"(d[44]), "+f"(d[45]), "+f"(d[46]), "+f"(d[47]),
      "+f"(d[48]), "+f"(d[49]), "+f"(d[50]), "+f"(d[51]), "+f"(d[52]), "+f"(d[53]), "+f"(d[54]), "+f"(d[55]),
      "+f"(d[56]), "+f"(d[57]), "+f"(d[58]), "+f"(d[59]), "+f"(d[60]), "+f"(d[61]), "+f"(d[62]), "+f"(d[63])
    : "l"(da), "l"(db), "r"(scale_d));
}
__device__ __forceinline__ void wgmma_n256(float (&d)[128], uint64_t da, uint64_t db, int scale_d) {
  asm volatile("{\n.reg .pred p;\nsetp.ne.b32 p, %130, 0;\n"
    "wgmma.mma_async.sync.aligned.m64n256k16.f32.bf16.bf16 "
    "{%0, %1, %2, %3, %4, %5, %6, %7, %8, %9, %10, %11, %12, %13, %14, %15, "
    "%16, %17, %18, %19, %20, %21, %22, %23, %24, %25, %26, %27, %28, %29, %30, %31, "
    "%32, %33, %34, %35, %36, %37, %38, %39, %40, %41, %42, %43, %44, %45, %46, %47, "
    "%48, %49, %50, %51, %52, %53, %54, %55, %56, %57, %58, %59, %60, %61, %62, %63, "
    "%64, %65, %66, %67, %68, %69, %70, %71, %72, %73, %74, %75, %76, %77, %78, %79, "
    "%80, %81, %82, %83, %84, %85, %86, %87, %88, %89, %90, %91, %92, %93, %94, %95, "
    "%96, %97, %98, %99, %100, %101, %102, %103, %104, %105, %106, %107, %108, %109, %110, %111, "
    "%112, %113, %114, %115, %116, %117, %118, %119, %120, %121, %122, %123, %124, %125, %126, %127}, "
    "%128, %129, p, 1, 1, 0, 1;\n}\n"
    : "+f"(d[0]), "+f"(d[1]), "+f"(d[2]), "+f"(d[3]), "+f"(d[4]), "+f"(d[5]), "+f"(d[6]), "+f"(d[7]),
      "+f"(d[8]), "+f"(d[9]), "+f"(d[10]), "+f"(d[11]), "+f"(d[12]), "+f"(d[13]), "+f"(d[14]), "+f"(d[15]),
      "+f"(d[16]), "+f"(d[17]), "+f"(d[18]), "+f"(d[19]), "+f"(d[20]), "+f"(d[21]), "+f"(d[22]), "+f"(d[23]),
      "+f"(d[24]), "+f"(d[25]), "+f"(d[26]), "+f"(d[27]), "+f"(d[28]), "+f"(d[29]), "+f"(d[30]), "+f"(d[31]),
      "+f"(d[32]), "+f"(d[33]), "+f"(d[34]), "+f"(d[35]), "+f"(d[36]), "+f"(d[37]), "+f"(d[38]), "+f"(d[39]),
      "+f"(d[40]), "+f"(d[41]), "+f"(d[42]), "+f"(d[43]), "+f"(d[44]), "+f"(d[45]), "+f"(d[46]), "+f"(d[47]),
      "+f"(d[48]), "+f"(d[49]), "+f"(d[50]), "+f"(d[51]), "+f"(d[52]), "+f"(d[53]), "+f"(d[54]), "+f"(d[55]),
      "+f"(d[56]), "+f"(d[57]), "+f"(d[58]), "+f"(d[59]), "+f"(d[60]), "+f"(d[61]), "+f"(d[62]), "+f"(d[63]),
      "+f"(d[64]), "+f"(d[65]), "+f"(d[66]), "+f"(d[67]), "+f"(d[68]), "+f"(d[69]), "+f"(d[70]), "+f"(d[71]),
      "+f"(d[72]), "+f"(d[73]), "+f"(d[74]), "+f"(d[75]), "+f"(d[76]), "+f"(d[77]), "+f"(d[78]), "+f"(d[79]),
      "+f"(d[80]), "+f"(d[81]), "+f"(d[82]), "+f"(d[83]), "+f"(d[84]), "+f"(d[85]), "+f"(d[86]), "+f"(d[87]),
      "+f"(d[88]), "+f"(d[89]), "+f"(d[90]), "+f"(d[91]), "+f"(d[92]), "+f"(d[93]), "+f"(d[94]), "+f"(d[95]),
      "+f"(d[96]), "+f"(d[97]), "+f"(d[98]), "+f"(d[99]), "+f"(d[100]), "+f"(d[101]), "+f"(d[102]), "+f"(d[103]),
      "+f"(d[104]), "+f"(d[105]), "+f"(d[106]), "+f"(d[107]), "+f"(d[108]), "+f"(d[109]), "+f"(d[110]), "+f"(d[111]),
      "+f"(d[112]), "+f"(d[113]), "+f"(d[114]), "+f"(d[115]), "+f"(d[116]), "+f"(d[117]), "+f"(d[118]), "+f"(d[119]),
      "+f"(d[120]), "+f"(d[121]), "+f"(d[122]), "+f"(d[123]), "+f"(d[124]), "+f"(d[125]), "+f"(d[126]), "+f"(d[127])
    : "l"(da), "l"(db), "r"(scale_d));
}
__device__ __forceinline__ void wgmma_rs_n128(float (&d)[64], const uint32_t* a, uint64_t db, int scale_d) {
  asm volatile("{\n.reg .pred p;\nsetp.ne.b32 p, %69, 0;\n"
    "wgmma.mma_async.sync.aligned.m64n128k16.f32.bf16.bf16 "
    "{%0, %1, %2, %3, %4, %5, %6, %7, %8, %9, %10, %11, %12, %13, %14, %15, "
    "%16, %17, %18, %19, %20, %21, %22, %23, %24, %25, %26, %27, %28, %29, %30, %31, "
    "%32, %33, %34, %35, %36, %37, %38, %39, %40, %41, %42, %43, %44, %45, %46, %47, "
    "%48, %49, %50, %51, %52, %53, %54, %55, %56, %57, %58, %59, %60, %61, %62, %63}, "
    "{%64, %65, %66, %67}, %68, p, 1, 1, 1;\n}\n"
    : "+f"(d[0]), "+f"(d[1]), "+f"(d[2]), "+f"(d[3]), "+f"(d[4]), "+f"(d[5]), "+f"(d[6]), "+f"(d[7]),
      "+f"(d[8]), "+f"(d[9]), "+f"(d[10]), "+f"(d[11]), "+f"(d[12]), "+f"(d[13]), "+f"(d[14]), "+f"(d[15]),
      "+f"(d[16]), "+f"(d[17]), "+f"(d[18]), "+f"(d[19]), "+f"(d[20]), "+f"(d[21]), "+f"(d[22]), "+f"(d[23]),
      "+f"(d[24]), "+f"(d[25]), "+f"(d[26]), "+f"(d[27]), "+f"(d[28]), "+f"(d[29]), "+f"(d[30]), "+f"(d[31]),
      "+f"(d[32]), "+f"(d[33]), "+f"(d[34]), "+f"(d[35]), "+f"(d[36]), "+f"(d[37]), "+f"(d[38]), "+f"(d[39]),
      "+f"(d[40]), "+f"(d[41]), "+f"(d[42]), "+f"(d[43]), "+f"(d[44]), "+f"(d[45]), "+f"(d[46]), "+f"(d[47]),
      "+f"(d[48]), "+f"(d[49]), "+f"(d[50]), "+f"(d[51]), "+f"(d[52]), "+f"(d[53]), "+f"(d[54]), "+f"(d[55]),
      "+f"(d[56]), "+f"(d[57]), "+f"(d[58]), "+f"(d[59]), "+f"(d[60]), "+f"(d[61]), "+f"(d[62]), "+f"(d[63])
    : "r"(a[0]), "r"(a[1]), "r"(a[2]), "r"(a[3]), "l"(db), "r"(scale_d));
}
__device__ __forceinline__ void wgmma_n64(float* d, uint64_t da, uint64_t db, int scale_d) {
  asm volatile("{\n.reg .pred p;\nsetp.ne.b32 p, %34, 0;\n"
    "wgmma.mma_async.sync.aligned.m64n64k16.f32.bf16.bf16 "
    "{%0, %1, %2, %3, %4, %5, %6, %7, %8, %9, %10, %11, %12, %13, %14, %15, "
    "%16, %17, %18, %19, %20, %21, %22, %23, %24, %25, %26, %27, %28, %29, %30, %31}, "
    "%32, %33, p, 1, 1, 0, 1;\n}\n"
    : "+f"(d[0]), "+f"(d[1]), "+f"(d[2]), "+f"(d[3]), "+f"(d[4]), "+f"(d[5]), "+f"(d[6]), "+f"(d[7]),
      "+f"(d[8]), "+f"(d[9]), "+f"(d[10]), "+f"(d[11]), "+f"(d[12]), "+f"(d[13]), "+f"(d[14]), "+f"(d[15]),
      "+f"(d[16]), "+f"(d[17]), "+f"(d[18]), "+f"(d[19]), "+f"(d[20]), "+f"(d[21]), "+f"(d[22]), "+f"(d[23]),
      "+f"(d[24]), "+f"(d[25]), "+f"(d[26]), "+f"(d[27]), "+f"(d[28]), "+f"(d[29]), "+f"(d[30]), "+f"(d[31])
    : "l"(da), "l"(db), "r"(scale_d));
}
__device__ __forceinline__ void wgmma_rs_n64(float* d, const uint32_t* a, uint64_t db, int scale_d) {
  asm volatile("{\n.reg .pred p;\nsetp.ne.b32 p, %37, 0;\n"
    "wgmma.mma_async.sync.aligned.m64n64k16.f32.bf16.bf16 "
    "{%0, %1, %2, %3, %4, %5, %6, %7, %8, %9, %10, %11, %12, %13, %14, %15, "
    "%16, %17, %18, %19, %20, %21, %22, %23, %24, %25, %26, %27, %28, %29, %30, %31}, "
    "{%32, %33, %34, %35}, %36, p, 1, 1, 1;\n}\n"
    : "+f"(d[0]), "+f"(d[1]), "+f"(d[2]), "+f"(d[3]), "+f"(d[4]), "+f"(d[5]), "+f"(d[6]), "+f"(d[7]),
      "+f"(d[8]), "+f"(d[9]), "+f"(d[10]), "+f"(d[11]), "+f"(d[12]), "+f"(d[13]), "+f"(d[14]), "+f"(d[15]),
      "+f"(d[16]), "+f"(d[17]), "+f"(d[18]), "+f"(d[19]), "+f"(d[20]), "+f"(d[21]), "+f"(d[22]), "+f"(d[23]),
      "+f"(d[24]), "+f"(d[25]), "+f"(d[26]), "+f"(d[27]), "+f"(d[28]), "+f"(d[29]), "+f"(d[30]), "+f"(d[31])
    : "r"(a[0]), "r"(a[1]), "r"(a[2]), "r"(a[3]), "l"(db), "r"(scale_d));
}

template <int BN> __device__ __forceinline__ void wgmma(float (&d)[BN / 2], uint64_t a, uint64_t b, int s) {
  if constexpr (BN == 128) wgmma_n128(d, a, b, s);
  else wgmma_n256(d, a, b, s);
}

template <int N> __device__ __forceinline__ void acc_fence(float* a) {
#pragma unroll
  for (int i = 0; i < N; i++) asm volatile("" : "+f"(a[i]) :: "memory");
}

#define SELECT8(a, f) do { \
  if ((a) & 4) { if ((a) & 2) { if ((a) & 1) f(7); else f(6); } else { if ((a) & 1) f(5); else f(4); } } \
  else { if ((a) & 2) { if ((a) & 1) f(3); else f(2); } else { if ((a) & 1) f(1); else f(0); } } } while (0)
__device__ __forceinline__ uint32_t lane_now() { uint32_t l; asm volatile("mov.u32 %0, %%laneid;" : "=r"(l)); return l; }

struct Prod {
  uint32_t sb, n, tail, addr, pat, ready;
  uint32_t rank, flip; uint16_t mask;
  __device__ __forceinline__ void load_b(uint32_t dst, uint32_t half, const CUtensorMap* m, uint32_t mstep, uint32_t fb, int k, int ch, int cstep) {
    uint32_t h = rank;
    do { tma_ld3_mc(dst + h * half, ptr_add(m, h * mstep), fb, 0, k * 64, ch + h * cstep, mask); h ^= flip; } while (h != rank);
  }
  __device__ __forceinline__ void load_wide(const Params& P, int ffn, uint32_t dst, uint32_t fb, int k, int ch) {
    load_b(dst, PAGE, &P.map[ffn ? M_W1 : M_WKV], ffn ? 128 : 0, fb, k, ffn ? ch : ch + 16, ffn ? 0 : 16);
  }
  __device__ __forceinline__ void load_narrow(const Params& P, int ffn, uint32_t dst, uint32_t fb, int k, int j) {
    load_b(dst, 8192, &P.map[ffn ? M_W1H : M_WQ], ffn ? 128 : 0, fb, k, ffn ? 48 + j : 2 * j, ffn ? 0 : 1);
  }
  __device__ __forceinline__ void finish() {
#pragma unroll 1
    for (; tail < n; tail++) mbar_wait(sb + BAR_EMPTY + ((tail & 7) << 3), (tail >> 3) & 1);
  }
  template <int PAGES> __device__ __forceinline__ uint32_t acquire(uint32_t& fb) { return acquire_n(PAGES, fb); }
  __device__ __forceinline__ uint32_t acquire_n(uint32_t PAGES, uint32_t& fb) {
    uint32_t nw = pat & 3; pat = (pat >> 2) | 0x40000000u;
#pragma unroll 1
    for (; nw; nw--) { mbar_wait(sb + BAR_EMPTY + ((tail & 7) << 3), (tail >> 3) & 1); tail++; }
    ST(4, n);
    fb = sb + BAR_FULL + ((n & 7) << 3);
    mbar_expect_tx(fb, PAGES * PAGE);
    const uint32_t a = sb + addr;
    addr += PAGES * PAGE; if (addr >= NPAGE * PAGE) addr = 0;
    n++;
    return a;
  }
  const uint32_t* flag; uint32_t base, seen;
  __device__ __forceinline__ void acquire_fence() { asm volatile("fence.acquire.gpu;" ::: "memory"); fence_async_global(); }
  __device__ __forceinline__ void next() {
    uint32_t v, spins = 0;
    seen++;
    do { asm volatile("ld.acquire.cta.shared.u32 %0, [%1];" : "=r"(v) : "r"(sb + SM_SEEN) : "memory"); spin_check(++spins >> 4); } while (v < seen);
    fence_async_global();
  }
  __device__ __forceinline__ void need(uint32_t mask) {
    if ((ready & mask) != mask) {
      uint32_t spins = 0;
      do { ready = ld_relaxed(flag) - base; spin_check(++spins); } while ((ready & mask) != mask);
      acquire_fence();
    }
    ST(5, n - 1);
  }
};

struct Cons {
  uint32_t sb, n, off, prev;
  uint32_t ebar;
  uint32_t da0, db0;
  int lane;
  template <int PAGES> __device__ __forceinline__ void advance() {
    n++; off += PAGES << 10; if (off >= (NPAGE << 10)) off = 0;
    asm volatile("" : "+r"(n), "+r"(off));
  }
  template <int BN, int PAGES> __device__ __forceinline__ void step_ab(float (&acc)[BN / 2], uint32_t da, uint32_t db, int accumulate) {
    STA();
    mbar_wait_fast(sb + BAR_FULL + ((n & 7) << 3), (n >> 3) & 1);
    STB(n);
    const uint64_t da64 = desc64(da), db64 = desc64(db);
    wgmma_fence();
#pragma unroll
    for (int k = 0; k < 4; k++) wgmma<BN>(acc, da64 + 2 * k, db64 + 128 * k, k ? 1 : accumulate);
    wgmma_commit();
    wgmma_wait<1>();
    if (prev && lane < 2) mbar_arrive_cluster(ebar + prev);
    prev = 64 + ((n & 7) << 3);
    advance<PAGES>();
  }
  template <int BN> __device__ __forceinline__ void step(float (&acc)[BN / 2], int accumulate = 1) { step_ab<BN, BN / 128 + 1>(acc, da0 + off, db0 + 1024 + off, accumulate); }
  template <int BN> __device__ __forceinline__ void step_own(float (&acc)[BN / 2], uint32_t da, int accumulate) { step_ab<BN, BN / 128>(acc, da, db0 + off, accumulate); }
  __device__ __forceinline__ void wait_full(uint32_t i) { mbar_wait_fast(sb + BAR_FULL + (((n + i) & 7) << 3), ((n + i) >> 3) & 1); }
  template <int I, int N> __device__ __forceinline__ void issue_rs(float (&acc)[64], uint32_t (&a)[16], int accumulate = 1) {
    if (I == 0) { STA(); STB(n); }
    const uint64_t db64 = desc64(db0 + off) + 1024 * I;
    wgmma_fence();
#pragma unroll
    for (int k = 0; k < 4; k++) wgmma_rs_n128(acc, a + 4 * k, db64 + 128 * k, k ? 1 : accumulate);
    if (I == N - 1) {
      wgmma_commit();
      prev = 64 + ((n & 7) << 3);
      advance<N>();
    }
  }
  template <int BN> __device__ __forceinline__ void steps(float (&acc)[BN / 2], int cnt) {
#pragma unroll 1
    do { step<BN>(acc); } while (--cnt > 0);
  }
  __device__ __forceinline__ void steps_skip(float (&acc)[64], int at) {
    int i = 0;
#pragma unroll 1
    do { if (i == at) off += 2 << 10; step<128>(acc); } while (++i < 2);
  }
  __device__ __forceinline__ void drain() {
    wgmma_wait<0>();
    if (lane < 2) mbar_arrive_cluster(ebar + prev);
    prev = 0;
  }
};

#define MAPPING 2
__device__ __forceinline__ uint32_t role_of_sm(uint32_t smid) {
  const uint32_t t = smid >> 1;
  uint32_t q, i;
  if (t < 32) { q = t & 7; i = t >> 3; }
  else if (t < 60) { const uint32_t u = t - 32, d = (u * 37) >> 8; q = 1 + u - d * 7; i = 4 + d; }
  else if (t < 62) return 128 + smid - 120;
  else { q = 0; i = t - 58; }
  return (q * 2 + (smid & 1)) * 8 + i;
}

template <typename T> __device__ __forceinline__ T* scratch(const Params& P, uint32_t off) { return (T*)ptr_add(P.scratch, off); }
__device__ __forceinline__ uint32_t* epoch_ptr(const Params& P) { uint32_t b; asm volatile("mov.u32 %0, %%ctaid.x;" : "=r"(b)); return scratch<uint32_t>(P, G_EPOCH + b * 4u); }

__device__ __forceinline__ int o_chunk(int s, int j) { const int hf = s >= 9, m = s - 2 - 7 * hf; return s < 2 ? 2 * j + s : 2 * (m == j ? 7 : m) + hf; }

__global__ void __cluster_dims__(2, 1, 1) __launch_bounds__(384, 1) fused_kernel(const __grid_constant__ Params P) {
  extern __shared__ __align__(1024) uint8_t smem_raw[];
  SP(0);
  const uint32_t sb = __shfl_sync(0xffffffffu, smem_u32(smem_raw), 0);
  const int warp = __shfl_sync(0xffffffffu, threadIdx.x >> 5, 0);
  const int lane = threadIdx.x & 31;
  if (warp == 7 && elect_one()) { prefetch_map(&P.map[M_XIN64]); prefetch_map(&P.map[M_WKV]); prefetch_map(&P.map[M_XIN]); }
  uint32_t role = blockIdx.x < 128 ? ((blockIdx.x >> 4) * 2 + (blockIdx.x & 1)) * 8 + ((blockIdx.x >> 1) & 7) : blockIdx.x;
  if (P.use_smid) { uint32_t smid; asm volatile("mov.u32 %0, %%smid;" : "=r"(smid)); role = role_of_sm(smid); }
  const bool spare = role >= 128;
  const int g = role >> 3, j = role & 7;
  uint32_t rank; asm("mov.u32 %0, %%cluster_ctarank;" : "=r"(rank));
  auto shared_b = [&]() {
    uint32_t peer;
    asm volatile("ld.shared::cluster.u32 %0, [%1];" : "=r"(peer) : "r"(mapa(sb + SM_ROLE, rank ^ 1)) : "memory");
    return !spare && peer < 128 && (peer & 7) == (uint32_t)j;
  };
  SP(1);

  if (warp >= 8) {
    asm volatile("setmaxnreg.dec.sync.aligned.u32 40;");
    if (elect_one()) {
      if (warp == 8) {
#pragma unroll
        for (int i = 0; i < 6; i++) mbar_init(sb + BAR_FULL + 8 * i, 1);
        mbar_init(sb + BAR_XIN, 1);
      } else if (warp == 9) {
#pragma unroll
        for (int i = 0; i < 8; i++) mbar_init(sb + BAR_EMPTY + 8 * i, 16);
      } else if (warp == 10) {
#pragma unroll
        for (int i = 0; i < 4; i++) mbar_init(sb + BAR_SFULL + 8 * i, 4);
        mbar_init(sb + BAR_CLR, 1); mbar_init(sb + BAR_FULL + 48, 1); mbar_init(sb + BAR_FULL + 56, 1);
      } else {
        sts128(sb + SM_ROLE, role, 0, 0, 0);
        mbar_init(sb + BAR_TAG, 1); mbar_init(sb + BAR_XFULL, 8); mbar_init(sb + BAR_CSE, 8);
        mbar_init(sb + BAR_SEMPTY, 1); mbar_init(sb + BAR_CSF, 1); mbar_init(sb + BAR_CSF + 8, 2);
      }
      asm volatile("fence.mbarrier_init.release.cluster;\nfence.release.sync_restrict::shared::cta.cluster;" ::: "memory");
      fence_async_smem();
    }
    __syncwarp();
    SP(2);
    asm volatile("barrier.cluster.arrive.relaxed.aligned;" ::: "memory");
    if (warp == 8 && !spare) {
      if (elect_one()) {
        const int par = g & 1, row = (g >> 1) * 128;
        mbar_arrive(sb + BAR_FULL);
        {
          const int s = 1;
          const uint32_t xb = sb + BAR_XIN, fb = sb + BAR_FULL + 8;
          mbar_expect_tx(xb, PAGE); mbar_expect_tx(fb, 2 * PAGE);
#pragma unroll
          for (int h = 0; h < 2; h++) tma_ld3(sb + SM_STAGE + h * PAGE + s * 8192, &P.map[M_XIN64], xb, s * 64, par, row + h * 64);
#pragma unroll
          for (int h = 0; h < 2; h++) tma_ld3(sb + (2 * s + h) * PAGE, &P.map[M_WKV], fb, 0, s * 64, 16 + 16 * h + 2 * j);
        }
#pragma unroll 1
        for (int s = 0; s < 2; s++) {
          const uint32_t fb = sb + BAR_FULL + 16 + 8 * s;
          mbar_expect_tx(fb, PAGE);
          tma_ld3(sb + (4 + s) * PAGE, &P.map[M_WKV], fb, 0, s * 64, 2 * j);
        }
#pragma unroll 1
        for (int s = 0; s < 2; s++) {
          const uint32_t fb = sb + BAR_FULL + 32 + 8 * s, a = sb + (6 + 3 * s) * PAGE;
          const int k = (j == 1 ? 4 : 2) + s;
          mbar_expect_tx(fb, 3 * PAGE);
          tma_ld3(a, &P.map[M_XIN], fb, k * 64, par, row);
#pragma unroll
          for (int h = 0; h < 2; h++) tma_ld3(a + PAGE + h * PAGE, &P.map[M_WKV], fb, 0, k * 64, 16 + 16 * h + 2 * j);
        }
        spin_check((sb & 1023) << 22);
      }
      __syncwarp();
    }
    SP(3);
    asm volatile("barrier.cluster.wait.acquire.aligned;" ::: "memory");
    SP(4);
    if (warp == 8) {
      if (elect_one()) {
        Prod p; p.sb = sb; p.n = 0; p.tail = 0; p.ready = 0; p.addr = 0;
        { const bool mc = shared_b(); p.rank = rank; p.flip = !mc; p.mask = mc ? 3 : 1 << rank; }
        uint32_t fb;
        if (spare) {
          p.pat = 0x55555000u;
#pragma unroll 1
          for (int r = -1; r < 7; r++) {
            const int ch = r < 0 ? 4 * j : ((r < 2 ? r : r == 2 ? 6 : r - 1) * 4 + j) * 2;
#pragma unroll 1
            for (int k = 0; k < 16; k++) { const uint32_t a = p.acquire<2>(fb); p.load_b(a, PAGE, &P.map[r < 0 ? M_WKV : M_W1], r < 0 ? 0 : 128, fb, k, ch, r < 0 ? 2 : 0); }
          }
        } else {
          p.seen = 0;
          const int xpar = g & 1, xrow = (g >> 1) * 128;
          SP(5);
#pragma unroll 1
          for (int hl = 0; hl < 4; hl++) {
            const int ffn = hl & 1;
            const CUtensorMap* xmap = &P.map[hl ? M_OUT_LD : M_XIN];
            if (hl) {
              p.pat = ffn ? Pat<3>::v : Pat<8>::v;
#pragma unroll 1
              for (int s = 0; s < 2; s++) { const uint32_t a = p.acquire<2>(fb); p.load_wide(P, ffn, a, fb, 2 * j + s, 2 * j); }
#pragma unroll 1
              for (int s = 0; s < 2; s++) { const uint32_t a = p.acquire<1>(fb); p.load_narrow(P, ffn, a, fb, 2 * j + s, j); }
            } else { p.pat = (Pat<0>::v >> 12) | 0x55500000u; p.addr = 0; p.n = 6; }
            if (hl == 0) SP(6);
            uint32_t fb0 = 0;
#pragma unroll 1
            for (int m = hl ? 0 : 2; m < 14; m++) {
              const int hf = m >= 7, mm = m - 7 * hf, jj = mm == j ? 7 : mm;
              int k = 2 * jj + hf;
              if (hl == 0) {
                const int pr = (m >> 1) + 1;
                k = 2 * (j && pr == 2 ? j : pr == j ? 2 : pr) + (m & 1);
              }
              const uint32_t a = p.acquire<3>(fb);
              p.load_wide(P, ffn, a + PAGE, fb, k, 2 * j);
              if (hl) {
                if (m == 0) { fb0 = fb; continue; }
                if (m == 1) {
                  const int j0 = j ? 0 : 7;
                  p.flag = scratch<uint32_t>(P, g * G_BLOCK + G_FLAGS + (ffn ? (hl >> 1) * EV_N + EV_XA : EV_XB) * 128);
                  p.ready = 0; p.need(1u << j0);
                  tma_ld3(a - 3 * PAGE, xmap, fb0, j0 * 128, xpar, xrow);
                }
                if (m < 7) p.need(1u << jj); else if (m == 7) p.next();
              }
              tma_ld3(a, xmap, fb, k * 64, xpar, xrow);
            }
            if (hl == 0) { mbar_wait(sb + BAR_TAG, 0); asm volatile("ld.shared.u32 %0, [%1];" : "=r"(p.base) : "r"(sb + SM_TAG) : "memory"); p.base = (p.base - 1) * 255; }
            p.pat = ffn ? Pat<4>::v : Pat<1>::v;
#pragma unroll 1
            for (int m = 0; m < 14; m++) {
              const int k = (m >> 1) == (hl ? j : 0) ? 14 + (m & 1) : m;
              if (ffn && m == 8) p.addr += 2 * PAGE;
              const uint32_t a = p.acquire<2>(fb);
              p.load_narrow(P, ffn, a + PAGE, fb, k, j);
              tma_ld3(a, xmap, fb, k * 64, xpar, xrow);
            }
            if (!ffn) {
              p.pat = Pat<2>::v;
              uint32_t a = 0;
#pragma unroll 1
              for (int s = 0; s < 16; s++) {
                if ((0x4925 >> s) & 1) a = p.acquire_n(s == 0 || s == 14 ? 2 : 3, fb); else a += PAGE;
                p.load_b(a, 8192, &P.map[M_WO], 0, fb, o_chunk(s, j), 2 * j, 1);
              }
              p.addr += 2 * PAGE;
              a = p.acquire<2>(fb);
              tma_ld3(a, xmap, fb, j * 128, xpar, xrow); tma_ld3(a + PAGE, xmap, fb, j * 128 + 64, xpar, xrow);
            } else {
              p.pat = Pat<5>::v;
#pragma unroll 1
              for (int s = 16; s < 48; s++) {
                const int pi = (s >> 1) & 7;
                const int k = (s < 32 ? pi : pi == 4 ? j : pi == j ? 4 : pi) * 2 + (s & 1);
                const uint32_t a = p.acquire<3>(fb);
                p.load_wide(P, 1, a + PAGE, fb, k, (s & 48) + 2 * j);
                tma_ld3(a, xmap, fb, k * 64, xpar, xrow);
              }
              p.pat = Pat<6>::v;
#pragma unroll 1
              for (int q = 0; q < 4; q++) {
                p.next();
                const int k0 = q == 0 ? 0 : q == 1 ? 48 : q * 16 - 16, k1 = k0 + (q == 1 ? 8 : 16);
#pragma unroll 1
                for (int k = k0; k < k1; k++) {
                  if (k == 24) { p.addr = 0; p.pat = Pat<7>::v; }
                  const uint32_t a = p.acquire<2>(fb);
                  p.load_b(a + PAGE, 8192, &P.map[M_W2], 0, fb, k, 2 * j, 1);
                  tma_ld3(a, &P.map[M_H_LD], fb, k * 64, g, 0);
                }
              }
            }
            TL(2, 1 + hl);
          }
        }
        p.finish();
      }
    } else if (!spare) {
      mbar_wait(sb + BAR_XIN, 0);
      if (elect_one()) {
#pragma unroll 1
        for (int i = warp - 9; i < 8; i += 3) prefetch_l2(ptr_add(P.wqkv, (i * 128 + role) * 6144u + 2048u), 4096);
      }
      uint32_t tag;
      {
        const uint32_t part = warp - 9, col = DM + role * 16 + (lane & 1) * 8;
        const int cnt = part ? 21 : 22;
        const uint4* wp = ptr_add((const uint4*)P.wqkv, ((part ? 16 + part * 336 : 0) + (lane >> 1)) * 6144u + col * 2);
        float s[8] = {0, 0, 0, 0, 0, 0, 0, 0};
        uint4 v[4];
#pragma unroll
        for (int i = 0; i < 4; i++) v[i] = ld_relaxed4(wp + i * (16 * 6144 / 16));
        tag = ld_relaxed(epoch_ptr(P)) + 1;
        if (warp == 10 && lane == 0) { asm volatile("st.shared.u32 [%0], %1;" :: "r"(sb + SM_TAG), "r"(tag) : "memory"); mbar_arrive(sb + BAR_TAG); }
#pragma unroll 1
        for (int b = 4; b < 28; b += 4) {
          wp += 64 * 6144 / 16;
#pragma unroll
          for (int i = 0; i < 4; i++) {
            s[0] += bf_lo(v[i].x); s[1] += bf_hi(v[i].x); s[2] += bf_lo(v[i].y); s[3] += bf_hi(v[i].y);
            s[4] += bf_lo(v[i].z); s[5] += bf_hi(v[i].z); s[6] += bf_lo(v[i].w); s[7] += bf_hi(v[i].w);
            v[i] = make_uint4(0, 0, 0, 0);
            if (b + i < cnt) v[i] = __ldcg(wp + i * (16 * 6144 / 16));
          }
        }
#pragma unroll
        for (int e = 0; e < 4; e++) { const bool h = lane & 16; const float t = __shfl_xor_sync(0xffffffffu, h ? s[e] : s[e + 4], 16); s[e] = (h ? s[e + 4] : s[e]) + t; }
#pragma unroll
        for (int e = 0; e < 2; e++) { const bool h = lane & 8; const float t = __shfl_xor_sync(0xffffffffu, h ? s[e] : s[e + 2], 8); s[e] = (h ? s[e + 2] : s[e]) + t; }
        { const bool h = lane & 4; const float t = __shfl_xor_sync(0xffffffffu, h ? s[0] : s[1], 4); s[0] = (h ? s[1] : s[0]) + t; }
        s[0] += __shfl_xor_sync(0xffffffffu, s[0], 2);
        if (!(lane & 2) || part == 0) st_relaxed(scratch<uint32_t>(P, G_CS + (col + (lane >> 2)) * 16 + ((lane & 2) ? 3 : part) * 4), tagf((lane & 2) ? 0.f : s[0], tag));
        __syncwarp();
      }
      if (warp == 11 && lane == 0) TL(2, 30);
      {
        const uint32_t cspos = sb + SM_CS + ((lane & 16) + ((lane >> 1) & 3) * 4 + ((lane >> 3) & 1) * 2 + (lane & 1)) * 4;
#pragma unroll 1
        for (int it = 0; it < (warp == 10 ? 8 : 1); it++) {
          const int t = it & 3;
          if (it) mbar_wait(sb + BAR_CSE, (it - 1) & 1);
          if (t == 1) mbar_wait(sb + BAR_SEMPTY, 0);
#pragma unroll 1
          for (int b = it ? 0 : warp - 9; b < (it == 0 ? warp - 8 : t < 2 ? 3 : 2); b++) {
            uint32_t c0, c1;
            if (b < 2) { c0 = (t ? 2048 + t * 1024 + b * FF : 1024 + b * 1024) + j * 128; c1 = c0 + 64; }
            else if (t) { c0 = 6144 + j * 64; c1 = c0 + FF; }
            else { c0 = j * 128; c1 = c0 + 64; }
            const uint4* p0 = scratch<uint4>(P, G_CS + (c0 + lane) * 16u);
            const uint4* p1 = scratch<uint4>(P, G_CS + (c1 + lane) * 16u);
            uint4 v[4]; uint32_t spins = 0; bool ok;
            do {
              if (spins) __nanosleep(200);
              v[0] = ld_relaxed4(p0); v[1] = ld_relaxed4(p0 + 32); v[2] = ld_relaxed4(p1); v[3] = ld_relaxed4(p1 + 32);
              ok = tag_ok4(v[0], tag) && tag_ok4(v[1], tag) && tag_ok4(v[2], tag) && tag_ok4(v[3], tag);
              spin_check(++spins);
            } while (__any_sync(0xffffffffu, !ok));
#pragma unroll
            for (int m = 0; m < 4; m++) sts32f(cspos + b * 512 + m * 128, (untag(v[m].x) + untag(v[m].y)) + (untag(v[m].z) + untag(v[m].w)));
            __syncwarp();
            if (lane == 0) mbar_arrive(sb + BAR_CSF + (b ? 8 : 0));
          }
          if (lane == 0) { if (t >= 2) mbar_arrive(sb + BAR_CSF + 8); TL(2, 16 + it + (warp == 11 ? 8 : warp == 9 ? 9 : 0)); }
          if (t == 3) {
            if (g >= 2) {
              uint4* op = scratch<uint4>(P, G_HALO + (((it >> 2) * 16 + g - 2) * 8 + j) * 4096u + lane * 16u);
#pragma unroll 1
              for (int i = 0; i < 8; i++) { st_b128(op, 0, 0, 0, 0); op += 32; }
            }
          }
        }
      }
      if (warp == 11) {
        if (elect_one()) prefetch_l2(ptr_add(P.wo, role * 16384u), 16384);
        uint32_t* const fl = scratch<uint32_t>(P, g * G_BLOCK + G_FLAGS);
        uint32_t seen = 0;
#pragma unroll 1
        for (int e = EV_XA; e < EV_N + EV_XB; e++) {
          if (e == EV_XB) continue;
          const bool clr = (e & 7) == EV_XA;
          uint32_t* const f = ptr_add(fl, (clr ? 16 + e : e) * 128u);
          if (clr) {
            uint4* op = scratch<uint4>(P, g * G_BLOCK + G_O + j * 32768u + lane * 16u);
#pragma unroll 1
            for (int i = 0; i < 64; i++) { st_b128(op, 0, 0, 0, 0); op += 32; if (e || (i & 1)) __nanosleep(10); }
            __syncwarp();
            if (lane == 0) red_release(f, 1u << j);
          }
          uint32_t spins = 0, m;
          while ((m = ld_relaxed(f) - (tag - 1) * 255) != 255) { __nanosleep(m ? 50 : 500); spin_check(++spins); }
          asm volatile("fence.acquire.gpu;" ::: "memory");
          if (lane == 0) {
            if (clr) mbar_arrive(sb + BAR_CLR);
            else asm volatile("st.release.cta.shared.u32 [%0], %1;" :: "r"(sb + SM_SEEN), "r"(++seen) : "memory");
          }
          if (e == EV_H3) {
#pragma unroll 1
            for (int i = 0; i < 7; i++) { if (elect_one()) prefetch_l2(ptr_add(P.w2, (i * 128 + role) * 8192u), 8192); __nanosleep(500); }
          }
          __syncwarp();
        }
      } else if (warp == 9) {
        if (elect_one()) {
          prefetch_map(&P.map[M_WQ]); prefetch_map(&P.map[M_OUT_LD]); prefetch_map(&P.map[M_WO]); prefetch_map(&P.map[M_W1 + rank]);
          prefetch_map(&P.map[M_H_ST]); prefetch_map(&P.map[M_H_LD]); prefetch_map(&P.map[M_W1H + rank]); prefetch_map(&P.map[M_W2]); prefetch_map(&P.map[M_OUT_ST]);
          uint32_t* fl = scratch<uint32_t>(P, g * G_BLOCK + G_FLAGS);
          int pe = 0;
#pragma unroll 1
          for (int e = 0; e < 2 * EV_N; e++) {
            const int q = e & 7;
            const bool is_h = q >= EV_H0 && q < EV_XB, last = e >= EV_N + EV_XB;
            const CUtensorMap* map = &P.map[is_h ? M_H_ST : M_OUT_ST];
            const int col = q == EV_H3 ? 3072 - 64 + j * 64 : (q == EV_H1 ? 1024 : q == EV_H2 ? 2048 : 0) + j * 128;
            const int row = is_h ? 0 : (g >> 1) * 128, par = is_h ? g : g & 1;
#pragma unroll 1
            for (int hb = is_h ? q == EV_H3 : q & 1; hb <= (is_h ? 1 : q & 1); hb++) {
#pragma unroll
              for (int w = 0; w < 2; w++) {
                const bool sw = last;
                const int wg = sw ? hb : w, h = sw ? w : hb, p = sw ? pe - hb + w : pe;
                mbar_wait(sb + BAR_SFULL + 16 * wg + 8 * (p & 1), (p >> 1) & 1);
                if (w == 0) TL(3, 20 + e);
                tma_st3(map, sb + SM_STAGE + wg * PAGE + h * 8192, col + h * 64, par, row + wg * 64);
              }
              pe++;
            }
            bulk_commit();
            if (e != EV_N + EV_XB) bulk_wait<0>();
            TL(3, 40 + e);
            if (is_h || (q & 1)) mbar_arrive(sb + BAR_SEMPTY);
            if (!last) red_release(fl, 1u << j);
            TL(3, e);
            fl += 32;
          }
          *epoch_ptr(P) = tag;
        }
      }
    }
  } else {
    if (!spare) {
      const uint32_t r = threadIdx.x >> 3, so = r * 128 + (((threadIdx.x ^ r) & 7) << 4);
      const uint8_t* xp = ptr_add((const uint8_t*)P.x, (2 * ((g >> 1) * 128 + r) + (g & 1)) * 2048u + (threadIdx.x & 7) * 16u);
      const uint8_t* wp = ptr_add((const uint8_t*)P.wqkv, r * 6144u + 2048u + j * 256u + (threadIdx.x & 7) * 16u);
#pragma unroll
      for (int i = 0; i < 4; i++) asm volatile("cp.async.cg.shared.global [%0], [%1], 16;" :: "r"(sb + SM_STAGE + (i >> 1) * PAGE + (i & 1) * 4096 + so), "l"(xp + i * 32 * 4096) : "memory");
#pragma unroll
      for (int q = 0; q < 8; q++) {
        const int i = (q & 3) * 2 + (q >> 2);
        asm volatile("cp.async.cg.shared.global [%0], [%1], 16;" :: "r"(sb + i * 4096 + so), "l"(wp + (i & 1) * 32 * 6144 + ((i >> 1) & 1) * 128 + (i >> 2) * 2048) : "memory");
      }
    }
    if (!spare) {
      if (warp == 0) asm volatile("prefetch.global.L2 [%0];" :: "l"(ptr_add(P.x, (2 * ((g >> 1) * 128 + j * 16 + (lane >> 1)) + (g & 1)) * 2048u + (lane & 1) * 128u)));
      else if (warp < 3 && (warp == 1 || lane < 16)) asm volatile("prefetch.global.L2 [%0];" :: "l"(ptr_add(P.wqkv, role * 6144u + (warp - 1) * 4096u + lane * 128u)));
      __syncwarp();
    }
    asm volatile("barrier.cluster.arrive.relaxed.aligned;" ::: "memory");
    asm volatile("setmaxnreg.inc.sync.aligned.u32 232;");
    SP(4);
    asm volatile("barrier.cluster.wait.acquire.aligned;" ::: "memory");
    SP(5);
    const int wg = warp >> 2;
    const int quad = lane & 3, gr = lane >> 2;
    Cons c; c.sb = sb; c.n = 0; c.off = 0; c.prev = 0; c.lane = lane;
    c.ebar = mapa(sb + BAR_EMPTY - 64, shared_b() ? lane & 1 : rank);
    const uint32_t stage = sb + SM_STAGE + wg * PAGE;
    const uint32_t dstage = desc_lo(stage, 16);
    if (spare) {
      const uint32_t tag = ld_relaxed(epoch_ptr(P)) + 1;
      const int tid = threadIdx.x & 127;
#pragma unroll
      for (int i = 0; i < 4; i++) sts128(stage + (i * 128 + tid) * 16, 0x3f803f80u, 0x3f803f80u, 0x3f803f80u, 0x3f803f80u);
      fence_async_smem();
      bar_sync(2 + wg, 128);
      c.db0 = desc_lo(sb + wg * PAGE, 8192);
#pragma unroll 1
      for (int r = -1; r < 7; r++) {
        float acc[64];
#pragma unroll 1
        for (int k = 0; k < 16; k++) c.step_ab<128, 2>(acc, dstage, c.db0 + c.off, k);
        c.drain();
        acc_fence<64>(acc);
        {
          float v = 0;
#pragma unroll
          for (int i = 0; i < 32; i++) asm("{\n.reg .pred p;\nsetp.eq.u32 p, %2, %3;\nselp.f32 %0, %1, %0, p;\n}" : "+f"(v) : "f"(acc[4 * (i >> 1) + (i & 1)]), "r"(tid >> 2), "r"(i));
          st_b128(scratch<uint4>(P, G_CS + (uint32_t)((r < 0 ? j * 256 + wg * 128 : 3 * DM + wg * FF + ((r < 2 ? r : r == 2 ? 6 : r - 1) * 4 + j) * 128) + (tid >> 3) * 8 + quad * 2 + (gr & 1)) * 16u),
                  tagf(v, tag), tag & 15u, tag & 15u, tag & 15u);
        }
        __syncwarp();
      }
      if (wg == 0) {
        const uint32_t* p = scratch<uint32_t>(P, (tid >> 3) * G_BLOCK + G_STATS + (tid & 7) * 8u);
        uint32_t spins = 0;
        while (__any_sync(0xffffffffu, (ld_relaxed(p) ^ tag) & 15u)) spin_check(++spins);
      }
      bar_sync(1, 256);
      if (threadIdx.x == 0) *epoch_ptr(P) = tag;
    } else {
    c.da0 = desc_lo(sb + wg * 8192, 16); c.db0 = desc_lo(sb, 8192);
    uint32_t sphase = 1, sfull = sb + BAR_SFULL + 16 * wg;
    const uint32_t maddr = stage + ((warp & 3) * 16 + (lane & 15)) * 128 + (((lane >> 4) ^ (lane & 7)) << 4);
    const uint32_t csaddr = sb + SM_CS + quad * 16;
    float st[8] = {0, 0, 0, 0, 0, 0, 0, 0};
    float* const mean = st; float* const rstd = st + 2;
    SP(6);

    auto stage_wait = [&]() { mbar_wait_fast(sb + BAR_SEMPTY, sphase); sphase ^= 1; };
    auto stage_publish = [&]() { fence_async_smem(); __syncwarp(); if (lane == 0) mbar_arrive(sfull); sfull ^= 8; };
    auto cs_load = [&](uint32_t (&cs)[16], int grp) {
#pragma unroll
      for (int i = 0; i < 4; i++) lds128(csaddr + grp * 256 + i * 64, cs[4 * i], cs[4 * i + 1], cs[4 * i + 2], cs[4 * i + 3]);
    };
    auto cs_apply = [&](float* acc, uint32_t (&cs)[16]) {
      acc_fence<32>(acc);
#pragma unroll
      for (int b = 0; b < 8; b++) {
        acc[4 * b] -= mean[0] * __uint_as_float(cs[2 * b]); acc[4 * b + 1] -= mean[0] * __uint_as_float(cs[2 * b + 1]);
        acc[4 * b + 2] -= mean[1] * __uint_as_float(cs[2 * b]); acc[4 * b + 3] -= mean[1] * __uint_as_float(cs[2 * b + 1]);
      }
      acc_fence<32>(acc);
    };
    auto glu_pair = [&](float g0, float g1, float u0, float u1, int r) {
      const float nl = -LOG2E * rstd[r], r2 = rstd[r] * rstd[r];
      return pack_bf16(g0 * u0 * r2 * rcp(1.0f + ex2(g0 * nl)), g1 * u1 * r2 * rcp(1.0f + ex2(g1 * nl)));
    };
    auto glu_slice = [&](uint32_t (&pk)[64], int i) {
      uint32_t hp[4];
#pragma unroll
      for (int e = 0; e < 4; e++) {
        asm volatile("" : "+r"(pk[4 * i + e]), "+r"(pk[32 + 4 * i + e]));
        const uint32_t pg = pk[4 * i + e], pu = pk[32 + 4 * i + e];
        hp[e] = glu_pair(bf_lo(pg), bf_hi(pg), bf_lo(pu), bf_hi(pu), e & 1);
      }
      stsm4((maddr ^ ((i & 3) << 5)) + (i >> 2) * 8192, hp[0], hp[1], hp[2], hp[3]);
    };
    auto glu_slice_acc = [&](float (&acc)[128], int i) {
      uint32_t hp[4];
      acc_fence<8>(acc + 8 * i);
#pragma unroll
      for (int e = 0; e < 4; e++) hp[e] = glu_pair(acc[8 * i + 2 * e], acc[8 * i + 2 * e + 1], acc[64 + 8 * i + 2 * e], acc[64 + 8 * i + 2 * e + 1], e & 1);
      stsm4((maddr ^ ((i & 3) << 5)) + (i >> 2) * 8192, hp[0], hp[1], hp[2], hp[3]);
    };
    auto stage_x = [&](uint32_t (&x)[32], int hf) {
#pragma unroll
      for (int i = 4 * hf; i < 4 * hf + 4; i++) stsm4((maddr ^ ((i & 3) << 5)) + hf * 8192, x[4 * i], x[4 * i + 1], x[4 * i + 2], x[4 * i + 3]);
    };

    float acc[128];
    asm volatile("cp.async.wait_all;" ::: "memory");
    fence_async_smem();
    bar_sync(1, 256);
    SP(7);
    c.step_own<256>(acc, dstage, 0);
    mbar_wait_fast(sb + BAR_XIN, 0);
    SP(8);
#pragma unroll 1
    for (int hl = 0;; hl++) {
      int t = hl & 1;
      float acc2[64];
      uint32_t res[32];
      c.step_own<256>(acc, dstage + 512, 1);
#pragma unroll
      for (int s = 0; s < 2; s++) c.step_own<128>(acc2, dstage + s * 512, s);
#pragma unroll 1
      for (int s = 2; s < 11; s++) {
        const uint32_t apage = (c.off << 4) - (SM_STAGE + wg * 8192);
        if (s == 3 && wg) bar_sync(6, 256);
        c.step<256>(acc);
        if (s == 3 && !wg) asm volatile("bar.arrive 6, 256;" ::: "memory");
        int act = s;
        asm volatile("" : "+r"(act));
        auto get_tag = [&]() { uint32_t tag; asm volatile("ld.shared.u32 %0, [%1];" : "=r"(tag) : "r"(sb + SM_TAG) : "memory"); return tag; };
        auto stat_ptr = [&]() { return scratch<uint2>(P, g * G_BLOCK + G_STATS + (hl * 128 + warp * 16 + (lane_now() >> 2)) * 64u); };
        auto stat_get = [&]() {
          const uint2* sp = ptr_add(stat_ptr(), (lane_now() & 3) * 16);
          const uint4 a = ld_relaxed4(sp), b = ld_relaxed4(sp + 64);
          st[0] = __uint_as_float(a.x); st[1] = __uint_as_float(a.y); st[2] = __uint_as_float(a.z); st[3] = __uint_as_float(a.w);
          st[4] = __uint_as_float(b.x); st[5] = __uint_as_float(b.y); st[6] = __uint_as_float(b.z); st[7] = __uint_as_float(b.w);
        };
        switch (act) {
          case 4: case 5: {
            const uint32_t ra = maddr + ((hl || j == 0) ? (s & 1) * 8192 : apage);
#pragma unroll
            for (int i = 0; i < 4; i++) {
              uint32_t v[4];
              ldsm4(ra ^ (i << 5), v[0], v[1], v[2], v[3]);
              if (i == 0 && s == 4) { st[0] = bf_lo(v[0]); st[1] = bf_lo(v[1]); st[2] = st[3] = st[4] = st[5] = 0; }
#pragma unroll
              for (int e = 0; e < 4; e++) {
                const float a = bf_lo(v[e]) - st[e & 1], b = bf_hi(v[e]) - st[e & 1];
                st[2 + (e & 1)] += a + b; st[4 + (e & 1)] += a * a; st[4 + (e & 1)] += b * b;
              }
            }
          } break;
          case 6: {
            mbar_wait_fast(sb + BAR_TAG, 0);
            const uint32_t tag = get_tag();
#pragma unroll
            for (int r = 0; r < 2; r++) {
              const float mt = st[r] + st[2 + r] * (1.0f / 32);
              float m = mt + __shfl_xor_sync(0xffffffffu, mt, 1); m += __shfl_xor_sync(0xffffffffu, m, 2); m *= 0.25f;
              float q = st[4 + r] - st[2 + r] * st[2 + r] * (1.0f / 32) + 32.0f * (mt - m) * (mt - m);
              q += __shfl_xor_sync(0xffffffffu, q, 1); q += __shfl_xor_sync(0xffffffffu, q, 2);
              if (quad == 0) st_relaxed2(ptr_add(stat_ptr(), r * 512 + j * 8), tagf(m, tag), tagf(q, tag));
            }
          } break;
          case 8: stat_get(); break;
          case 10: {
            const uint32_t tag = get_tag();
            uint32_t spins = 0;
            for (;;) {
              uint32_t bad = 0;
#pragma unroll
              for (int i = 0; i < 8; i++) bad |= __float_as_uint(st[i]) ^ tag;
              if (!__any_sync(0xffffffffu, bad & 15u)) break;
              stat_get(); spin_check(++spins);
            }
            float mr[4];
#pragma unroll
            for (int r = 0; r < 2; r++) {
              const float m0 = untag(__float_as_uint(st[4 * r])), m1 = untag(__float_as_uint(st[4 * r + 2]));
              float m = m0 + m1; m += __shfl_xor_sync(0xffffffffu, m, 1); m += __shfl_xor_sync(0xffffffffu, m, 2); m *= 0.125f;
              float q = untag(__float_as_uint(st[4 * r + 1])) + untag(__float_as_uint(st[4 * r + 3])) + 128.0f * ((m0 - m) * (m0 - m) + (m1 - m) * (m1 - m));
              q += __shfl_xor_sync(0xffffffffu, q, 1); q += __shfl_xor_sync(0xffffffffu, q, 2);
              mr[r] = m; mr[2 + r] = rsqrtf(fmaxf(q, 0.f) * (1.0f / DM) + LN_EPS);
            }
            st[0] = mr[0]; st[1] = mr[1]; st[2] = mr[2]; st[3] = mr[3];
          } break;
          default: break;
        }
      }
#pragma unroll 1
      for (;;) {
      const int it = (hl >> 1) * 4 + t;
#pragma unroll
      for (int s = 0; s < 4; s++) {
        uint32_t cs[16];
        c.step<256>(acc);
        if (!(s & 1)) mbar_wait_fast(sb + BAR_CSF + 4 * s, t & 1);
        if (s >= 2 && t <= 1) { cs_load(cs, 2 + s); cs_apply(acc2 + 32 * (s - 2), cs); }
        cs_load(cs, s);
        c.drain();
        cs_apply(acc + 32 * s, cs);
      }
      c.step<256>(acc);
      if (lane == 0) mbar_arrive(sb + BAR_CSE);
      c.drain();
      acc_fence<128>(acc);
      TLC(1 + it * 6);
      uint32_t pkB[64];
      if (t == 2) {
#pragma unroll
        for (int i = 0; i < 64; i++) pkB[i] = pack_bf16(acc[2 * i], acc[2 * i + 1]);
      } else if (t == 0) {
        uint32_t pkA[64];
        auto kv_pack = [&](int v, int r) {
#pragma unroll
          for (int i = 32 * v + r; i < 32 * v + 32; i += 2) { acc_fence<2>(acc + 2 * i); pkA[i] = pack_bf16(acc[2 * i] * rstd[r], acc[2 * i + 1] * rstd[r]); }
        };
        const uint32_t l16 = lane_now() * 16u;
        uint4* const xs = ptr_add((uint4*)smem_raw, SM_STAGE + l16);
        uint4* const hp = scratch<uint4>(P, G_HALO + (((hl >> 1) * 16 + g) * 8 + j) * 4096u + l16);
        {
          uint4* const dst = (warp == 7 && g < 14) ? hp : ptr_add(xs, warp * 4096u);
#pragma unroll
          for (int s = 0; s < 2; s++) {
            c.steps<128>(acc2, s ? 2 : 1 + wg);
            if (s == 0) stage_wait();
            kv_pack(s, 1);
#pragma unroll
            for (int i = 4 * s; i < 4 * s + 4; i++) { pkA[8 * i + 1] = pkt_head(pkA[8 * i + 1]); gen_store(dst + i * 32, pkA[8 * i + 1], pkA[8 * i + 3], pkA[8 * i + 5], pkA[8 * i + 7]); }
          }
        }
        __syncwarp();
        if (lane == 0) mbar_arrive(sb + BAR_XFULL);
#pragma unroll
        for (int s = 0; s < 2; s++) {
          c.steps<128>(acc2, 2);
#pragma unroll
          for (int i = 33 - s; i < 64; i += 2) pkA[i] = movm(pkA[i]);
          kv_pack(1 - s, 0);
        }
        uint32_t kvH[32];
        {
          const uint4* const src = (warp == 0 && g >= 2) ? hp - 2 * 8 * 256 : ptr_add(xs, (warp ? warp - 1 : 0) * 4096u);
          c.steps<128>(acc2, 2);
          mbar_wait_fast(sb + BAR_XFULL, hl >> 1);
#pragma unroll
          for (int i = 0; i < 8; i++) gen_load(src + i * 32, kvH + 4 * i);
          c.steps<128>(acc2, 3 - wg);
          uint32_t spins = 0;
          while (__any_sync(0xffffffffu, !(kvH[0] && kvH[4] && kvH[8] && kvH[12] && kvH[16] && kvH[20] && kvH[24] && kvH[28]))) {
#pragma unroll
            for (int i = 0; i < 8; i++) gen_load(src + i * 32, kvH + 4 * i);
            spin_check(++spins);
          }
        }
#pragma unroll
        for (int i = 16; i < 32; i++) kvH[i] = movm(kvH[i]);
        mbar_wait_fast(sb + BAR_CLR, hl >> 1);
        c.steps<128>(acc2, 2);
        AP(0);
        c.wait_full(0);
        AP(1);
        c.drain();
        AP(2);
        acc_fence<64>(acc2);
        TLC(2 + it * 6);
        uint32_t q[32];
#pragma unroll
        for (int i = 0; i < 32; i++) q[i] = pack_bf16(acc2[2 * i], acc2[2 * i + 1]);
        const uint32_t zm = bar_sync_zero(1, 256);
        AP(3);
        uint32_t ob[6][16];
        uint4* const omail = scratch<uint4>(P, g * G_BLOCK + G_O + warp * 2048u + l16);
        float o2[8][4], r2[4];
        {
          const float hv = (warp == 0 && g < 2) ? -INFINITY : 0.f;
          const float hinit[4] = {hv, hv, hv, hv};
          const bool c0 = (2 * quad <= gr), c1 = (2 * quad + 1 <= gr);
          const uint32_t lm = (c0 ? 0xffffu : 0u) | (c1 ? 0xffff0000u : 0u);
          const float sc[2] = {rstd[0] * (0.17677669529663687f * LOG2E), rstd[1] * (0.17677669529663687f * LOG2E)};
          float lg[4][4], mx[4][2];
#pragma unroll
          for (int h = 0; h < 4; h++) {
            const int b = h * 4;
            float sH[4], sL[4], sU[4];
            q[2 * b] |= zm;
            mma16816(sH, q[2 * b], q[2 * b + 1], q[2 * b + 2], q[2 * b + 3], kvH[b], kvH[b + 1], hinit);
            mma16816z(sL, q[2 * b], q[2 * b + 1], q[2 * b + 2], q[2 * b + 3], pkA[2 * b], pkA[2 * b + 2]);
            mma16816z(sU, q[2 * b], q[2 * b + 1], q[2 * b + 2], q[2 * b + 3], pkA[2 * b + 1], pkA[2 * b + 3]);
            mma16816(sH, q[2 * b + 4], q[2 * b + 5], q[2 * b + 6], q[2 * b + 7], kvH[b + 2], kvH[b + 3], sH);
            mma16816(sL, q[2 * b + 4], q[2 * b + 5], q[2 * b + 6], q[2 * b + 7], pkA[2 * b + 4], pkA[2 * b + 6], sL);
            mma16816(sU, q[2 * b + 4], q[2 * b + 5], q[2 * b + 6], q[2 * b + 7], pkA[2 * b + 5], pkA[2 * b + 7], sU);
            lg[h][0] = c0 ? sL[0] : sH[0]; lg[h][1] = c1 ? sL[1] : sH[1]; lg[h][2] = c0 ? sU[2] : sL[2]; lg[h][3] = c1 ? sU[3] : sL[3];
            mx[h][0] = fmaxf(lg[h][0], lg[h][1]); mx[h][1] = fmaxf(lg[h][2], lg[h][3]);
          }
#pragma unroll
          for (int o = 1; o < 4; o <<= 1) {
#pragma unroll
            for (int i = 0; i < 8; i++) mx[i >> 1][i & 1] = fmaxf(mx[i >> 1][i & 1], __shfl_xor_sync(0xffffffffu, mx[i >> 1][i & 1], o));
          }
          AP(4);
          uint32_t z = zm, pp[4][2];
          float rs[4][2];
          auto probs = [&](int h) {
            pp[h][0] = pack_bf16(ex2((lg[h][0] - mx[h][0]) * sc[0]), ex2((lg[h][1] - mx[h][0]) * sc[0]));
            pp[h][1] = pack_bf16(ex2((lg[h][2] - mx[h][1]) * sc[1]), ex2((lg[h][3] - mx[h][1]) * sc[1]));
            float sum[4];
            mma1688z(sum, pp[h][0], pp[h][1], 0x3f803f80u);
            rs[h][0] = rcp(sum[0]); rs[h][1] = rcp(sum[2]);
            asm volatile("" : "+f"(rs[h][0]), "+f"(rs[h][1]));
          };
          probs(0); probs(1); probs(2); probs(3);
#pragma unroll
          for (int hf = 0; hf < 2; hf++) {
#pragma unroll
            for (int hh = 0; hh < 2; hh++) {
              const int h = hf * 2 + hh, b = h * 4;
              const uint32_t pa = pp[h][0], pb = pp[h][1];
              const uint32_t p0 = pa & ~lm, p1 = pa & z, p2 = pa & lm, p3 = pb & ~lm, p4 = pb & z, p5 = pb & lm;
              const float ra = rs[h][0], rb = rs[h][1];
#pragma unroll
              for (int d = 0; d < 4; d++) {
                float o[4];
                mma16816z(o, p0, p1, p2, p3, kvH[16 + b + d], pkA[32 + 2 * (b + d)]);
                mma1688(o, p4, p5, pkA[32 + 2 * (b + d) + 1], o);
                if (hf == 0) { ob[0][(hh * 4 + d) * 2] = pack_bf16(o[0] * ra, o[1] * ra); ob[0][(hh * 4 + d) * 2 + 1] = pack_bf16(o[2] * rb, o[3] * rb); }
                else { o2[hh * 4 + d][0] = o[0]; o2[hh * 4 + d][1] = o[1]; o2[hh * 4 + d][2] = o[2]; o2[hh * 4 + d][3] = o[3]; }
              }
              if (hf) { r2[2 * hh] = ra; r2[2 * hh + 1] = rb; }
            }
            if (hf == 0) {
#pragma unroll
              for (int i = 0; i < 4; i++) ob[0][4 * i] = pkt_head(ob[0][4 * i]);
              AP(5);
              uint4* op = ptr_add(omail, j * 32768u);
#pragma unroll
              for (int i = 0; i < 4; i++) st_b128(op + i * 32, ob[0][4 * i], ob[0][4 * i + 1], ob[0][4 * i + 2], ob[0][4 * i + 3]);
              z = late_zero(zm);
              AP(6);
            }
          }
        }
        auto finish_o2 = [&](uint32_t z) {
#pragma unroll
          for (int i = 0; i < 4; i++) r2[i] = __uint_as_float(__float_as_uint(r2[i]) | z);
#pragma unroll
          for (int i = 0; i < 8; i++) {
            ob[1][2 * i] = pack_bf16(o2[i][0] * r2[(i >> 2) * 2], o2[i][1] * r2[(i >> 2) * 2]);
            ob[1][2 * i + 1] = pack_bf16(o2[i][2] * r2[(i >> 2) * 2 + 1], o2[i][3] * r2[(i >> 2) * 2 + 1]);
          }
#pragma unroll
          for (int i = 0; i < 4; i++) { ob[1][4 * i] = pkt_head(ob[1][4 * i]); sts128(stage + (warp & 3) * 2048 + i * 512 + l16, ob[1][4 * i], ob[1][4 * i + 1], ob[1][4 * i + 2], ob[1][4 * i + 3]); }
        };
        {
          uint32_t dep = __float_as_uint(r2[0]) | __float_as_uint(r2[2]);
#pragma unroll
          for (int i = 0; i < 8; i++) dep |= __float_as_uint(o2[i][3]);
          const uint32_t cnt = 256 | (dep & zm);
          AP(7);
          if (wg) { asm volatile("bar.arrive 1, %0;" :: "r"(cnt) : "memory"); bar_sync(6, 256); } else bar_sync(1, cnt);
        }
        TLC(3 + it * 6);
        AP(8);
        uint64_t todo;
        { const uint32_t o7 = 0x6543210u | (7u << (4 * j) & 0xfffffffu); todo = (uint64_t)(o7 * 2) | (uint64_t)(o7 * 2 + 0x1111111u) << 28; }
        const uint4* pf[3];
        auto next_ptrs = [&](const uint4* (&p)[3]) {
#pragma unroll
          for (int i = 0; i < 3; i++) p[i] = ptr_add(omail, (((uint32_t)todo >> (4 * i)) & 15u) << 14);
          asm volatile("" : "+l"(p[0]), "+l"(p[1]), "+l"(p[2]));
          todo >>= 12;
        };
        next_ptrs(pf);
        auto batch = [&](int b, bool first, bool three) {
          const int y = 3 - b;
          auto o_fetch = [&]() {
#pragma unroll
            for (int i = 0; i < 8; i++) pkt_load(pf[i >> 2] + (i & 3) * 32, ob[y + (i >> 2)] + 4 * (i & 3));
            if (three) {
#pragma unroll
              for (int i = 0; i < 4; i++) pkt_load(pf[2] + i * 32, ob[y + 2] + 4 * i);
            }
          };
          if (first) {
            c.issue_rs<0, 2>(acc2, ob[0], 0);
            finish_o2(late_zero(zm));
            o_fetch();
            c.issue_rs<1, 2>(acc2, ob[1]);
            if (!wg) asm volatile("bar.arrive 6, 256;" ::: "memory");
          } else {
            o_fetch();
            c.issue_rs<0, 3>(acc2, ob[b]); c.issue_rs<1, 3>(acc2, ob[b + 1]); c.issue_rs<2, 3>(acc2, ob[b + 2]);
          }
          const uint32_t z = late_zero(zm);
          const uint4* pn[3];
          next_ptrs(pn);
          c.wait_full(0);
          uint32_t spins = 0;
          for (;;) {
            bool bad[3];
#pragma unroll
            for (int i = 0; i < 3; i++) bad[i] = ob[y + i][0] == z || ob[y + i][4] == z || ob[y + i][8] == z || ob[y + i][12] == z;
            if (__builtin_expect(!__any_sync(0xffffffffu, bad[0] | bad[1] | bad[2]), 1)) break;
            o_fetch();
            spin_check(++spins);
          }
          if (first) {
            fence_async_smem();
            __syncwarp();
            if (elect_one()) {
              asm volatile("cp.async.bulk.global.shared::cta.bulk_group [%0], [%1], 2048;"
                           :: "l"(scratch<uint4>(P, g * G_BLOCK + G_O + (2 * j + 1) * 16384u + warp * 2048u)), "r"(stage + (warp & 3) * 2048) : "memory");
              bulk_commit();
            }
          }
          pf[0] = pn[0]; pf[1] = pn[1]; pf[2] = pn[2];
          c.drain();
        };
        batch(0, true, true);
#pragma unroll 1
        for (int i = 0; i < 2; i++) { batch(3, false, true); batch(0, false, i == 0); }
        c.issue_rs<0, 2>(acc2, ob[3]); c.issue_rs<1, 2>(acc2, ob[4]);
        if (elect_one()) bulk_wait<0>();
        __syncwarp();
        {
          c.off += 2 << 10;
          c.wait_full(0);
          const uint32_t ra = maddr - (SM_STAGE + wg * 8192) + (c.off << 4);
#pragma unroll
          for (int i = 0; i < 8; i++) ldsm4((ra ^ ((i & 3) << 5)) + (i >> 2) * PAGE, res[4 * i], res[4 * i + 1], res[4 * i + 2], res[4 * i + 3]);
          if (lane < 2) mbar_arrive_cluster(c.ebar + 64 + ((c.n & 7) << 3));
          c.advance<2>();
          c.drain();
        }
        break;
      } else {
        c.steps<128>(acc2, 1 + wg);
        stage_wait();
        glu_slice_acc(acc, 0);
#pragma unroll
        for (int s = 1; s < 8; s++) {
          if (s == 5) c.steps_skip(acc2, t == 1 ? 1 - wg : 2); else c.steps<128>(acc2, (s & 1) || t == 3 ? 2 : 1);
          if (s == 4) stage_publish();
          glu_slice_acc(acc, s);
        }
        c.steps<128>(acc2, 2 - wg);
        stage_publish();
        if (t == 3) {
#pragma unroll
          for (int i = 0; i < 32; i++) { res[i] = 0x80008000u; asm volatile("" : "+r"(res[i])); }
#pragma unroll 1
          for (int i = 0; i < 3; i++) {
            c.steps<128>(acc2, i == 0 ? 15 : i == 1 ? 24 - TAIL_LAG : TAIL_LAG);
            if (i == 0) c.off = 0;
            else if (hl == 3) { if (wg == 1 && i == 1) { c.drain(); bar_sync(5, 256); } else if (wg == 0 && i == 2) asm volatile("bar.arrive 5, 256;" ::: "memory"); }
          }
          stage_wait();
          c.drain();
          break;
        }
        c.drain();
        TLC(2 + it * 6);
        c.step<256>(acc, 0);
        acc_fence<64>(acc2);
#pragma unroll
        for (int i = 0; i < 16; i++) {
          pkB[16 + i] = pack_bf16(acc2[2 * i], acc2[2 * i + 1]); pkB[48 + i] = pack_bf16(acc2[32 + 2 * i], acc2[32 + 2 * i + 1]);
          pkB[i] = 0; pkB[32 + i] = 0;
        }
      }
      t++;
#pragma unroll 1
      for (int s = 3 - t; s < 8; s++) {
        c.step<256>(acc, s);
        int act = (t == 3 || s >= 4) ? s : 8;
        asm volatile("" : "+r"(act));
        if (act < 8) {
          if (!(act & 3)) { if (act && t == 3) stage_publish(); else stage_wait(); }
          auto f = [&](int i) { glu_slice(pkB, i); };
          SELECT8(act, f);
        }
      }
#pragma unroll
      for (int s = 0; s < 2; s++) {
        const uint32_t ra = maddr - (SM_STAGE + wg * 8192) + (c.off << 4);
        c.step<256>(acc);
        if (s == 0) stage_publish();
#pragma unroll
        for (int i = 0; i < 4; i++) {
          uint32_t v[4];
          ldsm4(ra ^ (i << 5), v[0], v[1], v[2], v[3]);
#pragma unroll
          for (int e = 0; e < 4; e++) { acc2[32 * s + 8 * i + 2 * e] = bf_lo(v[e]); acc2[32 * s + 8 * i + 2 * e + 1] = bf_hi(v[e]); }
        }
        acc_fence<32>(acc2 + 32 * s);
      }
      c.step<256>(acc);
      }
      const int it = (hl >> 1) * 4 + t;
      acc_fence<64>(acc2);
      TLC(4 + it * 6);
      uint32_t xn[32];
#pragma unroll
      for (int i = 0; i < 16; i++) xn[i] = add_bf16x2(res[i], pack_bf16(acc2[2 * i], acc2[2 * i + 1]));
      stage_x(xn, 0);
#pragma unroll
      for (int i = 16; i < 32; i++) { xn[i] = add_bf16x2(res[i], pack_bf16(acc2[2 * i], acc2[2 * i + 1])); asm volatile("" : "+r"(xn[i])); }
      stage_publish();
      if (hl == 3) { stage_x(xn, 1); stage_publish(); TLE(47); TLG(63); break; }
      bar_sync(2 + wg, 128);
      TLC(5 + it * 6);
      c.step_own<256>(acc, dstage, 0);
      stage_x(xn, 1);
      stage_publish();
      bar_sync(2 + wg, 128);
    }
    }
  }
}

typedef CUresult (*EncodeFn)(CUtensorMap*, CUtensorMapDataType, cuuint32_t, void*, const cuuint64_t*, const cuuint64_t*, const cuuint32_t*,
                             const cuuint32_t*, CUtensorMapInterleave, CUtensorMapSwizzle, CUtensorMapL2promotion, CUtensorMapFloatOOBfill);

void encode(EncodeFn fn, CUtensorMap* m, const void* ptr, int rank, const cuuint64_t* dims, const cuuint64_t* strides, const cuuint32_t* box) {
  cuuint32_t es[5] = {1, 1, 1, 1, 1};
  fn(m, CU_TENSOR_MAP_DATA_TYPE_BFLOAT16, rank, const_cast<void*>(ptr), dims, strides, box, es, CU_TENSOR_MAP_INTERLEAVE_NONE,
     CU_TENSOR_MAP_SWIZZLE_128B, CU_TENSOR_MAP_L2_PROMOTION_L2_128B, CU_TENSOR_MAP_FLOAT_OOB_FILL_NONE);
}

}

extern "C" void kernel_launch(void* const* d_in, const int* in_sizes, int n_in, void* d_out, int out_size) {
  const __nv_bfloat16* x = (const __nv_bfloat16*)d_in[0];
  const __nv_bfloat16* wqkv = (const __nv_bfloat16*)d_in[1];
  const __nv_bfloat16* wo = (const __nv_bfloat16*)d_in[2];
  const __nv_bfloat16* w1 = (const __nv_bfloat16*)d_in[4];
  const __nv_bfloat16* w3 = (const __nv_bfloat16*)d_in[5];
  const __nv_bfloat16* w2 = (const __nv_bfloat16*)d_in[6];

  void* fnp = nullptr; cudaDriverEntryPointQueryResult qr;
  cudaGetDriverEntryPoint("cuTensorMapEncodeTiled", &fnp, cudaEnableDefault, &qr);
  EncodeFn fn = (EncodeFn)fnp;
  void* sym;
  cudaGetSymbolAddress(&sym, g_scratch);
  uint8_t* scr = (uint8_t*)(((uintptr_t)sym + G_PAGE - 1) / G_PAGE * G_PAGE);

  Params P = {};
  { cuuint64_t d[3] = {DM, 2, SEQ / 2}, s[2] = {DM * 2, DM * 4}; cuuint32_t b[3] = {64, 1, 128}, b2[3] = {64, 1, 64};
    encode(fn, &P.map[M_XIN], x, 3, d, s, b); encode(fn, &P.map[M_XIN64], x, 3, d, s, b2);
    encode(fn, &P.map[M_OUT_LD], d_out, 3, d, s, b); encode(fn, &P.map[M_OUT_ST], d_out, 3, d, s, b2); }
  { cuuint64_t d[3] = {FF, 16, 128}, s[2] = {G_BLOCK, FF * 2}; cuuint32_t b[3] = {64, 1, 128}, b2[3] = {64, 1, 64};
    encode(fn, &P.map[M_H_LD], scr + G_H, 3, d, s, b); encode(fn, &P.map[M_H_ST], scr + G_H, 3, d, s, b2); }
  { const cuuint32_t b2[3] = {64, 64, 2}, b1[3] = {64, 64, 1};
    { cuuint64_t d[3] = {64, DM, 48}, s[2] = {3 * DM * 2, 128}; encode(fn, &P.map[M_WKV], wqkv, 3, d, s, b2); encode(fn, &P.map[M_WQ], wqkv, 3, d, s, b1); }
    { cuuint64_t d[3] = {64, DM, 16}, s[2] = {DM * 2, 128}; encode(fn, &P.map[M_WO], wo, 3, d, s, b1); }
    { cuuint64_t d[3] = {64, FF, 16}, s[2] = {DM * 2, 128}; encode(fn, &P.map[M_W2], w2, 3, d, s, b1); }
    { cuuint64_t d[3] = {64, DM, FF / 64}, s[2] = {FF * 2, 128};
      encode(fn, &P.map[M_W1], w1, 3, d, s, b2); encode(fn, &P.map[M_W3], w3, 3, d, s, b2);
      encode(fn, &P.map[M_W1H], w1, 3, d, s, b1); encode(fn, &P.map[M_W3H], w3, 3, d, s, b1); }
  }
  P.scratch = scr; P.x = x; P.wqkv = wqkv; P.wo = wo; P.w2 = w2;
  int dev = 0, sms = 0;
  cudaGetDevice(&dev);
  cudaDeviceGetAttribute(&sms, cudaDevAttrMultiProcessorCount, dev);
  P.use_smid = (sms == 132);
  cudaFuncSetAttribute(fused_kernel, cudaFuncAttributeMaxDynamicSharedMemorySize, SM_ALLOC);
  fused_kernel<<<132, 384, SM_ALLOC>>>(P);
}
```

```cpp
#include <cuda_runtime.h>
#include <cuda_bf16.h>
#include <cuda.h>
#include <stdint.h>
#include <math.h>

namespace {

constexpr int SEQ = 2048, DM = 1024, FF = 3584;
constexpr float LN_EPS = 1e-5f;
constexpr float LOG2E = 1.4426950408889634f;

#define G_SKEW 4096
constexpr uint32_t G_PAGE = 2u << 20, G_BLOCK = G_PAGE + G_SKEW;
constexpr uint32_t G_H = 0;
constexpr uint32_t G_O = G_H + 128 * FF * 2;
constexpr uint32_t G_STATS = G_O + 128 * DM * 2;
constexpr uint32_t G_FLAGS = G_STATS + 4 * 128 * 64;
static_assert(G_FLAGS + 4096 + 15 * G_SKEW <= G_PAGE, "");
constexpr uint32_t G_HALO = 16 * G_PAGE;
constexpr uint32_t G_CS = G_HALO + 2 * 16 * 8 * 4096;
constexpr uint32_t G_EPOCH = G_CS + (3 * DM + 2 * FF) * 16;
__device__ __align__(1024) uint8_t g_scratch[18 * G_PAGE];

enum { M_XIN, M_XIN64, M_H_LD, M_H_ST, M_OUT_LD, M_OUT_ST, M_WKV, M_WQ, M_WO, M_W1, M_W3, M_W1H, M_W3H, M_W2, M_COUNT };
struct alignas(64) Params {
  CUtensorMap map[M_COUNT];
  uint8_t* scratch;
  const __nv_bfloat16* x;
  const __nv_bfloat16* wqkv;
  const __nv_bfloat16* wo;
  const __nv_bfloat16* w2;
  int use_smid;
};

constexpr uint32_t PAGE = 16384, NPAGE = 12;
constexpr uint32_t SM_STAGE = NPAGE * PAGE;
constexpr uint32_t SM_BAR = SM_STAGE + 2 * PAGE;
constexpr uint32_t SM_CS = SM_BAR + 256;
constexpr uint32_t SM_TOTAL = SM_CS + 1536;
constexpr uint32_t SM_ALLOC = SM_TOTAL;
static_assert(SM_ALLOC <= 232448, "shared memory");
constexpr uint32_t BAR_FULL = SM_BAR, BAR_EMPTY = SM_BAR + 64, BAR_SFULL = SM_BAR + 128;
constexpr uint32_t BAR_XFULL = SM_BAR + 160, BAR_CSE = SM_BAR + 168;
constexpr uint32_t BAR_SEMPTY = SM_BAR + 176, BAR_CSF = SM_BAR + 184, BAR_XIN = SM_BAR + 200;
constexpr uint32_t BAR_CLR = SM_BAR + 240, BAR_TAG = SM_BAR + 216, SM_ROLE = SM_BAR + 224, SM_TAG = SM_BAR + 228, SM_SEEN = SM_BAR + 232;
enum { EV_XA, EV_XA2, EV_H0, EV_H3, EV_H1, EV_H2, EV_XB, EV_XB2, EV_N };

struct Sched { uint32_t pat[16]; uint32_t page0[16]; bool ok; };
constexpr int seg_steps(int seg) { return seg == 0 || seg == 3 ? 18 : seg == 1 || seg == 4 ? 14 : seg == 2 ? 7 : seg == 7 ? 24 : 32; }
constexpr int step_pages(int seg, int i) {
  return seg == 0 || seg == 3 ? (i < 2 ? 2 : i < 4 ? 1 : 3) : seg == 5 || (seg == 2 && i >= 1 && i <= 4) ? 3 : 2;
}
constexpr Sched make_sched() {
  Sched s = {};
  int owner[NPAGE] = {-1, -1, -1, -1, -1, -1, -1, -1, -1, -1, -1, -1};
  int n = 0, tail = 0, page = 0;
  s.ok = true;
  for (int sg = 0; sg < 16; sg++) {
    const int seg = sg % 8;
    s.page0[sg] = page;
    for (int i = 0; i < seg_steps(seg); i++) {
      const int p = step_pages(seg, i);
      if ((seg == 2 && i == 6) || (seg == 4 && i == 8) || (seg == 7 && i == 0)) page = (page + 2) % NPAGE;
      if (page + p > (int)NPAGE) { s.ok = false; return s; }
      int need = n - 8;
      for (int q = 0; q < p; q++) { if (owner[page + q] > need) need = owner[page + q]; owner[page + q] = n; }
      int nw = need + 1 - tail; if (nw < 0) nw = 0;
      tail += nw;
      if (i < 16) s.pat[sg] |= (uint32_t)nw << (2 * i); else if (nw != 1) s.ok = false;
      if (nw > 3) s.ok = false;
      page = (page + p) % NPAGE; n++;
    }
  }
  for (int sg = 0; sg < 8; sg++) if (s.page0[sg] != s.page0[sg + 8] || (sg && s.pat[sg] != s.pat[sg + 8])) s.ok = false;
  return s;
}
constexpr Sched SCHED = make_sched();
static_assert(SCHED.ok && SCHED.page0[0] == 0 && SCHED.page0[3] == 0 && SCHED.page0[5] == 6 && SCHED.page0[2] == 4 && SCHED.page0[7] == 10 && (SCHED.pat[0] & 0xfff) == 0, "ring schedule");
template <int SEG> struct Pat { static constexpr uint32_t v = SCHED.pat[SEG]; };

constexpr int H_ROWS = 16;
#define TAIL_LAG 3
__device__ __forceinline__ uint32_t smem_u32(const void* p) { return (uint32_t)__cvta_generic_to_shared(p); }
__device__ __forceinline__ void mbar_init(uint32_t bar, uint32_t cnt) { asm volatile("mbarrier.init.shared::cta.b64 [%0], %1;" :: "r"(bar), "r"(cnt)); }
__device__ __forceinline__ void mbar_expect_tx(uint32_t bar, uint32_t bytes) { asm volatile("mbarrier.arrive.expect_tx.shared::cta.b64 _, [%0], %1;" :: "r"(bar), "r"(bytes) : "memory"); }
__device__ __forceinline__ void mbar_arrive(uint32_t bar) { asm volatile("mbarrier.arrive.shared::cta.b64 _, [%0];" :: "r"(bar) : "memory"); }
__device__ __forceinline__ void mbar_wait(uint32_t bar, uint32_t parity) {
  asm volatile("{\n.reg .pred p;\n.reg .u32 n;\nmov.u32 n, 0;\nLAB_WAIT:\n"
               "mbarrier.try_wait.parity.shared::cta.b64 p, [%0], %1;\n@p bra LAB_DONE;\n"
               "add.u32 n, n, 1;\nsetp.lt.u32 p, n, 4194304;\n@p bra LAB_WAIT;\ntrap;\nLAB_DONE:\n}" :: "r"(bar), "r"(parity) : "memory");
}
__device__ __forceinline__ void mbar_wait_fast(uint32_t bar, uint32_t parity) {
  asm volatile("{\n.reg .pred p;\nLAB_WAIT:\nmbarrier.try_wait.parity.shared::cta.b64 p, [%0], %1;\n@!p bra LAB_WAIT;\n}" :: "r"(bar), "r"(parity) : "memory");
}
__device__ __forceinline__ void spin_check(uint32_t n) { asm volatile("{\n.reg .pred p;\nsetp.ge.u32 p, %0, 4194304;\n@p st.volatile.global.u32 [%1], %0;\n}" :: "r"(n), "l"(0ull)); }
__device__ __forceinline__ void tma_ld3(uint32_t dst, const CUtensorMap* m, uint32_t bar, int c0, int c1, int c2) {
  asm volatile("cp.async.bulk.tensor.3d.shared::cluster.global.mbarrier::complete_tx::bytes [%0], [%1, {%3, %4, %5}], [%2];" :: "r"(dst), "l"(m), "r"(bar), "r"(c0), "r"(c1), "r"(c2) : "memory");
}
__device__ __forceinline__ void tma_ld3_mc(uint32_t dst, const CUtensorMap* m, uint32_t bar, int c0, int c1, int c2, uint16_t mask) {
  asm volatile("cp.async.bulk.tensor.3d.shared::cluster.global.mbarrier::complete_tx::bytes.multicast::cluster [%0], [%1, {%3, %4, %5}], [%2], %6;"
               :: "r"(dst), "l"(m), "r"(bar), "r"(c0), "r"(c1), "r"(c2), "h"(mask) : "memory");
}
__device__ __forceinline__ uint32_t mapa(uint32_t addr, uint32_t cta) { uint32_t r; asm("mapa.shared::cluster.u32 %0, %1, %2;" : "=r"(r) : "r"(addr), "r"(cta)); return r; }
__device__ __forceinline__ void mbar_arrive_cluster(uint32_t bar) { asm volatile("mbarrier.arrive.shared::cluster.b64 _, [%0];" :: "r"(bar) : "memory"); }
__device__ __forceinline__ void tma_st3(const CUtensorMap* m, uint32_t src, int c0, int c1, int c2) {
  asm volatile("cp.async.bulk.tensor.3d.global.shared::cta.bulk_group [%0, {%2, %3, %4}], [%1];" :: "l"(m), "r"(src), "r"(c0), "r"(c1), "r"(c2) : "memory");
}
__device__ __forceinline__ void bulk_commit() { asm volatile("cp.async.bulk.commit_group;" ::: "memory"); }
template <int N> __device__ __forceinline__ void bulk_wait() { asm volatile("cp.async.bulk.wait_group %0;" :: "n"(N) : "memory"); }
__device__ __forceinline__ void fence_async_smem() { asm volatile("fence.proxy.async.shared::cta;" ::: "memory"); }
__device__ __forceinline__ void fence_async_global() { asm volatile("fence.proxy.async.global;" ::: "memory"); }
__device__ __forceinline__ bool elect_one() { uint32_t p; asm volatile("{\n.reg .pred P;\nelect.sync _|P, 0xffffffff;\nselp.u32 %0, 1, 0, P;\n}" : "=r"(p)); return p; }
__device__ __forceinline__ void prefetch_map(const CUtensorMap* m) { asm volatile("prefetch.tensormap [%0];" :: "l"(m) : "memory"); }
__device__ __forceinline__ void prefetch_l2(const void* p, uint32_t bytes) { asm volatile("cp.async.bulk.prefetch.L2.global [%0], %1;" :: "l"(p), "r"(bytes) : "memory"); }
__device__ __forceinline__ void wgmma_fence() { asm volatile("wgmma.fence.sync.aligned;" ::: "memory"); }
__device__ __forceinline__ void wgmma_commit() { asm volatile("wgmma.commit_group.sync.aligned;" ::: "memory"); }
template <int N> __device__ __forceinline__ void wgmma_wait() { asm volatile("wgmma.wait_group.sync.aligned %0;" :: "n"(N) : "memory"); }
__device__ __forceinline__ uint32_t desc_lo(uint32_t addr, uint32_t lbo) { return ((addr & 0x3FFFF) >> 4) | ((lbo >> 4) << 16); }
__device__ __forceinline__ uint64_t desc64(uint32_t lo) { uint64_t r; asm("mov.b64 %0, {%1, %2};" : "=l"(r) : "r"(lo), "r"(0x40000040u)); return r; }
__device__ __forceinline__ void bar_sync(int id, int n) { asm volatile("bar.sync %0, %1;" :: "r"(id), "r"(n) : "memory"); }
__device__ __forceinline__ uint32_t pack_bf16(float lo, float hi) { uint32_t r; asm("cvt.rn.bf16x2.f32 %0, %1, %2;" : "=r"(r) : "f"(hi), "f"(lo)); return r; }
__device__ __forceinline__ float bf_lo(uint32_t v) { return __uint_as_float(v << 16); }
__device__ __forceinline__ float bf_hi(uint32_t v) { return __uint_as_float(v & 0xffff0000u); }
__device__ __forceinline__ float ex2(float x) { float r; asm("ex2.approx.ftz.f32 %0, %1;" : "=f"(r) : "f"(x)); return r; }
__device__ __forceinline__ float rcp(float x) { float r; asm("rcp.approx.ftz.f32 %0, %1;" : "=f"(r) : "f"(x)); return r; }
__device__ __forceinline__ void stsm4(uint32_t a, uint32_t r0, uint32_t r1, uint32_t r2, uint32_t r3) {
  asm volatile("stmatrix.sync.aligned.m8n8.x4.shared.b16 [%0], {%1, %2, %3, %4};" :: "r"(a), "r"(r0), "r"(r1), "r"(r2), "r"(r3) : "memory");
}
__device__ __forceinline__ void ldsm4(uint32_t a, uint32_t& r0, uint32_t& r1, uint32_t& r2, uint32_t& r3) {
  asm volatile("ldmatrix.sync.aligned.m8n8.x4.shared.b16 {%0, %1, %2, %3}, [%4];" : "=r"(r0), "=r"(r1), "=r"(r2), "=r"(r3) : "r"(a) : "memory");
}
__device__ __forceinline__ uint32_t movm(uint32_t v) { uint32_t r; asm volatile("movmatrix.sync.aligned.m8n8.trans.b16 %0, %1;" : "=r"(r) : "r"(v)); return r; }
__device__ __forceinline__ void sts128(uint32_t a, uint32_t r0, uint32_t r1, uint32_t r2, uint32_t r3) {
  asm volatile("st.shared.v4.b32 [%0], {%1, %2, %3, %4};" :: "r"(a), "r"(r0), "r"(r1), "r"(r2), "r"(r3) : "memory");
}
__device__ __forceinline__ void lds128(uint32_t a, uint32_t& r0, uint32_t& r1, uint32_t& r2, uint32_t& r3) {
  asm volatile("ld.shared.v4.b32 {%0, %1, %2, %3}, [%4];" : "=r"(r0), "=r"(r1), "=r"(r2), "=r"(r3) : "r"(a) : "memory");
}
__device__ __forceinline__ uint32_t add_bf16x2(uint32_t a, uint32_t b) { uint32_t r; asm("add.rn.bf16x2 %0, %1, %2;" : "=r"(r) : "r"(a), "r"(b)); return r; }
__device__ __forceinline__ void sts32f(uint32_t a, float v) { asm volatile("st.shared.f32 [%0], %1;" :: "r"(a), "f"(v) : "memory"); }
__device__ __forceinline__ void mma16816(float (&d)[4], uint32_t a0, uint32_t a1, uint32_t a2, uint32_t a3, uint32_t b0, uint32_t b1, const float (&c)[4]) {
  asm("mma.sync.aligned.m16n8k16.row.col.f32.bf16.bf16.f32 {%0, %1, %2, %3}, {%4, %5, %6, %7}, {%8, %9}, {%10, %11, %12, %13};"
      : "=f"(d[0]), "=f"(d[1]), "=f"(d[2]), "=f"(d[3]) : "r"(a0), "r"(a1), "r"(a2), "r"(a3), "r"(b0), "r"(b1), "f"(c[0]), "f"(c[1]), "f"(c[2]), "f"(c[3]));
}
__device__ __forceinline__ void mma1688(float (&d)[4], uint32_t a0, uint32_t a1, uint32_t b0, const float (&c)[4]) {
  asm("mma.sync.aligned.m16n8k8.row.col.f32.bf16.bf16.f32 {%0, %1, %2, %3}, {%4, %5}, {%6}, {%7, %8, %9, %10};"
      : "=f"(d[0]), "=f"(d[1]), "=f"(d[2]), "=f"(d[3]) : "r"(a0), "r"(a1), "r"(b0), "f"(c[0]), "f"(c[1]), "f"(c[2]), "f"(c[3]));
}
__device__ __forceinline__ void mma16816z(float (&d)[4], uint32_t a0, uint32_t a1, uint32_t a2, uint32_t a3, uint32_t b0, uint32_t b1) {
  asm("mma.sync.aligned.m16n8k16.row.col.f32.bf16.bf16.f32 {%0, %1, %2, %3}, {%4, %5, %6, %7}, {%8, %9}, {0f00000000, 0f00000000, 0f00000000, 0f00000000};"
      : "=f"(d[0]), "=f"(d[1]), "=f"(d[2]), "=f"(d[3]) : "r"(a0), "r"(a1), "r"(a2), "r"(a3), "r"(b0), "r"(b1));
}
__device__ __forceinline__ void mma1688z(float (&d)[4], uint32_t a0, uint32_t a1, uint32_t b0) {
  asm("mma.sync.aligned.m16n8k8.row.col.f32.bf16.bf16.f32 {%0, %1, %2, %3}, {%4, %5}, {%6}, {0f00000000, 0f00000000, 0f00000000, 0f00000000};"
      : "=f"(d[0]), "=f"(d[1]), "=f"(d[2]), "=f"(d[3]) : "r"(a0), "r"(a1), "r"(b0));
}
__device__ __forceinline__ uint32_t bar_sync_zero(int id, int n) {
  uint32_t r;
  asm volatile("{\n.reg .pred p;\nsetp.eq.u32 p, %1, 0;\nbarrier.cta.red.popc.aligned.u32 %0, %1, %2, p;\n}" : "=r"(r) : "r"(id), "r"(n) : "memory");
  return r;
}
__device__ __forceinline__ uint32_t late_zero(uint32_t zm) { uint32_t c; asm volatile("mov.u32 %0, %%clock;" : "=r"(c) :: "memory"); return c & zm; }
__device__ __forceinline__ void st_b128(uint4* p, uint32_t a, uint32_t b, uint32_t c, uint32_t d) {
  asm volatile("{\n.reg .b128 t;\n.reg .b64 lo, hi;\nmov.b64 lo, {%0, %1};\nmov.b64 hi, {%2, %3};\nmov.b128 t, {lo, hi};\nst.relaxed.gpu.global.b128 [%4], t;\n}"
               :: "r"(a), "r"(b), "r"(c), "r"(d), "l"(p) : "memory");
}
__device__ __forceinline__ uint32_t pkt_head(uint32_t a) { return a ? a : 0x8000u; }
__device__ __forceinline__ void gen_store(uint4* p, uint32_t a, uint32_t b, uint32_t c, uint32_t d) {
  asm volatile("{\n.reg .b128 t;\n.reg .b64 lo, hi;\nmov.b64 lo, {%0, %1};\nmov.b64 hi, {%2, %3};\nmov.b128 t, {lo, hi};\nst.relaxed.gpu.b128 [%4], t;\n}"
               :: "r"(a), "r"(b), "r"(c), "r"(d), "l"(p) : "memory");
}
__device__ __forceinline__ void gen_load(const uint4* p, uint32_t* v) {
  asm volatile("{\n.reg .b128 t;\n.reg .b64 lo, hi;\nld.relaxed.gpu.b128 t, [%4];\nmov.b128 {lo, hi}, t;\nmov.b64 {%0, %1}, lo;\nmov.b64 {%2, %3}, hi;\n}"
               : "=r"(v[0]), "=r"(v[1]), "=r"(v[2]), "=r"(v[3]) : "l"(p) : "memory");
}
__device__ __forceinline__ void pkt_load(const uint4* p, uint32_t* v) {
  asm volatile("{\n.reg .b128 t;\n.reg .b64 lo, hi;\nld.relaxed.gpu.global.b128 t, [%4];\nmov.b128 {lo, hi}, t;\nmov.b64 {%0, %1}, lo;\nmov.b64 {%2, %3}, hi;\n}"
               : "=r"(v[0]), "=r"(v[1]), "=r"(v[2]), "=r"(v[3]) : "l"(p) : "memory");
}
__device__ __forceinline__ uint32_t ld_relaxed(const uint32_t* p) { uint32_t v; asm volatile("ld.relaxed.gpu.global.u32 %0, [%1];" : "=r"(v) : "l"(p) : "memory"); return v; }
__device__ __forceinline__ uint4 ld_relaxed4(const void* p) { uint4 v; asm volatile("ld.relaxed.gpu.global.v4.u32 {%0, %1, %2, %3}, [%4];" : "=r"(v.x), "=r"(v.y), "=r"(v.z), "=r"(v.w) : "l"(p) : "memory"); return v; }
__device__ __forceinline__ void st_relaxed(uint32_t* p, uint32_t v) { asm volatile("st.relaxed.gpu.global.u32 [%0], %1;" :: "l"(p), "r"(v) : "memory"); }
__device__ __forceinline__ void st_relaxed2(void* p, uint32_t a, uint32_t b) { asm volatile("st.relaxed.gpu.global.v2.u32 [%0], {%1, %2};" :: "l"(p), "r"(a), "r"(b) : "memory"); }
__device__ __forceinline__ void red_release(uint32_t* p, uint32_t v) { asm volatile("red.release.gpu.global.add.u32 [%0], %1;" :: "l"(p), "r"(v) : "memory"); }
__device__ __forceinline__ uint32_t tagf(float v, uint32_t tag) { return (__float_as_uint(v) & ~15u) | (tag & 15u); }
__device__ __forceinline__ bool tag_ok4(const uint4& v, uint32_t tag) { return (((v.x ^ tag) | (v.y ^ tag) | (v.z ^ tag) | (v.w ^ tag)) & 15u) == 0; }
__device__ __forceinline__ float untag(uint32_t v) { return __uint_as_float(v & ~15u); }
template <typename T> __device__ __forceinline__ T* ptr_add(T* p, uint32_t bytes) {
  uint64_t r;
  asm("{\n.reg .u32 lo, hi;\nmov.b64 {lo, hi}, %1;\nadd.cc.u32 lo, lo, %2;\naddc.u32 hi, hi, 0;\nmov.b64 %0, {lo, hi};\n}" : "=l"(r) : "l"(p), "r"(bytes));
  return (T*)r;
}
#define TL(who, slot) do {} while (0)
#define TLC(slot) do {} while (0)
#define TLE(slot) do {} while (0)
#define ST(who, n) do {} while (0)
#define AP(i) do {} while (0)
#define SP(v) do {} while (0)
#define TLG(slot) do {} while (0)
#define STA() do {} while (0)
#define STB(n) do {} while (0)

__device__ __forceinline__ void wgmma_n128(float (&d)[64], uint64_t da, uint64_t db, int scale_d) {
  asm volatile("{\n.reg .pred p;\nsetp.ne.b32 p, %66, 0;\n"
    "wgmma.mma_async.sync.aligned.m64n128k16.f32.bf16.bf16 "
    "{%0, %1, %2, %3, %4, %5, %6, %7, %8, %9, %10, %11, %12, %13, %14, %15, "
    "%16, %17, %18, %19, %20, %21, %22, %23, %24, %25, %26, %27, %28, %29, %30, %31, "
    "%32, %33, %34, %35, %36, %37, %38, %39, %40, %41, %42, %43, %44, %45, %46, %47, "
    "%48, %49, %50, %51, %52, %53, %54, %55, %56, %57, %58, %59, %60, %61, %62, %63}, "
    "%64, %65, p, 1, 1, 0, 1;\n}\n"
    : "+f"(d[0]), "+f"(d[1]), "+f"(d[2]), "+f"(d[3]), "+f"(d[4]), "+f"(d[5]), "+f"(d[6]), "+f"(d[7]),
      "+f"(d[8]), "+f"(d[9]), "+f"(d[10]), "+f"(d[11]), "+f"(d[12]), "+f"(d[13]), "+f"(d[14]), "+f"(d[15]),
      "+f"(d[16]), "+f"(d[17]), "+f"(d[18]), "+f"(d[19]), "+f"(d[20]), "+f"(d[21]), "+f"(d[22]), "+f"(d[23]),
      "+f"(d[24]), "+f"(d[25]), "+f"(d[26]), "+f"(d[27]), "+f"(d[28]), "+f"(d[29]), "+f"(d[30]), "+f"(d[31]),
      "+f"(d[32]), "+f"(d[33]), "+f"(d[34]), "+f"(d[35]), "+f"(d[36]), "+f"(d[37]), "+f"(d[38]), "+f"(d[39]),
      "+f"(d[40]), "+f"(d[41]), "+f"(d[42]), "+f"(d[43]), "+f"(d[44]), "+f"(d[45]), "+f"(d[46]), "+f"(d[47]),
      "+f"(d[48]), "+f"(d[49]), "+f"(d[50]), "+f"(d[51]), "+f"(d[52]), "+f"(d[53]), "+f"(d[54]), "+f"(d[55]),
      "+f"(d[56]), "+f"(d[57]), "+f"(d[58]), "+f"(d[59]), "+f"(d[60]), "+f"(d[61]), "+f"(d[62]), "+f"(d[63])
    : "l"(da), "l"(db), "r"(scale_d));
}
__device__ __forceinline__ void wgmma_n256(float (&d)[128], uint64_t da, uint64_t db, int scale_d) {
  asm volatile("{\n.reg .pred p;\nsetp.ne.b32 p, %130, 0;\n"
    "wgmma.mma_async.sync.aligned.m64n256k16.f32.bf16.bf16 "
    "{%0, %1, %2, %3, %4, %5, %6, %7, %8, %9, %10, %11, %12, %13, %14, %15, "
    "%16, %17, %18, %19, %20, %21, %22, %23, %24, %25, %26, %27, %28, %29, %30, %31, "
    "%32, %33, %34, %35, %36, %37, %38, %39, %40, %41, %42, %43, %44, %45, %46, %47, "
    "%48, %49, %50, %51, %52, %53, %54, %55, %56, %57, %58, %59, %60, %61, %62, %63, "
    "%64, %65, %66, %67, %68, %69, %70, %71, %72, %73, %74, %75, %76, %77, %78, %79, "
    "%80, %81, %82, %83, %84, %85, %86, %87, %88, %89, %90, %91, %92, %93, %94, %95, "
    "%96, %97, %98, %99, %100, %101, %102, %103, %104, %105, %106, %107, %108, %109, %110, %111, "
    "%112, %113, %114, %115, %116, %117, %118, %119, %120, %121, %122, %123, %124, %125, %126, %127}, "
    "%128, %129, p, 1, 1, 0, 1;\n}\n"
    : "+f"(d[0]), "+f"(d[1]), "+f"(d[2]), "+f"(d[3]), "+f"(d[4]), "+f"(d[5]), "+f"(d[6]), "+f"(d[7]),
      "+f"(d[8]), "+f"(d[9]), "+f"(d[10]), "+f"(d[11]), "+f"(d[12]), "+f"(d[13]), "+f"(d[14]), "+f"(d[15]),
      "+f"(d[16]), "+f"(d[17]), "+f"(d[18]), "+f"(d[19]), "+f"(d[20]), "+f"(d[21]), "+f"(d[22]), "+f"(d[23]),
      "+f"(d[24]), "+f"(d[25]), "+f"(d[26]), "+f"(d[27]), "+f"(d[28]), "+f"(d[29]), "+f"(d[30]), "+f"(d[31]),
      "+f"(d[32]), "+f"(d[33]), "+f"(d[34]), "+f"(d[35]), "+f"(d[36]), "+f"(d[37]), "+f"(d[38]), "+f"(d[39]),
      "+f"(d[40]), "+f"(d[41]), "+f"(d[42]), "+f"(d[43]), "+f"(d[44]), "+f"(d[45]), "+f"(d[46]), "+f"(d[47]),
      "+f"(d[48]), "+f"(d[49]), "+f"(d[50]), "+f"(d[51]), "+f"(d[52]), "+f"(d[53]), "+f"(d[54]), "+f"(d[55]),
      "+f"(d[56]), "+f"(d[57]), "+f"(d[58]), "+f"(d[59]), "+f"(d[60]), "+f"(d[61]), "+f"(d[62]), "+f"(d[63]),
      "+f"(d[64]), "+f"(d[65]), "+f"(d[66]), "+f"(d[67]), "+f"(d[68]), "+f"(d[69]), "+f"(d[70]), "+f"(d[71]),
      "+f"(d[72]), "+f"(d[73]), "+f"(d[74]), "+f"(d[75]), "+f"(d[76]), "+f"(d[77]), "+f"(d[78]), "+f"(d[79]),
      "+f"(d[80]), "+f"(d[81]), "+f"(d[82]), "+f"(d[83]), "+f"(d[84]), "+f"(d[85]), "+f"(d[86]), "+f"(d[87]),
      "+f"(d[88]), "+f"(d[89]), "+f"(d[90]), "+f"(d[91]), "+f"(d[92]), "+f"(d[93]), "+f"(d[94]), "+f"(d[95]),
      "+f"(d[96]), "+f"(d[97]), "+f"(d[98]), "+f"(d[99]), "+f"(d[100]), "+f"(d[101]), "+f"(d[102]), "+f"(d[103]),
      "+f"(d[104]), "+f"(d[105]), "+f"(d[106]), "+f"(d[107]), "+f"(d[108]), "+f"(d[109]), "+f"(d[110]), "+f"(d[111]),
      "+f"(d[112]), "+f"(d[113]), "+f"(d[114]), "+f"(d[115]), "+f"(d[116]), "+f"(d[117]), "+f"(d[118]), "+f"(d[119]),
      "+f"(d[120]), "+f"(d[121]), "+f"(d[122]), "+f"(d[123]), "+f"(d[124]), "+f"(d[125]), "+f"(d[126]), "+f"(d[127])
    : "l"(da), "l"(db), "r"(scale_d));
}
__device__ __forceinline__ void wgmma_rs_n128(float (&d)[64], const uint32_t* a, uint64_t db, int scale_d) {
  asm volatile("{\n.reg .pred p;\nsetp.ne.b32 p, %69, 0;\n"
    "wgmma.mma_async.sync.aligned.m64n128k16.f32.bf16.bf16 "
    "{%0, %1, %2, %3, %4, %5, %6, %7, %8, %9, %10, %11, %12, %13, %14, %15, "
    "%16, %17, %18, %19, %20, %21, %22, %23, %24, %25, %26, %27, %28, %29, %30, %31, "
    "%32, %33, %34, %35, %36, %37, %38, %39, %40, %41, %42, %43, %44, %45, %46, %47, "
    "%48, %49, %50, %51, %52, %53, %54, %55, %56, %57, %58, %59, %60, %61, %62, %63}, "
    "{%64, %65, %66, %67}, %68, p, 1, 1, 1;\n}\n"
    : "+f"(d[0]), "+f"(d[1]), "+f"(d[2]), "+f"(d[3]), "+f"(d[4]), "+f"(d[5]), "+f"(d[6]), "+f"(d[7]),
      "+f"(d[8]), "+f"(d[9]), "+f"(d[10]), "+f"(d[11]), "+f"(d[12]), "+f"(d[13]), "+f"(d[14]), "+f"(d[15]),
      "+f"(d[16]), "+f"(d[17]), "+f"(d[18]), "+f"(d[19]), "+f"(d[20]), "+f"(d[21]), "+f"(d[22]), "+f"(d[23]),
      "+f"(d[24]), "+f"(d[25]), "+f"(d[26]), "+f"(d[27]), "+f"(d[28]), "+f"(d[29]), "+f"(d[30]), "+f"(d[31]),
      "+f"(d[32]), "+f"(d[33]), "+f"(d[34]), "+f"(d[35]), "+f"(d[36]), "+f"(d[37]), "+f"(d[38]), "+f"(d[39]),
      "+f"(d[40]), "+f"(d[41]), "+f"(d[42]), "+f"(d[43]), "+f"(d[44]), "+f"(d[45]), "+f"(d[46]), "+f"(d[47]),
      "+f"(d[48]), "+f"(d[49]), "+f"(d[50]), "+f"(d[51]), "+f"(d[52]), "+f"(d[53]), "+f"(d[54]), "+f"(d[55]),
      "+f"(d[56]), "+f"(d[57]), "+f"(d[58]), "+f"(d[59]), "+f"(d[60]), "+f"(d[61]), "+f"(d[62]), "+f"(d[63])
    : "r"(a[0]), "r"(a[1]), "r"(a[2]), "r"(a[3]), "l"(db), "r"(scale_d));
}
__device__ __forceinline__ void wgmma_n64(float* d, uint64_t da, uint64_t db, int scale_d) {
  asm volatile("{\n.reg .pred p;\nsetp.ne.b32 p, %34, 0;\n"
    "wgmma.mma_async.sync.aligned.m64n64k16.f32.bf16.bf16 "
    "{%0, %1, %2, %3, %4, %5, %6, %7, %8, %9, %10, %11, %12, %13, %14, %15, "
    "%16, %17, %18, %19, %20, %21, %22, %23, %24, %25, %26, %27, %28, %29, %30, %31}, "
    "%32, %33, p, 1, 1, 0, 1;\n}\n"
    : "+f"(d[0]), "+f"(d[1]), "+f"(d[2]), "+f"(d[3]), "+f"(d[4]), "+f"(d[5]), "+f"(d[6]), "+f"(d[7]),
      "+f"(d[8]), "+f"(d[9]), "+f"(d[10]), "+f"(d[11]), "+f"(d[12]), "+f"(d[13]), "+f"(d[14]), "+f"(d[15]),
      "+f"(d[16]), "+f"(d[17]), "+f"(d[18]), "+f"(d[19]), "+f"(d[20]), "+f"(d[21]), "+f"(d[22]), "+f"(d[23]),
      "+f"(d[24]), "+f"(d[25]), "+f"(d[26]), "+f"(d[27]), "+f"(d[28]), "+f"(d[29]), "+f"(d[30]), "+f"(d[31])
    : "l"(da), "l"(db), "r"(scale_d));
}
__device__ __forceinline__ void wgmma_rs_n64(float* d, const uint32_t* a, uint64_t db, int scale_d) {
  asm volatile("{\n.reg .pred p;\nsetp.ne.b32 p, %37, 0;\n"
    "wgmma.mma_async.sync.aligned.m64n64k16.f32.bf16.bf16 "
    "{%0, %1, %2, %3, %4, %5, %6, %7, %8, %9, %10, %11, %12, %13, %14, %15, "
    "%16, %17, %18, %19, %20, %21, %22, %23, %24, %25, %26, %27, %28, %29, %30, %31}, "
    "{%32, %33, %34, %35}, %36, p, 1, 1, 1;\n}\n"
    : "+f"(d[0]), "+f"(d[1]), "+f"(d[2]), "+f"(d[3]), "+f"(d[4]), "+f"(d[5]), "+f"(d[6]), "+f"(d[7]),
      "+f"(d[8]), "+f"(d[9]), "+f"(d[10]), "+f"(d[11]), "+f"(d[12]), "+f"(d[13]), "+f"(d[14]), "+f"(d[15]),
      "+f"(d[16]), "+f"(d[17]), "+f"(d[18]), "+f"(d[19]), "+f"(d[20]), "+f"(d[21]), "+f"(d[22]), "+f"(d[23]),
      "+f"(d[24]), "+f"(d[25]), "+f"(d[26]), "+f"(d[27]), "+f"(d[28]), "+f"(d[29]), "+f"(d[30]), "+f"(d[31])
    : "r"(a[0]), "r"(a[1]), "r"(a[2]), "r"(a[3]), "l"(db), "r"(scale_d));
}

template <int BN> __device__ __forceinline__ void wgmma(float (&d)[BN / 2], uint64_t a, uint64_t b, int s) {
  if constexpr (BN == 128) wgmma_n128(d, a, b, s);
  else wgmma_n256(d, a, b, s);
}

template <int N> __device__ __forceinline__ void acc_fence(float* a) {
#pragma unroll
  for (int i = 0; i < N; i++) asm volatile("" : "+f"(a[i]) :: "memory");
}

#define SELECT8(a, f) do { \
  if ((a) & 4) { if ((a) & 2) { if ((a) & 1) f(7); else f(6); } else { if ((a) & 1) f(5); else f(4); } } \
  else { if ((a) & 2) { if ((a) & 1) f(3); else f(2); } else { if ((a) & 1) f(1); else f(0); } } } while (0)
__device__ __forceinline__ uint32_t lane_now() { uint32_t l; asm volatile("mov.u32 %0, %%laneid;" : "=r"(l)); return l; }

struct Prod {
  uint32_t sb, n, tail, addr, pat, ready;
  uint32_t rank, flip; uint16_t mask;
  __device__ __forceinline__ void load_b(uint32_t dst, uint32_t half, const CUtensorMap* m, uint32_t mstep, uint32_t fb, int k, int ch, int cstep) {
    uint32_t h = rank;
    do { tma_ld3_mc(dst + h * half, ptr_add(m, h * mstep), fb, 0, k * 64, ch + h * cstep, mask); h ^= flip; } while (h != rank);
  }
  __device__ __forceinline__ void load_wide(const Params& P, int ffn, uint32_t dst, uint32_t fb, int k, int ch) {
    load_b(dst, PAGE, &P.map[ffn ? M_W1 : M_WKV], ffn ? 128 : 0, fb, k, ffn ? ch : ch + 16, ffn ? 0 : 16);
  }
  __device__ __forceinline__ void load_narrow(const Params& P, int ffn, uint32_t dst, uint32_t fb, int k, int j) {
    load_b(dst, 8192, &P.map[ffn ? M_W1H : M_WQ], ffn ? 128 : 0, fb, k, ffn ? 48 + j : 2 * j, ffn ? 0 : 1);
  }
  __device__ __forceinline__ void finish() {
#pragma unroll 1
    for (; tail < n; tail++) mbar_wait(sb + BAR_EMPTY + ((tail & 7) << 3), (tail >> 3) & 1);
  }
  template <int PAGES> __device__ __forceinline__ uint32_t acquire(uint32_t& fb) { return acquire_n(PAGES, fb); }
  __device__ __forceinline__ uint32_t acquire_n(uint32_t PAGES, uint32_t& fb) {
    uint32_t nw = pat & 3; pat = (pat >> 2) | 0x40000000u;
#pragma unroll 1
    for (; nw; nw--) { mbar_wait(sb + BAR_EMPTY + ((tail & 7) << 3), (tail >> 3) & 1); tail++; }
    ST(4, n);
    fb = sb + BAR_FULL + ((n & 7) << 3);
    mbar_expect_tx(fb, PAGES * PAGE);
    const uint32_t a = sb + addr;
    addr += PAGES * PAGE; if (addr >= NPAGE * PAGE) addr = 0;
    n++;
    return a;
  }
  const uint32_t* flag; uint32_t base, seen;
  __device__ __forceinline__ void acquire_fence() { asm volatile("fence.acquire.gpu;" ::: "memory"); fence_async_global(); }
  __device__ __forceinline__ void next() {
    uint32_t v, spins = 0;
    seen++;
    do { asm volatile("ld.acquire.cta.shared.u32 %0, [%1];" : "=r"(v) : "r"(sb + SM_SEEN) : "memory"); spin_check(++spins >> 4); } while (v < seen);
    fence_async_global();
  }
  __device__ __forceinline__ void need(uint32_t mask) {
    if ((ready & mask) != mask) {
      uint32_t spins = 0;
      do { ready = ld_relaxed(flag) - base; spin_check(++spins); } while ((ready & mask) != mask);
      acquire_fence();
    }
    ST(5, n - 1);
  }
};

struct Cons {
  uint32_t sb, n, off, prev;
  uint32_t ebar;
  uint32_t da0, db0;
  int lane;
  template <int PAGES> __device__ __forceinline__ void advance() {
    n++; off += PAGES << 10; if (off >= (NPAGE << 10)) off = 0;
    asm volatile("" : "+r"(n), "+r"(off));
  }
  template <int BN, int PAGES> __device__ __forceinline__ void step_ab(float (&acc)[BN / 2], uint32_t da, uint32_t db, int accumulate) {
    STA();
    mbar_wait_fast(sb + BAR_FULL + ((n & 7) << 3), (n >> 3) & 1);
    STB(n);
    const uint64_t da64 = desc64(da), db64 = desc64(db);
    wgmma_fence();
#pragma unroll
    for (int k = 0; k < 4; k++) wgmma<BN>(acc, da64 + 2 * k, db64 + 128 * k, k ? 1 : accumulate);
    wgmma_commit();
    wgmma_wait<1>();
    if (prev && lane < 2) mbar_arrive_cluster(ebar + prev);
    prev = 64 + ((n & 7) << 3);
    advance<PAGES>();
  }
  template <int BN> __device__ __forceinline__ void step(float (&acc)[BN / 2], int accumulate = 1) { step_ab<BN, BN / 128 + 1>(acc, da0 + off, db0 + 1024 + off, accumulate); }
  template <int BN> __device__ __forceinline__ void step_own(float (&acc)[BN / 2], uint32_t da, int accumulate) { step_ab<BN, BN / 128>(acc, da, db0 + off, accumulate); }
  __device__ __forceinline__ void wait_full(uint32_t i) { mbar_wait_fast(sb + BAR_FULL + (((n + i) & 7) << 3), ((n + i) >> 3) & 1); }
  template <int I, int N> __device__ __forceinline__ void issue_rs(float (&acc)[64], uint32_t (&a)[16], int accumulate = 1) {
    if (I == 0) { STA(); STB(n); }
    const uint64_t db64 = desc64(db0 + off) + 1024 * I;
    wgmma_fence();
#pragma unroll
    for (int k = 0; k < 4; k++) wgmma_rs_n128(acc, a + 4 * k, db64 + 128 * k, k ? 1 : accumulate);
    if (I == N - 1) {
      wgmma_commit();
      prev = 64 + ((n & 7) << 3);
      advance<N>();
    }
  }
  template <int BN> __device__ __forceinline__ void steps(float (&acc)[BN / 2], int cnt) {
#pragma unroll 1
    do { step<BN>(acc); } while (--cnt > 0);
  }
  __device__ __forceinline__ void steps_skip(float (&acc)[64], int at) {
    int i = 0;
#pragma unroll 1
    do { if (i == at) off += 2 << 10; step<128>(acc); } while (++i < 2);
  }
  __device__ __forceinline__ void drain() {
    wgmma_wait<0>();
    if (lane < 2) mbar_arrive_cluster(ebar + prev);
    prev = 0;
  }
};

#define MAPPING 2
__device__ __forceinline__ uint32_t role_of_sm(uint32_t smid) {
  const uint32_t t = smid >> 1;
  uint32_t q, i;
  if (t < 32) { q = t & 7; i = t >> 3; }
  else if (t < 60) { const uint32_t u = t - 32, d = (u * 37) >> 8; q = 1 + u - d * 7; i = 4 + d; }
  else if (t < 62) return 128 + smid - 120;
  else { q = 0; i = t - 58; }
  return (q * 2 + (smid & 1)) * 8 + i;
}

template <typename T> __device__ __forceinline__ T* scratch(const Params& P, uint32_t off) { return (T*)ptr_add(P.scratch, off); }
__device__ __forceinline__ uint32_t* epoch_ptr(const Params& P) { uint32_t b; asm volatile("mov.u32 %0, %%ctaid.x;" : "=r"(b)); return scratch<uint32_t>(P, G_EPOCH + b * 4u); }

__device__ __forceinline__ int o_chunk(int s, int j) { const int hf = s >= 9, m = s - 2 - 7 * hf; return s < 2 ? 2 * j + s : 2 * (m == j ? 7 : m) + hf; }

__global__ void __cluster_dims__(2, 1, 1) __launch_bounds__(384, 1) fused_kernel(const __grid_constant__ Params P) {
  extern __shared__ __align__(1024) uint8_t smem_raw[];
  SP(0);
  const uint32_t sb = __shfl_sync(0xffffffffu, smem_u32(smem_raw), 0);
  const int warp = __shfl_sync(0xffffffffu, threadIdx.x >> 5, 0);
  const int lane = threadIdx.x & 31;
  if (warp == 7 && elect_one()) { prefetch_map(&P.map[M_XIN64]); prefetch_map(&P.map[M_WKV]); prefetch_map(&P.map[M_XIN]); }
  uint32_t role = blockIdx.x < 128 ? ((blockIdx.x >> 4) * 2 + (blockIdx.x & 1)) * 8 + ((blockIdx.x >> 1) & 7) : blockIdx.x;
  if (P.use_smid) { uint32_t smid; asm volatile("mov.u32 %0, %%smid;" : "=r"(smid)); role = role_of_sm(smid); }
  const bool spare = role >= 128;
  const int g = role >> 3, j = role & 7;
  uint32_t rank; asm("mov.u32 %0, %%cluster_ctarank;" : "=r"(rank));
  auto shared_b = [&]() {
    uint32_t peer;
    asm volatile("ld.shared::cluster.u32 %0, [%1];" : "=r"(peer) : "r"(mapa(sb + SM_ROLE, rank ^ 1)) : "memory");
    return !spare && peer < 128 && (peer & 7) == (uint32_t)j;
  };
  SP(1);

  if (warp >= 8) {
    asm volatile("setmaxnreg.dec.sync.aligned.u32 40;");
    if (elect_one()) {
      if (warp == 8) {
#pragma unroll
        for (int i = 0; i < 6; i++) mbar_init(sb + BAR_FULL + 8 * i, 1);
        mbar_init(sb + BAR_XIN, 1);
      } else if (warp == 9) {
#pragma unroll
        for (int i = 0; i < 8; i++) mbar_init(sb + BAR_EMPTY + 8 * i, 16);
      } else if (warp == 10) {
#pragma unroll
        for (int i = 0; i < 4; i++) mbar_init(sb + BAR_SFULL + 8 * i, 4);
        mbar_init(sb + BAR_CLR, 1); mbar_init(sb + BAR_FULL + 48, 1); mbar_init(sb + BAR_FULL + 56, 1);
      } else {
        sts128(sb + SM_ROLE, role, 0, 0, 0);
        mbar_init(sb + BAR_TAG, 1); mbar_init(sb + BAR_XFULL, 8); mbar_init(sb + BAR_CSE, 8);
        mbar_init(sb + BAR_SEMPTY, 1); mbar_init(sb + BAR_CSF, 1); mbar_init(sb + BAR_CSF + 8, 2);
      }
      asm volatile("fence.mbarrier_init.release.cluster;\nfence.release.sync_restrict::shared::cta.cluster;" ::: "memory");
      fence_async_smem();
    }
    __syncwarp();
    SP(2);
    asm volatile("barrier.cluster.arrive.relaxed.aligned;" ::: "memory");
    if (warp == 8 && !spare) {
      if (elect_one()) {
        const int par = g & 1, row = (g >> 1) * 128;
        mbar_arrive(sb + BAR_FULL);
        {
          const int s = 1;
          const uint32_t xb = sb + BAR_XIN, fb = sb + BAR_FULL + 8;
          mbar_expect_tx(xb, PAGE); mbar_expect_tx(fb, 2 * PAGE);
#pragma unroll
          for (int h = 0; h < 2; h++) tma_ld3(sb + SM_STAGE + h * PAGE + s * 8192, &P.map[M_XIN64], xb, s * 64, par, row + h * 64);
#pragma unroll
          for (int h = 0; h < 2; h++) tma_ld3(sb + (2 * s + h) * PAGE, &P.map[M_WKV], fb, 0, s * 64, 16 + 16 * h + 2 * j);
        }
#pragma unroll 1
        for (int s = 0; s < 2; s++) {
          const uint32_t fb = sb + BAR_FULL + 16 + 8 * s;
          mbar_expect_tx(fb, PAGE);
          tma_ld3(sb + (4 + s) * PAGE, &P.map[M_WKV], fb, 0, s * 64, 2 * j);
        }
#pragma unroll 1
        for (int s = 0; s < 2; s++) {
          const uint32_t fb = sb + BAR_FULL + 32 + 8 * s, a = sb + (6 + 3 * s) * PAGE;
          const int k = (j == 1 ? 4 : 2) + s;
          mbar_expect_tx(fb, 3 * PAGE);
          tma_ld3(a, &P.map[M_XIN], fb, k * 64, par, row);
#pragma unroll
          for (int h = 0; h < 2; h++) tma_ld3(a + PAGE + h * PAGE, &P.map[M_WKV], fb, 0, k * 64, 16 + 16 * h + 2 * j);
        }
        spin_check((sb & 1023) << 22);
      }
      __syncwarp();
    }
    SP(3);
    asm volatile("barrier.cluster.wait.acquire.aligned;" ::: "memory");
    SP(4);
    if (warp == 8) {
      if (elect_one()) {
        Prod p; p.sb = sb; p.n = 0; p.tail = 0; p.ready = 0; p.addr = 0;
        { const bool mc = shared_b(); p.rank = rank; p.flip = !mc; p.mask = mc ? 3 : 1 << rank; }
        uint32_t fb;
        if (spare) {
          p.pat = 0x55555000u;
#pragma unroll 1
          for (int r = -1; r < 7; r++) {
            const int ch = r < 0 ? 4 * j : ((r < 2 ? r : r == 2 ? 6 : r - 1) * 4 + j) * 2;
#pragma unroll 1
            for (int k = 0; k < 16; k++) { const uint32_t a = p.acquire<2>(fb); p.load_b(a, PAGE, &P.map[r < 0 ? M_WKV : M_W1], r < 0 ? 0 : 128, fb, k, ch, r < 0 ? 2 : 0); }
          }
        } else {
          p.seen = 0;
          const int xpar = g & 1, xrow = (g >> 1) * 128;
          SP(5);
#pragma unroll 1
          for (int hl = 0; hl < 4; hl++) {
            const int ffn = hl & 1;
            const CUtensorMap* xmap = &P.map[hl ? M_OUT_LD : M_XIN];
            if (hl) {
              p.pat = ffn ? Pat<3>::v : Pat<8>::v;
#pragma unroll 1
              for (int s = 0; s < 2; s++) { const uint32_t a = p.acquire<2>(fb); p.load_wide(P, ffn, a, fb, 2 * j + s, 2 * j); }
#pragma unroll 1
              for (int s = 0; s < 2; s++) { const uint32_t a = p.acquire<1>(fb); p.load_narrow(P, ffn, a, fb, 2 * j + s, j); }
            } else { p.pat = (Pat<0>::v >> 12) | 0x55500000u; p.addr = 0; p.n = 6; }
            if (hl == 0) SP(6);
            uint32_t fb0 = 0;
#pragma unroll 1
            for (int m = hl ? 0 : 2; m < 14; m++) {
              const int hf = m >= 7, mm = m - 7 * hf, jj = mm == j ? 7 : mm;
              int k = 2 * jj + hf;
              if (hl == 0) {
                const int pr = (m >> 1) + 1;
                k = 2 * (j && pr == 2 ? j : pr == j ? 2 : pr) + (m & 1);
              }
              const uint32_t a = p.acquire<3>(fb);
              p.load_wide(P, ffn, a + PAGE, fb, k, 2 * j);
              if (hl) {
                if (m == 0) { fb0 = fb; continue; }
                if (m == 1) {
                  const int j0 = j ? 0 : 7;
                  p.flag = scratch<uint32_t>(P, g * G_BLOCK + G_FLAGS + (ffn ? (hl >> 1) * EV_N + EV_XA : EV_XB) * 128);
                  p.ready = 0; p.need(1u << j0);
                  tma_ld3(a - 3 * PAGE, xmap, fb0, j0 * 128, xpar, xrow);
                }
                if (m < 7) p.need(1u << jj); else if (m == 7) p.next();
              }
              tma_ld3(a, xmap, fb, k * 64, xpar, xrow);
            }
            if (hl == 0) { mbar_wait(sb + BAR_TAG, 0); asm volatile("ld.shared.u32 %0, [%1];" : "=r"(p.base) : "r"(sb + SM_TAG) : "memory"); p.base = (p.base - 1) * 255; }
            p.pat = ffn ? Pat<4>::v : Pat<1>::v;
#pragma unroll 1
            for (int m = 0; m < 14; m++) {
              const int k = (m >> 1) == (hl ? j : 0) ? 14 + (m & 1) : m;
              if (ffn && m == 8) p.addr += 2 * PAGE;
              const uint32_t a = p.acquire<2>(fb);
              p.load_narrow(P, ffn, a + PAGE, fb, k, j);
              tma_ld3(a, xmap, fb, k * 64, xpar, xrow);
            }
            if (!ffn) {
              p.pat = Pat<2>::v;
              uint32_t a = 0;
#pragma unroll 1
              for (int s = 0; s < 16; s++) {
                if ((0x4925 >> s) & 1) a = p.acquire_n(s == 0 || s == 14 ? 2 : 3, fb); else a += PAGE;
                p.load_b(a, 8192, &P.map[M_WO], 0, fb, o_chunk(s, j), 2 * j, 1);
              }
              p.addr += 2 * PAGE;
              a = p.acquire<2>(fb);
              tma_ld3(a, xmap, fb, j * 128, xpar, xrow); tma_ld3(a + PAGE, xmap, fb, j * 128 + 64, xpar, xrow);
            } else {
              p.pat = Pat<5>::v;
#pragma unroll 1
              for (int s = 16; s < 48; s++) {
                const int pi = (s >> 1) & 7;
                const int k = (s < 32 ? pi : pi == 4 ? j : pi == j ? 4 : pi) * 2 + (s & 1);
                const uint32_t a = p.acquire<3>(fb);
                p.load_wide(P, 1, a + PAGE, fb, k, (s & 48) + 2 * j);
                tma_ld3(a, xmap, fb, k * 64, xpar, xrow);
              }
              p.pat = Pat<6>::v;
#pragma unroll 1
              for (int q = 0; q < 4; q++) {
                p.next();
                const int k0 = q == 0 ? 0 : q == 1 ? 48 : q * 16 - 16, k1 = k0 + (q == 1 ? 8 : 16);
#pragma unroll 1
                for (int k = k0; k < k1; k++) {
                  if (k == 24) { p.addr = 0; p.pat = Pat<7>::v; }
                  const uint32_t a = p.acquire<2>(fb);
                  p.load_b(a + PAGE, 8192, &P.map[M_W2], 0, fb, k, 2 * j, 1);
                  tma_ld3(a, &P.map[M_H_LD], fb, k * 64, g, 0);
                }
              }
            }
            TL(2, 1 + hl);
          }
        }
        p.finish();
      }
    } else if (!spare) {
      mbar_wait(sb + BAR_XIN, 0);
      if (elect_one()) {
#pragma unroll 1
        for (int i = warp - 9; i < 8; i += 3) prefetch_l2(ptr_add(P.wqkv, (i * 128 + role) * 6144u + 2048u), 4096);
      }
      uint32_t tag;
      {
        const uint32_t part = warp - 9, col = DM + role * 16 + (lane & 1) * 8;
        const int cnt = part ? 21 : 22;
        const uint4* wp = ptr_add((const uint4*)P.wqkv, ((part ? 16 + part * 336 : 0) + (lane >> 1)) * 6144u + col * 2);
        float s[8] = {0, 0, 0, 0, 0, 0, 0, 0};
        uint4 v[4];
#pragma unroll
        for (int i = 0; i < 4; i++) v[i] = ld_relaxed4(wp + i * (16 * 6144 / 16));
        tag = ld_relaxed(epoch_ptr(P)) + 1;
        if (warp == 10 && lane == 0) { asm volatile("st.shared.u32 [%0], %1;" :: "r"(sb + SM_TAG), "r"(tag) : "memory"); mbar_arrive(sb + BAR_TAG); }
#pragma unroll 1
        for (int b = 4; b < 28; b += 4) {
          wp += 64 * 6144 / 16;
#pragma unroll
          for (int i = 0; i < 4; i++) {
            s[0] += bf_lo(v[i].x); s[1] += bf_hi(v[i].x); s[2] += bf_lo(v[i].y); s[3] += bf_hi(v[i].y);
            s[4] += bf_lo(v[i].z); s[5] += bf_hi(v[i].z); s[6] += bf_lo(v[i].w); s[7] += bf_hi(v[i].w);
            v[i] = make_uint4(0, 0, 0, 0);
            if (b + i < cnt) v[i] = __ldcg(wp + i * (16 * 6144 / 16));
          }
        }
#pragma unroll
        for (int e = 0; e < 4; e++) { const bool h = lane & 16; const float t = __shfl_xor_sync(0xffffffffu, h ? s[e] : s[e + 4], 16); s[e] = (h ? s[e + 4] : s[e]) + t; }
#pragma unroll
        for (int e = 0; e < 2; e++) { const bool h = lane & 8; const float t = __shfl_xor_sync(0xffffffffu, h ? s[e] : s[e + 2], 8); s[e] = (h ? s[e + 2] : s[e]) + t; }
        { const bool h = lane & 4; const float t = __shfl_xor_sync(0xffffffffu, h ? s[0] : s[1], 4); s[0] = (h ? s[1] : s[0]) + t; }
        s[0] += __shfl_xor_sync(0xffffffffu, s[0], 2);
        if (!(lane & 2) || part == 0) st_relaxed(scratch<uint32_t>(P, G_CS + (col + (lane >> 2)) * 16 + ((lane & 2) ? 3 : part) * 4), tagf((lane & 2) ? 0.f : s[0], tag));
        __syncwarp();
      }
      if (warp == 11 && lane == 0) TL(2, 30);
      {
        const uint32_t cspos = sb + SM_CS + ((lane & 16) + ((lane >> 1) & 3) * 4 + ((lane >> 3) & 1) * 2 + (lane & 1)) * 4;
#pragma unroll 1
        for (int it = 0; it < (warp == 10 ? 8 : 1); it++) {
          const int t = it & 3;
          if (it) mbar_wait(sb + BAR_CSE, (it - 1) & 1);
          if (t == 1) mbar_wait(sb + BAR_SEMPTY, 0);
#pragma unroll 1
          for (int b = it ? 0 : warp - 9; b < (it == 0 ? warp - 8 : t < 2 ? 3 : 2); b++) {
            uint32_t c0, c1;
            if (b < 2) { c0 = (t ? 2048 + t * 1024 + b * FF : 1024 + b * 1024) + j * 128; c1 = c0 + 64; }
            else if (t) { c0 = 6144 + j * 64; c1 = c0 + FF; }
            else { c0 = j * 128; c1 = c0 + 64; }
            const uint4* p0 = scratch<uint4>(P, G_CS + (c0 + lane) * 16u);
            const uint4* p1 = scratch<uint4>(P, G_CS + (c1 + lane) * 16u);
            uint4 v[4]; uint32_t spins = 0; bool ok;
            do {
              if (spins) __nanosleep(200);
              v[0] = ld_relaxed4(p0); v[1] = ld_relaxed4(p0 + 32); v[2] = ld_relaxed4(p1); v[3] = ld_relaxed4(p1 + 32);
              ok = tag_ok4(v[0], tag) && tag_ok4(v[1], tag) && tag_ok4(v[2], tag) && tag_ok4(v[3], tag);
              spin_check(++spins);
            } while (__any_sync(0xffffffffu, !ok));
#pragma unroll
            for (int m = 0; m < 4; m++) sts32f(cspos + b * 512 + m * 128, (untag(v[m].x) + untag(v[m].y)) + (untag(v[m].z) + untag(v[m].w)));
            __syncwarp();
            if (lane == 0) mbar_arrive(sb + BAR_CSF + (b ? 8 : 0));
          }
          if (lane == 0) { if (t >= 2) mbar_arrive(sb + BAR_CSF + 8); TL(2, 16 + it + (warp == 11 ? 8 : warp == 9 ? 9 : 0)); }
          if (t == 3) {
            if (g >= 2) {
              uint4* op = scratch<uint4>(P, G_HALO + (((it >> 2) * 16 + g - 2) * 8 + j) * 4096u + lane * 16u);
#pragma unroll 1
              for (int i = 0; i < 8; i++) { st_b128(op, 0, 0, 0, 0); op += 32; }
            }
          }
        }
      }
      if (warp == 11) {
        if (elect_one()) prefetch_l2(ptr_add(P.wo, role * 16384u), 16384);
        uint32_t* const fl = scratch<uint32_t>(P, g * G_BLOCK + G_FLAGS);
        uint32_t seen = 0;
#pragma unroll 1
        for (int e = EV_XA; e < EV_N + EV_XB; e++) {
          if (e == EV_XB) continue;
          const bool clr = (e & 7) == EV_XA;
          uint32_t* const f = ptr_add(fl, (clr ? 16 + e : e) * 128u);
          if (clr) {
            uint4* op = scratch<uint4>(P, g * G_BLOCK + G_O + j * 32768u + lane * 16u);
#pragma unroll 1
            for (int i = 0; i < 64; i++) { st_b128(op, 0, 0, 0, 0); op += 32; if (e || (i & 1)) __nanosleep(10); }
            __syncwarp();
            if (lane == 0) red_release(f, 1u << j);
          }
          uint32_t spins = 0, m;
          while ((m = ld_relaxed(f) - (tag - 1) * 255) != 255) { __nanosleep(m ? 50 : 500); spin_check(++spins); }
          asm volatile("fence.acquire.gpu;" ::: "memory");
          if (lane == 0) {
            if (clr) mbar_arrive(sb + BAR_CLR);
            else asm volatile("st.release.cta.shared.u32 [%0], %1;" :: "r"(sb + SM_SEEN), "r"(++seen) : "memory");
          }
          if (e == EV_H3) {
#pragma unroll 1
            for (int i = 0; i < 7; i++) { if (elect_one()) prefetch_l2(ptr_add(P.w2, (i * 128 + role) * 8192u), 8192); __nanosleep(500); }
          }
          __syncwarp();
        }
      } else if (warp == 9) {
        if (elect_one()) {
          prefetch_map(&P.map[M_WQ]); prefetch_map(&P.map[M_OUT_LD]); prefetch_map(&P.map[M_WO]); prefetch_map(&P.map[M_W1 + rank]);
          prefetch_map(&P.map[M_H_ST]); prefetch_map(&P.map[M_H_LD]); prefetch_map(&P.map[M_W1H + rank]); prefetch_map(&P.map[M_W2]); prefetch_map(&P.map[M_OUT_ST]);
          uint32_t* fl = scratch<uint32_t>(P, g * G_BLOCK + G_FLAGS);
          int pe = 0;
#pragma unroll 1
          for (int e = 0; e < 2 * EV_N; e++) {
            const int q = e & 7;
            const bool is_h = q >= EV_H0 && q < EV_XB, last = e >= EV_N + EV_XB;
            const CUtensorMap* map = &P.map[is_h ? M_H_ST : M_OUT_ST];
            const int col = q == EV_H3 ? 3072 - 64 + j * 64 : (q == EV_H1 ? 1024 : q == EV_H2 ? 2048 : 0) + j * 128;
            const int row = is_h ? 0 : (g >> 1) * 128, par = is_h ? g : g & 1;
#pragma unroll 1
            for (int hb = is_h ? q == EV_H3 : q & 1; hb <= (is_h ? 1 : q & 1); hb++) {
#pragma unroll
              for (int w = 0; w < 2; w++) {
                const bool sw = last;
                const int wg = sw ? hb : w, h = sw ? w : hb, p = sw ? pe - hb + w : pe;
                mbar_wait(sb + BAR_SFULL + 16 * wg + 8 * (p & 1), (p >> 1) & 1);
                if (w == 0) TL(3, 20 + e);
                const uint32_t src = sb + (last ? 0 : SM_STAGE) + wg * PAGE + h * 8192;
                if (is_h) {
#pragma unroll 1
                  for (int r = 0; r < 64; r += H_ROWS) { tma_st3(map, src + r * 128, col + h * 64, par, wg * 64 + r); __nanosleep(60); }
                } else tma_st3(map, src, col + h * 64, par, row + wg * 64);
              }
              pe++;
            }
            bulk_commit();
            if (e != EV_N + EV_XB) bulk_wait<0>();
            TL(3, 40 + e);
            if (is_h || (q & 1)) mbar_arrive(sb + BAR_SEMPTY);
            if (!last) red_release(fl, 1u << j);
            TL(3, e);
            fl += 32;
          }
          *epoch_ptr(P) = tag;
        }
      }
    }
  } else {
    if (!spare) {
      const uint32_t r = threadIdx.x >> 3, so = r * 128 + (((threadIdx.x ^ r) & 7) << 4);
      const uint8_t* xp = ptr_add((const uint8_t*)P.x, (2 * ((g >> 1) * 128 + r) + (g & 1)) * 2048u + (threadIdx.x & 7) * 16u);
      const uint8_t* wp = ptr_add((const uint8_t*)P.wqkv, r * 6144u + 2048u + j * 256u + (threadIdx.x & 7) * 16u);
#pragma unroll
      for (int i = 0; i < 4; i++) asm volatile("cp.async.cg.shared.global [%0], [%1], 16;" :: "r"(sb + SM_STAGE + (i >> 1) * PAGE + (i & 1) * 4096 + so), "l"(xp + i * 32 * 4096) : "memory");
#pragma unroll
      for (int q = 0; q < 8; q++) {
        const int i = (q & 3) * 2 + (q >> 2);
        asm volatile("cp.async.cg.shared.global [%0], [%1], 16;" :: "r"(sb + i * 4096 + so), "l"(wp + (i & 1) * 32 * 6144 + ((i >> 1) & 1) * 128 + (i >> 2) * 2048) : "memory");
      }
    }
    if (!spare) {
      if (warp == 0) asm volatile("prefetch.global.L2 [%0];" :: "l"(ptr_add(P.x, (2 * ((g >> 1) * 128 + j * 16 + (lane >> 1)) + (g & 1)) * 2048u + (lane & 1) * 128u)));
      else if (warp < 3 && (warp == 1 || lane < 16)) asm volatile("prefetch.global.L2 [%0];" :: "l"(ptr_add(P.wqkv, role * 6144u + (warp - 1) * 4096u + lane * 128u)));
      __syncwarp();
    }
    asm volatile("barrier.cluster.arrive.relaxed.aligned;" ::: "memory");
    asm volatile("setmaxnreg.inc.sync.aligned.u32 232;");
    SP(4);
    asm volatile("barrier.cluster.wait.acquire.aligned;" ::: "memory");
    SP(5);
    const int wg = warp >> 2;
    const int quad = lane & 3, gr = lane >> 2;
    Cons c; c.sb = sb; c.n = 0; c.off = 0; c.prev = 0; c.lane = lane;
    c.ebar = mapa(sb + BAR_EMPTY - 64, shared_b() ? lane & 1 : rank);
    const uint32_t stage = sb + SM_STAGE + wg * PAGE;
    const uint32_t dstage = desc_lo(stage, 16);
    if (spare) {
      const uint32_t tag = ld_relaxed(epoch_ptr(P)) + 1;
      const int tid = threadIdx.x & 127;
#pragma unroll
      for (int i = 0; i < 4; i++) sts128(stage + (i * 128 + tid) * 16, 0x3f803f80u, 0x3f803f80u, 0x3f803f80u, 0x3f803f80u);
      fence_async_smem();
      bar_sync(2 + wg, 128);
      c.db0 = desc_lo(sb + wg * PAGE, 8192);
#pragma unroll 1
      for (int r = -1; r < 7; r++) {
        float acc[64];
#pragma unroll 1
        for (int k = 0; k < 16; k++) c.step_ab<128, 2>(acc, dstage, c.db0 + c.off, k);
        c.drain();
        acc_fence<64>(acc);
        {
          float v = 0;
#pragma unroll
          for (int i = 0; i < 32; i++) asm("{\n.reg .pred p;\nsetp.eq.u32 p, %2, %3;\nselp.f32 %0, %1, %0, p;\n}" : "+f"(v) : "f"(acc[4 * (i >> 1) + (i & 1)]), "r"(tid >> 2), "r"(i));
          st_b128(scratch<uint4>(P, G_CS + (uint32_t)((r < 0 ? j * 256 + wg * 128 : 3 * DM + wg * FF + ((r < 2 ? r : r == 2 ? 6 : r - 1) * 4 + j) * 128) + (tid >> 3) * 8 + quad * 2 + (gr & 1)) * 16u),
                  tagf(v, tag), tag & 15u, tag & 15u, tag & 15u);
        }
        __syncwarp();
      }
      if (wg == 0) {
        const uint32_t* p = scratch<uint32_t>(P, (tid >> 3) * G_BLOCK + G_STATS + (tid & 7) * 8u);
        uint32_t spins = 0;
        while (__any_sync(0xffffffffu, (ld_relaxed(p) ^ tag) & 15u)) spin_check(++spins);
      }
      bar_sync(1, 256);
      if (threadIdx.x == 0) *epoch_ptr(P) = tag;
    } else {
    c.da0 = desc_lo(sb + wg * 8192, 16); c.db0 = desc_lo(sb, 8192);
    uint32_t sphase = 1, sfull = sb + BAR_SFULL + 16 * wg;
    const uint32_t maddr = stage + ((warp & 3) * 16 + (lane & 15)) * 128 + (((lane >> 4) ^ (lane & 7)) << 4);
    const uint32_t csaddr = sb + SM_CS + quad * 16;
    float st[8] = {0, 0, 0, 0, 0, 0, 0, 0};
    float* const mean = st; float* const rstd = st + 2;
    SP(6);

    auto stage_wait = [&]() { mbar_wait_fast(sb + BAR_SEMPTY, sphase); sphase ^= 1; };
    auto stage_publish = [&]() { fence_async_smem(); __syncwarp(); if (lane == 0) mbar_arrive(sfull); sfull ^= 8; };
    auto cs_load = [&](uint32_t (&cs)[16], int grp) {
#pragma unroll
      for (int i = 0; i < 4; i++) lds128(csaddr + grp * 256 + i * 64, cs[4 * i], cs[4 * i + 1], cs[4 * i + 2], cs[4 * i + 3]);
    };
    auto cs_apply = [&](float* acc, uint32_t (&cs)[16]) {
      acc_fence<32>(acc);
#pragma unroll
      for (int b = 0; b < 8; b++) {
        acc[4 * b] -= mean[0] * __uint_as_float(cs[2 * b]); acc[4 * b + 1] -= mean[0] * __uint_as_float(cs[2 * b + 1]);
        acc[4 * b + 2] -= mean[1] * __uint_as_float(cs[2 * b]); acc[4 * b + 3] -= mean[1] * __uint_as_float(cs[2 * b + 1]);
      }
      acc_fence<32>(acc);
    };
    auto glu_pair = [&](float g0, float g1, float u0, float u1, int r) {
      const float nl = -LOG2E * rstd[r], r2 = rstd[r] * rstd[r];
      return pack_bf16(g0 * u0 * r2 * rcp(1.0f + ex2(g0 * nl)), g1 * u1 * r2 * rcp(1.0f + ex2(g1 * nl)));
    };
    auto glu_slice = [&](uint32_t (&pk)[64], int i) {
      uint32_t hp[4];
#pragma unroll
      for (int e = 0; e < 4; e++) {
        asm volatile("" : "+r"(pk[4 * i + e]), "+r"(pk[32 + 4 * i + e]));
        const uint32_t pg = pk[4 * i + e], pu = pk[32 + 4 * i + e];
        hp[e] = glu_pair(bf_lo(pg), bf_hi(pg), bf_lo(pu), bf_hi(pu), e & 1);
      }
      stsm4((maddr ^ ((i & 3) << 5)) + (i >> 2) * 8192, hp[0], hp[1], hp[2], hp[3]);
    };
    auto glu_slice_acc = [&](float (&acc)[128], int i) {
      uint32_t hp[4];
      acc_fence<8>(acc + 8 * i);
#pragma unroll
      for (int e = 0; e < 4; e++) hp[e] = glu_pair(acc[8 * i + 2 * e], acc[8 * i + 2 * e + 1], acc[64 + 8 * i + 2 * e], acc[64 + 8 * i + 2 * e + 1], e & 1);
      stsm4((maddr ^ ((i & 3) << 5)) + (i >> 2) * 8192, hp[0], hp[1], hp[2], hp[3]);
    };
    auto stage_x = [&](uint32_t (&x)[32], int hf, uint32_t maddr) {
#pragma unroll
      for (int i = 4 * hf; i < 4 * hf + 4; i++) stsm4((maddr ^ ((i & 3) << 5)) + hf * 8192, x[4 * i], x[4 * i + 1], x[4 * i + 2], x[4 * i + 3]);
    };

    float acc[128];
    asm volatile("cp.async.wait_all;" ::: "memory");
    fence_async_smem();
    bar_sync(1, 256);
    SP(7);
    c.step_own<256>(acc, dstage, 0);
    mbar_wait_fast(sb + BAR_XIN, 0);
    SP(8);
#pragma unroll 1
    for (int hl = 0;; hl++) {
      int t = hl & 1;
      float acc2[64];
      uint32_t res[32];
      c.step_own<256>(acc, dstage + 512, 1);
#pragma unroll
      for (int s = 0; s < 2; s++) c.step_own<128>(acc2, dstage + s * 512, s);
#pragma unroll 1
      for (int s = 2; s < 11; s++) {
        const uint32_t apage = (c.off << 4) - (SM_STAGE + wg * 8192);
        if (s == 3 && wg) bar_sync(6, 256);
        c.step<256>(acc);
        if (s == 3 && !wg) asm volatile("bar.arrive 6, 256;" ::: "memory");
        int act = s;
        asm volatile("" : "+r"(act));
        auto get_tag = [&]() { uint32_t tag; asm volatile("ld.shared.u32 %0, [%1];" : "=r"(tag) : "r"(sb + SM_TAG) : "memory"); return tag; };
        auto stat_ptr = [&]() { return scratch<uint2>(P, g * G_BLOCK + G_STATS + (hl * 128 + warp * 16 + (lane_now() >> 2)) * 64u); };
        auto stat_get = [&]() {
          const uint2* sp = ptr_add(stat_ptr(), (lane_now() & 3) * 16);
          const uint4 a = ld_relaxed4(sp), b = ld_relaxed4(sp + 64);
          st[0] = __uint_as_float(a.x); st[1] = __uint_as_float(a.y); st[2] = __uint_as_float(a.z); st[3] = __uint_as_float(a.w);
          st[4] = __uint_as_float(b.x); st[5] = __uint_as_float(b.y); st[6] = __uint_as_float(b.z); st[7] = __uint_as_float(b.w);
        };
        switch (act) {
          case 4: case 5: {
            const uint32_t ra = maddr + ((hl || j == 0) ? (s & 1) * 8192 : apage);
#pragma unroll
            for (int i = 0; i < 4; i++) {
              uint32_t v[4];
              ldsm4(ra ^ (i << 5), v[0], v[1], v[2], v[3]);
              if (i == 0 && s == 4) { st[0] = bf_lo(v[0]); st[1] = bf_lo(v[1]); st[2] = st[3] = st[4] = st[5] = 0; }
#pragma unroll
              for (int e = 0; e < 4; e++) {
                const float a = bf_lo(v[e]) - st[e & 1], b = bf_hi(v[e]) - st[e & 1];
                st[2 + (e & 1)] += a + b; st[4 + (e & 1)] += a * a; st[4 + (e & 1)] += b * b;
              }
            }
          } break;
          case 6: {
            mbar_wait_fast(sb + BAR_TAG, 0);
            const uint32_t tag = get_tag();
#pragma unroll
            for (int r = 0; r < 2; r++) {
              const float mt = st[r] + st[2 + r] * (1.0f / 32);
              float m = mt + __shfl_xor_sync(0xffffffffu, mt, 1); m += __shfl_xor_sync(0xffffffffu, m, 2); m *= 0.25f;
              float q = st[4 + r] - st[2 + r] * st[2 + r] * (1.0f / 32) + 32.0f * (mt - m) * (mt - m);
              q += __shfl_xor_sync(0xffffffffu, q, 1); q += __shfl_xor_sync(0xffffffffu, q, 2);
              if (quad == 0) st_relaxed2(ptr_add(stat_ptr(), r * 512 + j * 8), tagf(m, tag), tagf(q, tag));
            }
          } break;
          case 8: stat_get(); break;
          case 10: {
            const uint32_t tag = get_tag();
            uint32_t spins = 0;
            for (;;) {
              uint32_t bad = 0;
#pragma unroll
              for (int i = 0; i < 8; i++) bad |= __float_as_uint(st[i]) ^ tag;
              if (!__any_sync(0xffffffffu, bad & 15u)) break;
              stat_get(); spin_check(++spins);
            }
            float mr[4];
#pragma unroll
            for (int r = 0; r < 2; r++) {
              const float m0 = untag(__float_as_uint(st[4 * r])), m1 = untag(__float_as_uint(st[4 * r + 2]));
              float m = m0 + m1; m += __shfl_xor_sync(0xffffffffu, m, 1); m += __shfl_xor_sync(0xffffffffu, m, 2); m *= 0.125f;
              float q = untag(__float_as_uint(st[4 * r + 1])) + untag(__float_as_uint(st[4 * r + 3])) + 128.0f * ((m0 - m) * (m0 - m) + (m1 - m) * (m1 - m));
              q += __shfl_xor_sync(0xffffffffu, q, 1); q += __shfl_xor_sync(0xffffffffu, q, 2);
              mr[r] = m; mr[2 + r] = rsqrtf(fmaxf(q, 0.f) * (1.0f / DM) + LN_EPS);
            }
            st[0] = mr[0]; st[1] = mr[1]; st[2] = mr[2]; st[3] = mr[3];
          } break;
          default: break;
        }
      }
#pragma unroll 1
      for (;;) {
      const int it = (hl >> 1) * 4 + t;
#pragma unroll
      for (int s = 0; s < 4; s++) {
        uint32_t cs[16];
        c.step<256>(acc);
        if (!(s & 1)) mbar_wait_fast(sb + BAR_CSF + 4 * s, t & 1);
        if (s >= 2 && t <= 1) { cs_load(cs, 2 + s); cs_apply(acc2 + 32 * (s - 2), cs); }
        cs_load(cs, s);
        c.drain();
        cs_apply(acc + 32 * s, cs);
      }
      c.step<256>(acc);
      if (lane == 0) mbar_arrive(sb + BAR_CSE);
      c.drain();
      acc_fence<128>(acc);
      TLC(1 + it * 6);
      uint32_t pkB[64];
      if (t == 2) {
#pragma unroll
        for (int i = 0; i < 64; i++) pkB[i] = pack_bf16(acc[2 * i], acc[2 * i + 1]);
      } else if (t == 0) {
        uint32_t pkA[64];
        auto kv_pack = [&](int v, int r) {
#pragma unroll
          for (int i = 32 * v + r; i < 32 * v + 32; i += 2) { acc_fence<2>(acc + 2 * i); pkA[i] = pack_bf16(acc[2 * i] * rstd[r], acc[2 * i + 1] * rstd[r]); }
        };
        const uint32_t l16 = lane_now() * 16u;
        uint4* const xs = ptr_add((uint4*)smem_raw, SM_STAGE + l16);
        uint4* const hp = scratch<uint4>(P, G_HALO + (((hl >> 1) * 16 + g) * 8 + j) * 4096u + l16);
        {
          uint4* const dst = (warp == 7 && g < 14) ? hp : ptr_add(xs, warp * 4096u);
#pragma unroll
          for (int s = 0; s < 2; s++) {
            c.steps<128>(acc2, s ? 2 : 1 + wg);
            if (s == 0) stage_wait();
            kv_pack(s, 1);
#pragma unroll
            for (int i = 4 * s; i < 4 * s + 4; i++) { pkA[8 * i + 1] = pkt_head(pkA[8 * i + 1]); gen_store(dst + i * 32, pkA[8 * i + 1], pkA[8 * i + 3], pkA[8 * i + 5], pkA[8 * i + 7]); }
          }
        }
        __syncwarp();
        if (lane == 0) mbar_arrive(sb + BAR_XFULL);
#pragma unroll
        for (int s = 0; s < 2; s++) {
          c.steps<128>(acc2, 2);
#pragma unroll
          for (int i = 33 - s; i < 64; i += 2) pkA[i] = movm(pkA[i]);
          kv_pack(1 - s, 0);
        }
        uint32_t kvH[32];
        {
          const uint4* const src = (warp == 0 && g >= 2) ? hp - 2 * 8 * 256 : ptr_add(xs, (warp ? warp - 1 : 0) * 4096u);
          c.steps<128>(acc2, 2);
          mbar_wait_fast(sb + BAR_XFULL, hl >> 1);
#pragma unroll
          for (int i = 0; i < 8; i++) gen_load(src + i * 32, kvH + 4 * i);
          c.steps<128>(acc2, 3 - wg);
          uint32_t spins = 0;
          while (__any_sync(0xffffffffu, !(kvH[0] && kvH[4] && kvH[8] && kvH[12] && kvH[16] && kvH[20] && kvH[24] && kvH[28]))) {
#pragma unroll
            for (int i = 0; i < 8; i++) gen_load(src + i * 32, kvH + 4 * i);
            spin_check(++spins);
          }
        }
#pragma unroll
        for (int i = 16; i < 32; i++) kvH[i] = movm(kvH[i]);
        mbar_wait_fast(sb + BAR_CLR, hl >> 1);
        c.steps<128>(acc2, 2);
        AP(0);
        c.wait_full(0);
        AP(1);
        c.drain();
        AP(2);
        acc_fence<64>(acc2);
        TLC(2 + it * 6);
        uint32_t q[32];
#pragma unroll
        for (int i = 0; i < 32; i++) q[i] = pack_bf16(acc2[2 * i], acc2[2 * i + 1]);
        const uint32_t zm = bar_sync_zero(1, 256);
        AP(3);
        uint32_t ob[6][16];
        uint4* const omail = scratch<uint4>(P, g * G_BLOCK + G_O + warp * 2048u + l16);
        float o2[8][4], r2[4];
        {
          const float hv = (warp == 0 && g < 2) ? -INFINITY : 0.f;
          const float hinit[4] = {hv, hv, hv, hv};
          const bool c0 = (2 * quad <= gr), c1 = (2 * quad + 1 <= gr);
          const uint32_t lm = (c0 ? 0xffffu : 0u) | (c1 ? 0xffff0000u : 0u);
          const float sc[2] = {rstd[0] * (0.17677669529663687f * LOG2E), rstd[1] * (0.17677669529663687f * LOG2E)};
          float lg[4][4], mx[4][2];
#pragma unroll
          for (int h = 0; h < 4; h++) {
            const int b = h * 4;
            float sH[4], sL[4], sU[4];
            q[2 * b] |= zm;
            mma16816(sH, q[2 * b], q[2 * b + 1], q[2 * b + 2], q[2 * b + 3], kvH[b], kvH[b + 1], hinit);
            mma16816z(sL, q[2 * b], q[2 * b + 1], q[2 * b + 2], q[2 * b + 3], pkA[2 * b], pkA[2 * b + 2]);
            mma16816z(sU, q[2 * b], q[2 * b + 1], q[2 * b + 2], q[2 * b + 3], pkA[2 * b + 1], pkA[2 * b + 3]);
            mma16816(sH, q[2 * b + 4], q[2 * b + 5], q[2 * b + 6], q[2 * b + 7], kvH[b + 2], kvH[b + 3], sH);
            mma16816(sL, q[2 * b + 4], q[2 * b + 5], q[2 * b + 6], q[2 * b + 7], pkA[2 * b + 4], pkA[2 * b + 6], sL);
            mma16816(sU, q[2 * b + 4], q[2 * b + 5], q[2 * b + 6], q[2 * b + 7], pkA[2 * b + 5], pkA[2 * b + 7], sU);
            lg[h][0] = c0 ? sL[0] : sH[0]; lg[h][1] = c1 ? sL[1] : sH[1]; lg[h][2] = c0 ? sU[2] : sL[2]; lg[h][3] = c1 ? sU[3] : sL[3];
            mx[h][0] = fmaxf(lg[h][0], lg[h][1]); mx[h][1] = fmaxf(lg[h][2], lg[h][3]);
          }
#pragma unroll
          for (int o = 1; o < 4; o <<= 1) {
#pragma unroll
            for (int i = 0; i < 8; i++) mx[i >> 1][i & 1] = fmaxf(mx[i >> 1][i & 1], __shfl_xor_sync(0xffffffffu, mx[i >> 1][i & 1], o));
          }
          AP(4);
          uint32_t z = zm, pp[4][2];
          float rs[4][2];
          auto probs = [&](int h) {
            pp[h][0] = pack_bf16(ex2((lg[h][0] - mx[h][0]) * sc[0]), ex2((lg[h][1] - mx[h][0]) * sc[0]));
            pp[h][1] = pack_bf16(ex2((lg[h][2] - mx[h][1]) * sc[1]), ex2((lg[h][3] - mx[h][1]) * sc[1]));
            float sum[4];
            mma1688z(sum, pp[h][0], pp[h][1], 0x3f803f80u);
            rs[h][0] = rcp(sum[0]); rs[h][1] = rcp(sum[2]);
            asm volatile("" : "+f"(rs[h][0]), "+f"(rs[h][1]));
          };
          probs(0); probs(1); probs(2); probs(3);
#pragma unroll
          for (int hf = 0; hf < 2; hf++) {
#pragma unroll
            for (int hh = 0; hh < 2; hh++) {
              const int h = hf * 2 + hh, b = h * 4;
              const uint32_t pa = pp[h][0], pb = pp[h][1];
              const uint32_t p0 = pa & ~lm, p1 = pa & z, p2 = pa & lm, p3 = pb & ~lm, p4 = pb & z, p5 = pb & lm;
              const float ra = rs[h][0], rb = rs[h][1];
#pragma unroll
              for (int d = 0; d < 4; d++) {
                float o[4];
                mma16816z(o, p0, p1, p2, p3, kvH[16 + b + d], pkA[32 + 2 * (b + d)]);
                mma1688(o, p4, p5, pkA[32 + 2 * (b + d) + 1], o);
                if (hf == 0) { ob[0][(hh * 4 + d) * 2] = pack_bf16(o[0] * ra, o[1] * ra); ob[0][(hh * 4 + d) * 2 + 1] = pack_bf16(o[2] * rb, o[3] * rb); }
                else { o2[hh * 4 + d][0] = o[0]; o2[hh * 4 + d][1] = o[1]; o2[hh * 4 + d][2] = o[2]; o2[hh * 4 + d][3] = o[3]; }
              }
              if (hf) { r2[2 * hh] = ra; r2[2 * hh + 1] = rb; }
            }
            if (hf == 0) {
#pragma unroll
              for (int i = 0; i < 4; i++) ob[0][4 * i] = pkt_head(ob[0][4 * i]);
              AP(5);
              uint4* op = ptr_add(omail, j * 32768u);
#pragma unroll
              for (int i = 0; i < 4; i++) st_b128(op + i * 32, ob[0][4 * i], ob[0][4 * i + 1], ob[0][4 * i + 2], ob[0][4 * i + 3]);
              z = late_zero(zm);
              AP(6);
            }
          }
        }
        auto finish_o2 = [&](uint32_t z) {
#pragma unroll
          for (int i = 0; i < 4; i++) r2[i] = __uint_as_float(__float_as_uint(r2[i]) | z);
#pragma unroll
          for (int i = 0; i < 8; i++) {
            ob[1][2 * i] = pack_bf16(o2[i][0] * r2[(i >> 2) * 2], o2[i][1] * r2[(i >> 2) * 2]);
            ob[1][2 * i + 1] = pack_bf16(o2[i][2] * r2[(i >> 2) * 2 + 1], o2[i][3] * r2[(i >> 2) * 2 + 1]);
          }
#pragma unroll
          for (int i = 0; i < 4; i++) { ob[1][4 * i] = pkt_head(ob[1][4 * i]); sts128(stage + (warp & 3) * 2048 + i * 512 + l16, ob[1][4 * i], ob[1][4 * i + 1], ob[1][4 * i + 2], ob[1][4 * i + 3]); }
        };
        {
          uint32_t dep = __float_as_uint(r2[0]) | __float_as_uint(r2[2]);
#pragma unroll
          for (int i = 0; i < 8; i++) dep |= __float_as_uint(o2[i][3]);
          const uint32_t cnt = 256 | (dep & zm);
          AP(7);
          if (wg) { asm volatile("bar.arrive 1, %0;" :: "r"(cnt) : "memory"); bar_sync(6, 256); } else bar_sync(1, cnt);
        }
        TLC(3 + it * 6);
        AP(8);
        uint64_t todo;
        { const uint32_t o7 = 0x6543210u | (7u << (4 * j) & 0xfffffffu); todo = (uint64_t)(o7 * 2) | (uint64_t)(o7 * 2 + 0x1111111u) << 28; }
        const uint4* pf[3];
        auto next_ptrs = [&](const uint4* (&p)[3]) {
#pragma unroll
          for (int i = 0; i < 3; i++) p[i] = ptr_add(omail, (((uint32_t)todo >> (4 * i)) & 15u) << 14);
          asm volatile("" : "+l"(p[0]), "+l"(p[1]), "+l"(p[2]));
          todo >>= 12;
        };
        next_ptrs(pf);
        auto batch = [&](int b, bool first, bool three) {
          const int y = 3 - b;
          auto o_fetch = [&]() {
#pragma unroll
            for (int i = 0; i < 8; i++) pkt_load(pf[i >> 2] + (i & 3) * 32, ob[y + (i >> 2)] + 4 * (i & 3));
            if (three) {
#pragma unroll
              for (int i = 0; i < 4; i++) pkt_load(pf[2] + i * 32, ob[y + 2] + 4 * i);
            }
          };
          if (first) {
            c.issue_rs<0, 2>(acc2, ob[0], 0);
            finish_o2(late_zero(zm));
            o_fetch();
            c.issue_rs<1, 2>(acc2, ob[1]);
            if (!wg) asm volatile("bar.arrive 6, 256;" ::: "memory");
          } else {
            o_fetch();
            c.issue_rs<0, 3>(acc2, ob[b]); c.issue_rs<1, 3>(acc2, ob[b + 1]); c.issue_rs<2, 3>(acc2, ob[b + 2]);
          }
          const uint32_t z = late_zero(zm);
          const uint4* pn[3];
          next_ptrs(pn);
          c.wait_full(0);
          uint32_t spins = 0;
          for (;;) {
            bool bad[3];
#pragma unroll
            for (int i = 0; i < 3; i++) bad[i] = ob[y + i][0] == z || ob[y + i][4] == z || ob[y + i][8] == z || ob[y + i][12] == z;
            if (__builtin_expect(!__any_sync(0xffffffffu, bad[0] | bad[1] | bad[2]), 1)) break;
            o_fetch();
            spin_check(++spins);
          }
          if (first) {
            fence_async_smem();
            __syncwarp();
            if (elect_one()) {
              asm volatile("cp.async.bulk.global.shared::cta.bulk_group [%0], [%1], 2048;"
                           :: "l"(scratch<uint4>(P, g * G_BLOCK + G_O + (2 * j + 1) * 16384u + warp * 2048u)), "r"(stage + (warp & 3) * 2048) : "memory");
              bulk_commit();
            }
          }
          pf[0] = pn[0]; pf[1] = pn[1]; pf[2] = pn[2];
          c.drain();
        };
        batch(0, true, true);
#pragma unroll 1
        for (int i = 0; i < 2; i++) { batch(3, false, true); batch(0, false, i == 0); }
        c.issue_rs<0, 2>(acc2, ob[3]); c.issue_rs<1, 2>(acc2, ob[4]);
        if (elect_one()) bulk_wait<0>();
        __syncwarp();
        {
          c.off += 2 << 10;
          c.wait_full(0);
          const uint32_t ra = maddr - (SM_STAGE + wg * 8192) + (c.off << 4);
#pragma unroll
          for (int i = 0; i < 8; i++) ldsm4((ra ^ ((i & 3) << 5)) + (i >> 2) * PAGE, res[4 * i], res[4 * i + 1], res[4 * i + 2], res[4 * i + 3]);
          if (lane < 2) mbar_arrive_cluster(c.ebar + 64 + ((c.n & 7) << 3));
          c.advance<2>();
          c.drain();
        }
        break;
      } else {
        c.steps<128>(acc2, 1 + wg);
        stage_wait();
        glu_slice_acc(acc, 0);
#pragma unroll
        for (int s = 1; s < 8; s++) {
          if (s == 5) c.steps_skip(acc2, t == 1 ? 1 - wg : 2); else c.steps<128>(acc2, (s & 1) || t == 3 ? 2 : 1);
          if (s == 4) stage_publish();
          glu_slice_acc(acc, s);
        }
        c.steps<128>(acc2, 2 - wg);
        stage_publish();
        if (t == 3) {
#pragma unroll
          for (int i = 0; i < 32; i++) { res[i] = 0x80008000u; asm volatile("" : "+r"(res[i])); }
#pragma unroll 1
          for (int i = 0; i < 3; i++) {
            c.steps<128>(acc2, i == 0 ? 15 : i == 1 ? 24 - TAIL_LAG : TAIL_LAG);
            if (i == 0) c.off = 0;
            else if (hl == 3) { if (wg == 1 && i == 1) c.drain(); if (wg + i == 2) bar_sync(5, 256); }
          }
          stage_wait();
          c.drain();
          break;
        }
        c.drain();
        TLC(2 + it * 6);
        c.step<256>(acc, 0);
        acc_fence<64>(acc2);
#pragma unroll
        for (int i = 0; i < 16; i++) {
          pkB[16 + i] = pack_bf16(acc2[2 * i], acc2[2 * i + 1]); pkB[48 + i] = pack_bf16(acc2[32 + 2 * i], acc2[32 + 2 * i + 1]);
          pkB[i] = 0; pkB[32 + i] = 0;
        }
      }
      t++;
#pragma unroll 1
      for (int s = 3 - t; s < 8; s++) {
        c.step<256>(acc, s);
        int act = (t == 3 || s >= 4) ? s : 8;
        asm volatile("" : "+r"(act));
        if (act < 8) {
          if (!(act & 3)) { if (act && t == 3) stage_publish(); else stage_wait(); }
          auto f = [&](int i) { glu_slice(pkB, i); };
          SELECT8(act, f);
        }
      }
#pragma unroll
      for (int s = 0; s < 2; s++) {
        const uint32_t ra = maddr - (SM_STAGE + wg * 8192) + (c.off << 4);
        c.step<256>(acc);
        if (s == 0) stage_publish();
#pragma unroll
        for (int i = 0; i < 4; i++) {
          uint32_t v[4];
          ldsm4(ra ^ (i << 5), v[0], v[1], v[2], v[3]);
#pragma unroll
          for (int e = 0; e < 4; e++) { acc2[32 * s + 8 * i + 2 * e] = bf_lo(v[e]); acc2[32 * s + 8 * i + 2 * e + 1] = bf_hi(v[e]); }
        }
        acc_fence<32>(acc2 + 32 * s);
      }
      c.step<256>(acc);
      }
      const int it = (hl >> 1) * 4 + t;
      acc_fence<64>(acc2);
      TLC(4 + it * 6);
      uint32_t xn[32];
#pragma unroll
      for (int i = 0; i < 16; i++) xn[i] = add_bf16x2(res[i], pack_bf16(acc2[2 * i], acc2[2 * i + 1]));
      const uint32_t xaddr = hl == 3 ? maddr - SM_STAGE : maddr;
      stage_x(xn, 0, xaddr);
#pragma unroll
      for (int i = 16; i < 32; i++) { xn[i] = add_bf16x2(res[i], pack_bf16(acc2[2 * i], acc2[2 * i + 1])); asm volatile("" : "+r"(xn[i])); }
      stage_publish();
      if (hl == 3) { stage_x(xn, 1, xaddr); stage_publish(); TLE(47); TLG(63); break; }
      bar_sync(2 + wg, 128);
      TLC(5 + it * 6);
      c.step_own<256>(acc, dstage, 0);
      stage_x(xn, 1, maddr);
      stage_publish();
      bar_sync(2 + wg, 128);
    }
    }
  }
}

typedef CUresult (*EncodeFn)(CUtensorMap*, CUtensorMapDataType, cuuint32_t, void*, const cuuint64_t*, const cuuint64_t*, const cuuint32_t*,
                             const cuuint32_t*, CUtensorMapInterleave, CUtensorMapSwizzle, CUtensorMapL2promotion, CUtensorMapFloatOOBfill);

void encode(EncodeFn fn, CUtensorMap* m, const void* ptr, int rank, const cuuint64_t* dims, const cuuint64_t* strides, const cuuint32_t* box) {
  cuuint32_t es[5] = {1, 1, 1, 1, 1};
  fn(m, CU_TENSOR_MAP_DATA_TYPE_BFLOAT16, rank, const_cast<void*>(ptr), dims, strides, box, es, CU_TENSOR_MAP_INTERLEAVE_NONE,
     CU_TENSOR_MAP_SWIZZLE_128B, CU_TENSOR_MAP_L2_PROMOTION_L2_128B, CU_TENSOR_MAP_FLOAT_OOB_FILL_NONE);
}

}

extern "C" void kernel_launch(void* const* d_in, const int* in_sizes, int n_in, void* d_out, int out_size) {
  const __nv_bfloat16* x = (const __nv_bfloat16*)d_in[0];
  const __nv_bfloat16* wqkv = (const __nv_bfloat16*)d_in[1];
  const __nv_bfloat16* wo = (const __nv_bfloat16*)d_in[2];
  const __nv_bfloat16* w1 = (const __nv_bfloat16*)d_in[4];
  const __nv_bfloat16* w3 = (const __nv_bfloat16*)d_in[5];
  const __nv_bfloat16* w2 = (const __nv_bfloat16*)d_in[6];

  void* fnp = nullptr; cudaDriverEntryPointQueryResult qr;
  cudaGetDriverEntryPoint("cuTensorMapEncodeTiled", &fnp, cudaEnableDefault, &qr);
  EncodeFn fn = (EncodeFn)fnp;
  void* sym;
  cudaGetSymbolAddress(&sym, g_scratch);
  uint8_t* scr = (uint8_t*)(((uintptr_t)sym + G_PAGE - 1) / G_PAGE * G_PAGE);

  Params P = {};
  { cuuint64_t d[3] = {DM, 2, SEQ / 2}, s[2] = {DM * 2, DM * 4}; cuuint32_t b[3] = {64, 1, 128}, b2[3] = {64, 1, 64};
    encode(fn, &P.map[M_XIN], x, 3, d, s, b); encode(fn, &P.map[M_XIN64], x, 3, d, s, b2);
    encode(fn, &P.map[M_OUT_LD], d_out, 3, d, s, b); encode(fn, &P.map[M_OUT_ST], d_out, 3, d, s, b2); }
  { cuuint64_t d[3] = {FF, 16, 128}, s[2] = {G_BLOCK, FF * 2}; cuuint32_t b[3] = {64, 1, 128}, b2[3] = {64, 1, H_ROWS};
    encode(fn, &P.map[M_H_LD], scr + G_H, 3, d, s, b); encode(fn, &P.map[M_H_ST], scr + G_H, 3, d, s, b2); }
  { const cuuint32_t b2[3] = {64, 64, 2}, b1[3] = {64, 64, 1};
    { cuuint64_t d[3] = {64, DM, 48}, s[2] = {3 * DM * 2, 128}; encode(fn, &P.map[M_WKV], wqkv, 3, d, s, b2); encode(fn, &P.map[M_WQ], wqkv, 3, d, s, b1); }
    { cuuint64_t d[3] = {64, DM, 16}, s[2] = {DM * 2, 128}; encode(fn, &P.map[M_WO], wo, 3, d, s, b1); }
    { cuuint64_t d[3] = {64, FF, 16}, s[2] = {DM * 2, 128}; encode(fn, &P.map[M_W2], w2, 3, d, s, b1); }
    { cuuint64_t d[3] = {64, DM, FF / 64}, s[2] = {FF * 2, 128};
      encode(fn, &P.map[M_W1], w1, 3, d, s, b2); encode(fn, &P.map[M_W3], w3, 3, d, s, b2);
      encode(fn, &P.map[M_W1H], w1, 3, d, s, b1); encode(fn, &P.map[M_W3H], w3, 3, d, s, b1); }
  }
  P.scratch = scr; P.x = x; P.wqkv = wqkv; P.wo = wo; P.w2 = w2;
  int dev = 0, sms = 0;
  cudaGetDevice(&dev);
  cudaDeviceGetAttribute(&sms, cudaDevAttrMultiProcessorCount, dev);
  P.use_smid = (sms == 132);
  cudaFuncSetAttribute(fused_kernel, cudaFuncAttributeMaxDynamicSharedMemorySize, SM_ALLOC);
  fused_kernel<<<132, 384, SM_ALLOC>>>(P);
}
```

```cpp
#include <cuda_runtime.h>
#include <cuda_bf16.h>
#include <cuda.h>
#include <stdint.h>
#include <math.h>

namespace {

constexpr int SEQ = 2048, DM = 1024, FF = 3584;
constexpr float LN_EPS = 1e-5f;
constexpr float LOG2E = 1.4426950408889634f;

#define G_SKEW 4096
constexpr uint32_t G_PAGE = 2u << 20, G_BLOCK = G_PAGE + G_SKEW;
constexpr uint32_t G_H = 0;
constexpr uint32_t G_O = G_H + 128 * FF * 2;
constexpr uint32_t G_STATS = G_O + 128 * DM * 2;
constexpr uint32_t G_FLAGS = G_STATS + 4 * 128 * 64;
static_assert(G_FLAGS + 4096 + 15 * G_SKEW <= G_PAGE, "");
constexpr uint32_t G_HALO = 16 * G_PAGE;
constexpr uint32_t G_CS = G_HALO + 2 * 16 * 8 * 4096;
constexpr uint32_t G_EPOCH = G_CS + (3 * DM + 2 * FF) * 16;
__device__ __align__(1024) uint8_t g_scratch[18 * G_PAGE];

enum { M_XIN, M_XIN64, M_H_LD, M_H_ST, M_OUT_LD, M_OUT_ST, M_WKV, M_WQ, M_WO, M_W1, M_W3, M_W1H, M_W3H, M_W2, M_COUNT };
struct alignas(64) Params {
  CUtensorMap map[M_COUNT];
  uint8_t* scratch;
  const __nv_bfloat16* x;
  const __nv_bfloat16* wqkv;
  const __nv_bfloat16* wo;
  const __nv_bfloat16* w2;
  int use_smid;
};

constexpr uint32_t PAGE = 16384, NPAGE = 12;
constexpr uint32_t SM_STAGE = NPAGE * PAGE;
constexpr uint32_t SM_BAR = SM_STAGE + 2 * PAGE;
constexpr uint32_t SM_CS = SM_BAR + 256;
constexpr uint32_t SM_TOTAL = SM_CS + 1536;
constexpr uint32_t SM_ALLOC = SM_TOTAL;
static_assert(SM_ALLOC <= 232448, "shared memory");
constexpr uint32_t BAR_FULL = SM_BAR, BAR_EMPTY = SM_BAR + 64, BAR_SFULL = SM_BAR + 128;
constexpr uint32_t BAR_XFULL = SM_BAR + 160, BAR_CSE = SM_BAR + 168;
constexpr uint32_t BAR_SEMPTY = SM_BAR + 176, BAR_CSF = SM_BAR + 184, BAR_XIN = SM_BAR + 200;
constexpr uint32_t BAR_CLR = SM_BAR + 240, BAR_CLR2 = SM_BAR + 248, BAR_TAG = SM_BAR + 216, SM_ROLE = SM_BAR + 224, SM_TAG = SM_BAR + 228, SM_SEEN = SM_BAR + 232;
enum { EV_XA, EV_XA2, EV_H0, EV_H3, EV_H1, EV_H2, EV_XB, EV_XB2, EV_N };

#define WSKIP 15
struct Sched { uint32_t pat[16]; uint32_t page0[16]; bool ok; };
constexpr int seg_steps(int seg) { return seg == 0 || seg == 3 ? 18 : seg == 1 || seg == 4 ? 14 : seg == 2 ? 7 : seg == 7 ? 54 : 16; }
constexpr int step_pages(int seg, int i) {
  return seg == 0 || seg == 3 ? (i < 2 ? 2 : i < 4 ? 1 : 3) : seg == 5 || seg == 6 || (seg == 2 && i >= 1 && i <= 4) ? 3 : 2;
}
constexpr Sched make_sched() {
  Sched s = {};
  int owner[NPAGE] = {-1, -1, -1, -1, -1, -1, -1, -1, -1, -1, -1, -1};
  int n = 0, tail = 0, page = 0;
  s.ok = true;
  for (int sg = 0; sg < 16; sg++) {
    const int seg = sg % 8;
    s.page0[sg] = page;
    for (int i = 0; i < seg_steps(seg); i++) {
      const int p = step_pages(seg, i);
      if ((seg == 2 && i == 6) || (seg == 4 && i == 8)) page = (page + 2) % NPAGE;
      if ((seg == 5 || seg == 6) && i == WSKIP) page = (page + 3) % NPAGE;
      if (page + p > (int)NPAGE) { s.ok = false; return s; }
      int need = n - 8;
      for (int q = 0; q < p; q++) { if (owner[page + q] > need) need = owner[page + q]; owner[page + q] = n; }
      int nw = need + 1 - tail; if (nw < 0) nw = 0;
      tail += nw;
      if (i < 16) s.pat[sg] |= (uint32_t)nw << (2 * i); else if (nw != 1) s.ok = false;
      if (nw > 3) s.ok = false;
      page = (page + p) % NPAGE; n++;
    }
  }
  for (int sg = 0; sg < 8; sg++) if (s.page0[sg] != s.page0[sg + 8] || (sg && s.pat[sg] != s.pat[sg + 8])) s.ok = false;
  return s;
}
constexpr Sched SCHED = make_sched();
static_assert(SCHED.ok && SCHED.page0[0] == 0 && SCHED.page0[3] == 0 && SCHED.page0[5] == 6 && SCHED.page0[2] == 4 && SCHED.page0[7] == 0 && (SCHED.pat[0] & 0xfff) == 0, "ring schedule");
template <int SEG> struct Pat { static constexpr uint32_t v = SCHED.pat[SEG]; };

constexpr int H_ROWS = 16;
#define RES_AT 26
#define TAIL_LAG 3
__device__ __forceinline__ uint32_t smem_u32(const void* p) { return (uint32_t)__cvta_generic_to_shared(p); }
__device__ __forceinline__ void mbar_init(uint32_t bar, uint32_t cnt) { asm volatile("mbarrier.init.shared::cta.b64 [%0], %1;" :: "r"(bar), "r"(cnt)); }
__device__ __forceinline__ void mbar_expect_tx(uint32_t bar, uint32_t bytes) { asm volatile("mbarrier.arrive.expect_tx.shared::cta.b64 _, [%0], %1;" :: "r"(bar), "r"(bytes) : "memory"); }
__device__ __forceinline__ void mbar_arrive(uint32_t bar) { asm volatile("mbarrier.arrive.shared::cta.b64 _, [%0];" :: "r"(bar) : "memory"); }
__device__ __forceinline__ void mbar_wait(uint32_t bar, uint32_t parity) {
  asm volatile("{\n.reg .pred p;\n.reg .u32 n;\nmov.u32 n, 0;\nLAB_WAIT:\n"
               "mbarrier.try_wait.parity.shared::cta.b64 p, [%0], %1;\n@p bra LAB_DONE;\n"
               "add.u32 n, n, 1;\nsetp.lt.u32 p, n, 4194304;\n@p bra LAB_WAIT;\ntrap;\nLAB_DONE:\n}" :: "r"(bar), "r"(parity) : "memory");
}
__device__ __forceinline__ void mbar_wait_fast(uint32_t bar, uint32_t parity) {
  asm volatile("{\n.reg .pred p;\nLAB_WAIT:\nmbarrier.try_wait.parity.shared::cta.b64 p, [%0], %1;\n@!p bra LAB_WAIT;\n}" :: "r"(bar), "r"(parity) : "memory");
}
__device__ __forceinline__ void spin_check(uint32_t n) { asm volatile("{\n.reg .pred p;\nsetp.ge.u32 p, %0, 4194304;\n@p st.volatile.global.u32 [%1], %0;\n}" :: "r"(n), "l"(0ull)); }
__device__ __forceinline__ void tma_ld3(uint32_t dst, const CUtensorMap* m, uint32_t bar, int c0, int c1, int c2) {
  asm volatile("cp.async.bulk.tensor.3d.shared::cluster.global.mbarrier::complete_tx::bytes [%0], [%1, {%3, %4, %5}], [%2];" :: "r"(dst), "l"(m), "r"(bar), "r"(c0), "r"(c1), "r"(c2) : "memory");
}
__device__ __forceinline__ void tma_ld3_mc(uint32_t dst, const CUtensorMap* m, uint32_t bar, int c0, int c1, int c2, uint16_t mask) {
  asm volatile("cp.async.bulk.tensor.3d.shared::cluster.global.mbarrier::complete_tx::bytes.multicast::cluster [%0], [%1, {%3, %4, %5}], [%2], %6;"
               :: "r"(dst), "l"(m), "r"(bar), "r"(c0), "r"(c1), "r"(c2), "h"(mask) : "memory");
}
__device__ __forceinline__ uint32_t mapa(uint32_t addr, uint32_t cta) { uint32_t r; asm("mapa.shared::cluster.u32 %0, %1, %2;" : "=r"(r) : "r"(addr), "r"(cta)); return r; }
__device__ __forceinline__ void mbar_arrive_cluster(uint32_t bar) { asm volatile("mbarrier.arrive.shared::cluster.b64 _, [%0];" :: "r"(bar) : "memory"); }
__device__ __forceinline__ void tma_st3(const CUtensorMap* m, uint32_t src, int c0, int c1, int c2) {
  asm volatile("cp.async.bulk.tensor.3d.global.shared::cta.bulk_group [%0, {%2, %3, %4}], [%1];" :: "l"(m), "r"(src), "r"(c0), "r"(c1), "r"(c2) : "memory");
}
__device__ __forceinline__ void bulk_commit() { asm volatile("cp.async.bulk.commit_group;" ::: "memory"); }
template <int N> __device__ __forceinline__ void bulk_wait() { asm volatile("cp.async.bulk.wait_group %0;" :: "n"(N) : "memory"); }
__device__ __forceinline__ void fence_async_smem() { asm volatile("fence.proxy.async.shared::cta;" ::: "memory"); }
__device__ __forceinline__ void fence_async_global() { asm volatile("fence.proxy.async.global;" ::: "memory"); }
__device__ __forceinline__ bool elect_one() { uint32_t p; asm volatile("{\n.reg .pred P;\nelect.sync _|P, 0xffffffff;\nselp.u32 %0, 1, 0, P;\n}" : "=r"(p)); return p; }
__device__ __forceinline__ void prefetch_map(const CUtensorMap* m) { asm volatile("prefetch.tensormap [%0];" :: "l"(m) : "memory"); }
__device__ __forceinline__ void prefetch_l2(const void* p, uint32_t bytes) { asm volatile("cp.async.bulk.prefetch.L2.global [%0], %1;" :: "l"(p), "r"(bytes) : "memory"); }
__device__ __forceinline__ void wgmma_fence() { asm volatile("wgmma.fence.sync.aligned;" ::: "memory"); }
__device__ __forceinline__ void wgmma_commit() { asm volatile("wgmma.commit_group.sync.aligned;" ::: "memory"); }
template <int N> __device__ __forceinline__ void wgmma_wait() { asm volatile("wgmma.wait_group.sync.aligned %0;" :: "n"(N) : "memory"); }
__device__ __forceinline__ uint32_t desc_lo(uint32_t addr, uint32_t lbo) { return ((addr & 0x3FFFF) >> 4) | ((lbo >> 4) << 16); }
__device__ __forceinline__ uint64_t desc64(uint32_t lo) { uint64_t r; asm("mov.b64 %0, {%1, %2};" : "=l"(r) : "r"(lo), "r"(0x40000040u)); return r; }
__device__ __forceinline__ void bar_sync(int id, int n) { asm volatile("bar.sync %0, %1;" :: "r"(id), "r"(n) : "memory"); }
__device__ __forceinline__ uint32_t pack_bf16(float lo, float hi) { uint32_t r; asm("cvt.rn.bf16x2.f32 %0, %1, %2;" : "=r"(r) : "f"(hi), "f"(lo)); return r; }
__device__ __forceinline__ float bf_lo(uint32_t v) { return __uint_as_float(v << 16); }
__device__ __forceinline__ float bf_hi(uint32_t v) { return __uint_as_float(v & 0xffff0000u); }
__device__ __forceinline__ float ex2(float x) { float r; asm("ex2.approx.ftz.f32 %0, %1;" : "=f"(r) : "f"(x)); return r; }
__device__ __forceinline__ float rcp(float x) { float r; asm("rcp.approx.ftz.f32 %0, %1;" : "=f"(r) : "f"(x)); return r; }
__device__ __forceinline__ void stsm4(uint32_t a, uint32_t r0, uint32_t r1, uint32_t r2, uint32_t r3) {
  asm volatile("stmatrix.sync.aligned.m8n8.x4.shared.b16 [%0], {%1, %2, %3, %4};" :: "r"(a), "r"(r0), "r"(r1), "r"(r2), "r"(r3) : "memory");
}
__device__ __forceinline__ void ldsm4(uint32_t a, uint32_t& r0, uint32_t& r1, uint32_t& r2, uint32_t& r3) {
  asm volatile("ldmatrix.sync.aligned.m8n8.x4.shared.b16 {%0, %1, %2, %3}, [%4];" : "=r"(r0), "=r"(r1), "=r"(r2), "=r"(r3) : "r"(a) : "memory");
}
__device__ __forceinline__ uint32_t movm(uint32_t v) { uint32_t r; asm volatile("movmatrix.sync.aligned.m8n8.trans.b16 %0, %1;" : "=r"(r) : "r"(v)); return r; }
__device__ __forceinline__ void sts128(uint32_t a, uint32_t r0, uint32_t r1, uint32_t r2, uint32_t r3) {
  asm volatile("st.shared.v4.b32 [%0], {%1, %2, %3, %4};" :: "r"(a), "r"(r0), "r"(r1), "r"(r2), "r"(r3) : "memory");
}
__device__ __forceinline__ void lds128(uint32_t a, uint32_t& r0, uint32_t& r1, uint32_t& r2, uint32_t& r3) {
  asm volatile("ld.shared.v4.b32 {%0, %1, %2, %3}, [%4];" : "=r"(r0), "=r"(r1), "=r"(r2), "=r"(r3) : "r"(a) : "memory");
}
__device__ __forceinline__ uint32_t add_bf16x2(uint32_t a, uint32_t b) { uint32_t r; asm("add.rn.bf16x2 %0, %1, %2;" : "=r"(r) : "r"(a), "r"(b)); return r; }
__device__ __forceinline__ void sts32f(uint32_t a, float v) { asm volatile("st.shared.f32 [%0], %1;" :: "r"(a), "f"(v) : "memory"); }
__device__ __forceinline__ void mma16816(float (&d)[4], uint32_t a0, uint32_t a1, uint32_t a2, uint32_t a3, uint32_t b0, uint32_t b1, const float (&c)[4]) {
  asm("mma.sync.aligned.m16n8k16.row.col.f32.bf16.bf16.f32 {%0, %1, %2, %3}, {%4, %5, %6, %7}, {%8, %9}, {%10, %11, %12, %13};"
      : "=f"(d[0]), "=f"(d[1]), "=f"(d[2]), "=f"(d[3]) : "r"(a0), "r"(a1), "r"(a2), "r"(a3), "r"(b0), "r"(b1), "f"(c[0]), "f"(c[1]), "f"(c[2]), "f"(c[3]));
}
__device__ __forceinline__ void mma1688(float (&d)[4], uint32_t a0, uint32_t a1, uint32_t b0, const float (&c)[4]) {
  asm("mma.sync.aligned.m16n8k8.row.col.f32.bf16.bf16.f32 {%0, %1, %2, %3}, {%4, %5}, {%6}, {%7, %8, %9, %10};"
      : "=f"(d[0]), "=f"(d[1]), "=f"(d[2]), "=f"(d[3]) : "r"(a0), "r"(a1), "r"(b0), "f"(c[0]), "f"(c[1]), "f"(c[2]), "f"(c[3]));
}
__device__ __forceinline__ void mma16816z(float (&d)[4], uint32_t a0, uint32_t a1, uint32_t a2, uint32_t a3, uint32_t b0, uint32_t b1) {
  asm("mma.sync.aligned.m16n8k16.row.col.f32.bf16.bf16.f32 {%0, %1, %2, %3}, {%4, %5, %6, %7}, {%8, %9}, {0f00000000, 0f00000000, 0f00000000, 0f00000000};"
      : "=f"(d[0]), "=f"(d[1]), "=f"(d[2]), "=f"(d[3]) : "r"(a0), "r"(a1), "r"(a2), "r"(a3), "r"(b0), "r"(b1));
}
__device__ __forceinline__ void mma1688z(float (&d)[4], uint32_t a0, uint32_t a1, uint32_t b0) {
  asm("mma.sync.aligned.m16n8k8.row.col.f32.bf16.bf16.f32 {%0, %1, %2, %3}, {%4, %5}, {%6}, {0f00000000, 0f00000000, 0f00000000, 0f00000000};"
      : "=f"(d[0]), "=f"(d[1]), "=f"(d[2]), "=f"(d[3]) : "r"(a0), "r"(a1), "r"(b0));
}
__device__ __forceinline__ uint32_t bar_sync_zero(int id, int n) {
  uint32_t r;
  asm volatile("{\n.reg .pred p;\nsetp.eq.u32 p, %1, 0;\nbarrier.cta.red.popc.aligned.u32 %0, %1, %2, p;\n}" : "=r"(r) : "r"(id), "r"(n) : "memory");
  return r;
}
__device__ __forceinline__ uint32_t late_zero(uint32_t zm) { uint32_t c; asm volatile("mov.u32 %0, %%clock;" : "=r"(c) :: "memory"); return c & zm; }
__device__ __forceinline__ void st_b128(uint4* p, uint32_t a, uint32_t b, uint32_t c, uint32_t d) {
  asm volatile("{\n.reg .b128 t;\n.reg .b64 lo, hi;\nmov.b64 lo, {%0, %1};\nmov.b64 hi, {%2, %3};\nmov.b128 t, {lo, hi};\nst.relaxed.gpu.global.b128 [%4], t;\n}"
               :: "r"(a), "r"(b), "r"(c), "r"(d), "l"(p) : "memory");
}
__device__ __forceinline__ uint32_t pkt_head(uint32_t a) { return a ? a : 0x8000u; }
__device__ __forceinline__ void gen_store(uint4* p, uint32_t a, uint32_t b, uint32_t c, uint32_t d) {
  asm volatile("{\n.reg .b128 t;\n.reg .b64 lo, hi;\nmov.b64 lo, {%0, %1};\nmov.b64 hi, {%2, %3};\nmov.b128 t, {lo, hi};\nst.relaxed.gpu.b128 [%4], t;\n}"
               :: "r"(a), "r"(b), "r"(c), "r"(d), "l"(p) : "memory");
}
__device__ __forceinline__ void gen_load(const uint4* p, uint32_t* v) {
  asm volatile("{\n.reg .b128 t;\n.reg .b64 lo, hi;\nld.relaxed.gpu.b128 t, [%4];\nmov.b128 {lo, hi}, t;\nmov.b64 {%0, %1}, lo;\nmov.b64 {%2, %3}, hi;\n}"
               : "=r"(v[0]), "=r"(v[1]), "=r"(v[2]), "=r"(v[3]) : "l"(p) : "memory");
}
__device__ __forceinline__ void pkt_load(const uint4* p, uint32_t* v) {
  asm volatile("{\n.reg .b128 t;\n.reg .b64 lo, hi;\nld.relaxed.gpu.global.b128 t, [%4];\nmov.b128 {lo, hi}, t;\nmov.b64 {%0, %1}, lo;\nmov.b64 {%2, %3}, hi;\n}"
               : "=r"(v[0]), "=r"(v[1]), "=r"(v[2]), "=r"(v[3]) : "l"(p) : "memory");
}
__device__ __forceinline__ uint32_t ld_relaxed(const uint32_t* p) { uint32_t v; asm volatile("ld.relaxed.gpu.global.u32 %0, [%1];" : "=r"(v) : "l"(p) : "memory"); return v; }
__device__ __forceinline__ uint4 ld_relaxed4(const void* p) { uint4 v; asm volatile("ld.relaxed.gpu.global.v4.u32 {%0, %1, %2, %3}, [%4];" : "=r"(v.x), "=r"(v.y), "=r"(v.z), "=r"(v.w) : "l"(p) : "memory"); return v; }
__device__ __forceinline__ void st_relaxed(uint32_t* p, uint32_t v) { asm volatile("st.relaxed.gpu.global.u32 [%0], %1;" :: "l"(p), "r"(v) : "memory"); }
__device__ __forceinline__ void st_relaxed2(void* p, uint32_t a, uint32_t b) { asm volatile("st.relaxed.gpu.global.v2.u32 [%0], {%1, %2};" :: "l"(p), "r"(a), "r"(b) : "memory"); }
__device__ __forceinline__ void red_release(uint32_t* p, uint32_t v) { asm volatile("red.release.gpu.global.add.u32 [%0], %1;" :: "l"(p), "r"(v) : "memory"); }
__device__ __forceinline__ uint32_t tagf(float v, uint32_t tag) { return (__float_as_uint(v) & ~15u) | (tag & 15u); }
__device__ __forceinline__ bool tag_ok4(const uint4& v, uint32_t tag) { return (((v.x ^ tag) | (v.y ^ tag) | (v.z ^ tag) | (v.w ^ tag)) & 15u) == 0; }
__device__ __forceinline__ float untag(uint32_t v) { return __uint_as_float(v & ~15u); }
template <typename T> __device__ __forceinline__ T* ptr_add(T* p, uint32_t bytes) {
  uint64_t r;
  asm("{\n.reg .u32 lo, hi;\nmov.b64 {lo, hi}, %1;\nadd.cc.u32 lo, lo, %2;\naddc.u32 hi, hi, 0;\nmov.b64 %0, {lo, hi};\n}" : "=l"(r) : "l"(p), "r"(bytes));
  return (T*)r;
}
#define TL(who, slot) do {} while (0)
#define TLC(slot) do {} while (0)
#define TLE(slot) do {} while (0)
#define ST(who, n) do {} while (0)
#define AP(i) do {} while (0)
#define SP(v) do {} while (0)
#define TLG(slot) do {} while (0)
#define STA() do {} while (0)
#define STB(n) do {} while (0)

__device__ __forceinline__ void wgmma_n128(float (&d)[64], uint64_t da, uint64_t db, int scale_d) {
  asm volatile("{\n.reg .pred p;\nsetp.ne.b32 p, %66, 0;\n"
    "wgmma.mma_async.sync.aligned.m64n128k16.f32.bf16.bf16 "
    "{%0, %1, %2, %3, %4, %5, %6, %7, %8, %9, %10, %11, %12, %13, %14, %15, "
    "%16, %17, %18, %19, %20, %21, %22, %23, %24, %25, %26, %27, %28, %29, %30, %31, "
    "%32, %33, %34, %35, %36, %37, %38, %39, %40, %41, %42, %43, %44, %45, %46, %47, "
    "%48, %49, %50, %51, %52, %53, %54, %55, %56, %57, %58, %59, %60, %61, %62, %63}, "
    "%64, %65, p, 1, 1, 0, 1;\n}\n"
    : "+f"(d[0]), "+f"(d[1]), "+f"(d[2]), "+f"(d[3]), "+f"(d[4]), "+f"(d[5]), "+f"(d[6]), "+f"(d[7]),
      "+f"(d[8]), "+f"(d[9]), "+f"(d[10]), "+f"(d[11]), "+f"(d[12]), "+f"(d[13]), "+f"(d[14]), "+f"(d[15]),
      "+f"(d[16]), "+f"(d[17]), "+f"(d[18]), "+f"(d[19]), "+f"(d[20]), "+f"(d[21]), "+f"(d[22]), "+f"(d[23]),
      "+f"(d[24]), "+f"(d[25]), "+f"(d[26]), "+f"(d[27]), "+f"(d[28]), "+f"(d[29]), "+f"(d[30]), "+f"(d[31]),
      "+f"(d[32]), "+f"(d[33]), "+f"(d[34]), "+f"(d[35]), "+f"(d[36]), "+f"(d[37]), "+f"(d[38]), "+f"(d[39]),
      "+f"(d[40]), "+f"(d[41]), "+f"(d[42]), "+f"(d[43]), "+f"(d[44]), "+f"(d[45]), "+f"(d[46]), "+f"(d[47]),
      "+f"(d[48]), "+f"(d[49]), "+f"(d[50]), "+f"(d[51]), "+f"(d[52]), "+f"(d[53]), "+f"(d[54]), "+f"(d[55]),
      "+f"(d[56]), "+f"(d[57]), "+f"(d[58]), "+f"(d[59]), "+f"(d[60]), "+f"(d[61]), "+f"(d[62]), "+f"(d[63])
    : "l"(da), "l"(db), "r"(scale_d));
}
__device__ __forceinline__ void wgmma_n256(float (&d)[128], uint64_t da, uint64_t db, int scale_d) {
  asm volatile("{\n.reg .pred p;\nsetp.ne.b32 p, %130, 0;\n"
    "wgmma.mma_async.sync.aligned.m64n256k16.f32.bf16.bf16 "
    "{%0, %1, %2, %3, %4, %5, %6, %7, %8, %9, %10, %11, %12, %13, %14, %15, "
    "%16, %17, %18, %19, %20, %21, %22, %23, %24, %25, %26, %27, %28, %29, %30, %31, "
    "%32, %33, %34, %35, %36, %37, %38, %39, %40, %41, %42, %43, %44, %45, %46, %47, "
    "%48, %49, %50, %51, %52, %53, %54, %55, %56, %57, %58, %59, %60, %61, %62, %63, "
    "%64, %65, %66, %67, %68, %69, %70, %71, %72, %73, %74, %75, %76, %77, %78, %79, "
    "%80, %81, %82, %83, %84, %85, %86, %87, %88, %89, %90, %91, %92, %93, %94, %95, "
    "%96, %97, %98, %99, %100, %101, %102, %103, %104, %105, %106, %107, %108, %109, %110, %111, "
    "%112, %113, %114, %115, %116, %117, %118, %119, %120, %121, %122, %123, %124, %125, %126, %127}, "
    "%128, %129, p, 1, 1, 0, 1;\n}\n"
    : "+f"(d[0]), "+f"(d[1]), "+f"(d[2]), "+f"(d[3]), "+f"(d[4]), "+f"(d[5]), "+f"(d[6]), "+f"(d[7]),
      "+f"(d[8]), "+f"(d[9]), "+f"(d[10]), "+f"(d[11]), "+f"(d[12]), "+f"(d[13]), "+f"(d[14]), "+f"(d[15]),
      "+f"(d[16]), "+f"(d[17]), "+f"(d[18]), "+f"(d[19]), "+f"(d[20]), "+f"(d[21]), "+f"(d[22]), "+f"(d[23]),
      "+f"(d[24]), "+f"(d[25]), "+f"(d[26]), "+f"(d[27]), "+f"(d[28]), "+f"(d[29]), "+f"(d[30]), "+f"(d[31]),
      "+f"(d[32]), "+f"(d[33]), "+f"(d[34]), "+f"(d[35]), "+f"(d[36]), "+f"(d[37]), "+f"(d[38]), "+f"(d[39]),
      "+f"(d[40]), "+f"(d[41]), "+f"(d[42]), "+f"(d[43]), "+f"(d[44]), "+f"(d[45]), "+f"(d[46]), "+f"(d[47]),
      "+f"(d[48]), "+f"(d[49]), "+f"(d[50]), "+f"(d[51]), "+f"(d[52]), "+f"(d[53]), "+f"(d[54]), "+f"(d[55]),
      "+f"(d[56]), "+f"(d[57]), "+f"(d[58]), "+f"(d[59]), "+f"(d[60]), "+f"(d[61]), "+f"(d[62]), "+f"(d[63]),
      "+f"(d[64]), "+f"(d[65]), "+f"(d[66]), "+f"(d[67]), "+f"(d[68]), "+f"(d[69]), "+f"(d[70]), "+f"(d[71]),
      "+f"(d[72]), "+f"(d[73]), "+f"(d[74]), "+f"(d[75]), "+f"(d[76]), "+f"(d[77]), "+f"(d[78]), "+f"(d[79]),
      "+f"(d[80]), "+f"(d[81]), "+f"(d[82]), "+f"(d[83]), "+f"(d[84]), "+f"(d[85]), "+f"(d[86]), "+f"(d[87]),
      "+f"(d[88]), "+f"(d[89]), "+f"(d[90]), "+f"(d[91]), "+f"(d[92]), "+f"(d[93]), "+f"(d[94]), "+f"(d[95]),
      "+f"(d[96]), "+f"(d[97]), "+f"(d[98]), "+f"(d[99]), "+f"(d[100]), "+f"(d[101]), "+f"(d[102]), "+f"(d[103]),
      "+f"(d[104]), "+f"(d[105]), "+f"(d[106]), "+f"(d[107]), "+f"(d[108]), "+f"(d[109]), "+f"(d[110]), "+f"(d[111]),
      "+f"(d[112]), "+f"(d[113]), "+f"(d[114]), "+f"(d[115]), "+f"(d[116]), "+f"(d[117]), "+f"(d[118]), "+f"(d[119]),
      "+f"(d[120]), "+f"(d[121]), "+f"(d[122]), "+f"(d[123]), "+f"(d[124]), "+f"(d[125]), "+f"(d[126]), "+f"(d[127])
    : "l"(da), "l"(db), "r"(scale_d));
}
__device__ __forceinline__ void wgmma_rs_n128(float (&d)[64], const uint32_t* a, uint64_t db, int scale_d) {
  asm volatile("{\n.reg .pred p;\nsetp.ne.b32 p, %69, 0;\n"
    "wgmma.mma_async.sync.aligned.m64n128k16.f32.bf16.bf16 "
    "{%0, %1, %2, %3, %4, %5, %6, %7, %8, %9, %10, %11, %12, %13, %14, %15, "
    "%16, %17, %18, %19, %20, %21, %22, %23, %24, %25, %26, %27, %28, %29, %30, %31, "
    "%32, %33, %34, %35, %36, %37, %38, %39, %40, %41, %42, %43, %44, %45, %46, %47, "
    "%48, %49, %50, %51, %52, %53, %54, %55, %56, %57, %58, %59, %60, %61, %62, %63}, "
    "{%64, %65, %66, %67}, %68, p, 1, 1, 1;\n}\n"
    : "+f"(d[0]), "+f"(d[1]), "+f"(d[2]), "+f"(d[3]), "+f"(d[4]), "+f"(d[5]), "+f"(d[6]), "+f"(d[7]),
      "+f"(d[8]), "+f"(d[9]), "+f"(d[10]), "+f"(d[11]), "+f"(d[12]), "+f"(d[13]), "+f"(d[14]), "+f"(d[15]),
      "+f"(d[16]), "+f"(d[17]), "+f"(d[18]), "+f"(d[19]), "+f"(d[20]), "+f"(d[21]), "+f"(d[22]), "+f"(d[23]),
      "+f"(d[24]), "+f"(d[25]), "+f"(d[26]), "+f"(d[27]), "+f"(d[28]), "+f"(d[29]), "+f"(d[30]), "+f"(d[31]),
      "+f"(d[32]), "+f"(d[33]), "+f"(d[34]), "+f"(d[35]), "+f"(d[36]), "+f"(d[37]), "+f"(d[38]), "+f"(d[39]),
      "+f"(d[40]), "+f"(d[41]), "+f"(d[42]), "+f"(d[43]), "+f"(d[44]), "+f"(d[45]), "+f"(d[46]), "+f"(d[47]),
      "+f"(d[48]), "+f"(d[49]), "+f"(d[50]), "+f"(d[51]), "+f"(d[52]), "+f"(d[53]), "+f"(d[54]), "+f"(d[55]),
      "+f"(d[56]), "+f"(d[57]), "+f"(d[58]), "+f"(d[59]), "+f"(d[60]), "+f"(d[61]), "+f"(d[62]), "+f"(d[63])
    : "r"(a[0]), "r"(a[1]), "r"(a[2]), "r"(a[3]), "l"(db), "r"(scale_d));
}
__device__ __forceinline__ void wgmma_n64(float* d, uint64_t da, uint64_t db, int scale_d) {
  asm volatile("{\n.reg .pred p;\nsetp.ne.b32 p, %34, 0;\n"
    "wgmma.mma_async.sync.aligned.m64n64k16.f32.bf16.bf16 "
    "{%0, %1, %2, %3, %4, %5, %6, %7, %8, %9, %10, %11, %12, %13, %14, %15, "
    "%16, %17, %18, %19, %20, %21, %22, %23, %24, %25, %26, %27, %28, %29, %30, %31}, "
    "%32, %33, p, 1, 1, 0, 1;\n}\n"
    : "+f"(d[0]), "+f"(d[1]), "+f"(d[2]), "+f"(d[3]), "+f"(d[4]), "+f"(d[5]), "+f"(d[6]), "+f"(d[7]),
      "+f"(d[8]), "+f"(d[9]), "+f"(d[10]), "+f"(d[11]), "+f"(d[12]), "+f"(d[13]), "+f"(d[14]), "+f"(d[15]),
      "+f"(d[16]), "+f"(d[17]), "+f"(d[18]), "+f"(d[19]), "+f"(d[20]), "+f"(d[21]), "+f"(d[22]), "+f"(d[23]),
      "+f"(d[24]), "+f"(d[25]), "+f"(d[26]), "+f"(d[27]), "+f"(d[28]), "+f"(d[29]), "+f"(d[30]), "+f"(d[31])
    : "l"(da), "l"(db), "r"(scale_d));
}
__device__ __forceinline__ void wgmma_rs_n64(float* d, const uint32_t* a, uint64_t db, int scale_d) {
  asm volatile("{\n.reg .pred p;\nsetp.ne.b32 p, %37, 0;\n"
    "wgmma.mma_async.sync.aligned.m64n64k16.f32.bf16.bf16 "
    "{%0, %1, %2, %3, %4, %5, %6, %7, %8, %9, %10, %11, %12, %13, %14, %15, "
    "%16, %17, %18, %19, %20, %21, %22, %23, %24, %25, %26, %27, %28, %29, %30, %31}, "
    "{%32, %33, %34, %35}, %36, p, 1, 1, 1;\n}\n"
    : "+f"(d[0]), "+f"(d[1]), "+f"(d[2]), "+f"(d[3]), "+f"(d[4]), "+f"(d[5]), "+f"(d[6]), "+f"(d[7]),
      "+f"(d[8]), "+f"(d[9]), "+f"(d[10]), "+f"(d[11]), "+f"(d[12]), "+f"(d[13]), "+f"(d[14]), "+f"(d[15]),
      "+f"(d[16]), "+f"(d[17]), "+f"(d[18]), "+f"(d[19]), "+f"(d[20]), "+f"(d[21]), "+f"(d[22]), "+f"(d[23]),
      "+f"(d[24]), "+f"(d[25]), "+f"(d[26]), "+f"(d[27]), "+f"(d[28]), "+f"(d[29]), "+f"(d[30]), "+f"(d[31])
    : "r"(a[0]), "r"(a[1]), "r"(a[2]), "r"(a[3]), "l"(db), "r"(scale_d));
}

template <int BN> __device__ __forceinline__ void wgmma(float (&d)[BN / 2], uint64_t a, uint64_t b, int s) {
  if constexpr (BN == 128) wgmma_n128(d, a, b, s);
  else wgmma_n256(d, a, b, s);
}

template <int N> __device__ __forceinline__ void acc_fence(float* a) {
#pragma unroll
  for (int i = 0; i < N; i++) asm volatile("" : "+f"(a[i]) :: "memory");
}

#define SELECT8(a, f) do { \
  if ((a) & 4) { if ((a) & 2) { if ((a) & 1) f(7); else f(6); } else { if ((a) & 1) f(5); else f(4); } } \
  else { if ((a) & 2) { if ((a) & 1) f(3); else f(2); } else { if ((a) & 1) f(1); else f(0); } } } while (0)
__device__ __forceinline__ uint32_t opaque(uint32_t v) { asm volatile("" : "+r"(v)); return v; }
__device__ __forceinline__ uint32_t lane_now() { uint32_t l; asm volatile("mov.u32 %0, %%laneid;" : "=r"(l)); return l; }

struct Prod {
  uint32_t sb, n, tail, addr, pat, ready;
  uint32_t rank, flip; uint16_t mask;
  __device__ __forceinline__ void load_b(uint32_t dst, uint32_t half, const CUtensorMap* m, uint32_t mstep, uint32_t fb, int k, int ch, int cstep) {
    uint32_t h = rank;
    do { tma_ld3_mc(dst + h * half, ptr_add(m, h * mstep), fb, 0, k * 64, ch + h * cstep, mask); h ^= flip; } while (h != rank);
  }
  __device__ __forceinline__ void load_wide(const Params& P, int ffn, uint32_t dst, uint32_t fb, int k, int ch) {
    load_b(dst, PAGE, &P.map[ffn ? M_W1 : M_WKV], ffn ? 128 : 0, fb, k, ffn ? ch : ch + 16, ffn ? 0 : 16);
  }
  __device__ __forceinline__ void load_narrow(const Params& P, int ffn, uint32_t dst, uint32_t fb, int k, int j) {
    load_b(dst, 8192, &P.map[ffn ? M_W1H : M_WQ], ffn ? 128 : 0, fb, k, ffn ? 48 + j : 2 * j, ffn ? 0 : 1);
  }
  __device__ __forceinline__ void finish() {
#pragma unroll 1
    for (; tail < n; tail++) mbar_wait(sb + BAR_EMPTY + ((tail & 7) << 3), (tail >> 3) & 1);
  }
  template <int PAGES> __device__ __forceinline__ uint32_t acquire(uint32_t& fb) { return acquire_n(PAGES, fb); }
  __device__ __forceinline__ uint32_t acquire_n(uint32_t PAGES, uint32_t& fb) {
    uint32_t nw = pat & 3; pat = (pat >> 2) | 0x40000000u;
#pragma unroll 1
    for (; nw; nw--) { mbar_wait(sb + BAR_EMPTY + ((tail & 7) << 3), (tail >> 3) & 1); tail++; }
    ST(4, n);
    fb = sb + BAR_FULL + ((n & 7) << 3);
    mbar_expect_tx(fb, PAGES * PAGE);
    const uint32_t a = sb + addr;
    addr += PAGES * PAGE; if (addr >= NPAGE * PAGE) addr = 0;
    n++;
    return a;
  }
  const uint32_t* flag; uint32_t base, seen;
  __device__ __forceinline__ void acquire_fence() { asm volatile("fence.acquire.gpu;" ::: "memory"); fence_async_global(); }
  __device__ __forceinline__ void next() {
    uint32_t v, spins = 0;
    seen++;
    do { asm volatile("ld.acquire.cta.shared.u32 %0, [%1];" : "=r"(v) : "r"(sb + SM_SEEN) : "memory"); spin_check(++spins >> 4); } while (v < seen);
    fence_async_global();
  }
  __device__ __forceinline__ void need(uint32_t mask) {
    if ((ready & mask) != mask) {
      uint32_t spins = 0;
      do { ready = ld_relaxed(flag) - base; spin_check(++spins); } while ((ready & mask) != mask);
      acquire_fence();
    }
    ST(5, n - 1);
  }
};

struct Cons {
  uint32_t sb, n, off, prev;
  uint32_t ebar;
  uint32_t da0, db0;
  int lane;
  template <int PAGES> __device__ __forceinline__ void advance() {
    n++; off += PAGES << 10; if (off >= (NPAGE << 10)) off = 0;
    asm volatile("" : "+r"(n), "+r"(off));
  }
  template <int BN, int PAGES> __device__ __forceinline__ void step_ab(float (&acc)[BN / 2], uint32_t da, uint32_t db, int accumulate) {
    STA();
    mbar_wait_fast(sb + BAR_FULL + ((n & 7) << 3), (n >> 3) & 1);
    STB(n);
    const uint64_t da64 = desc64(da), db64 = desc64(db);
    wgmma_fence();
#pragma unroll
    for (int k = 0; k < 4; k++) wgmma<BN>(acc, da64 + 2 * k, db64 + 128 * k, k ? 1 : accumulate);
    wgmma_commit();
    wgmma_wait<1>();
    if (prev && lane < 2) mbar_arrive_cluster(ebar + prev);
    prev = 64 + ((n & 7) << 3);
    advance<PAGES>();
  }
  template <int BN> __device__ __forceinline__ void step(float (&acc)[BN / 2], int accumulate = 1) { step_ab<BN, BN / 128 + 1>(acc, da0 + off, db0 + 1024 + off, accumulate); }
  template <int BN> __device__ __forceinline__ void step_own(float (&acc)[BN / 2], uint32_t da, int accumulate) { step_ab<BN, BN / 128>(acc, da, db0 + off, accumulate); }
  __device__ __forceinline__ void wait_full(uint32_t i) { mbar_wait_fast(sb + BAR_FULL + (((n + i) & 7) << 3), ((n + i) >> 3) & 1); }
  template <int I, int N> __device__ __forceinline__ void issue_rs(float (&acc)[64], uint32_t (&a)[16], int accumulate = 1) {
    if (I == 0) { STA(); STB(n); }
    const uint64_t db64 = desc64(db0 + off) + 1024 * I;
    wgmma_fence();
#pragma unroll
    for (int k = 0; k < 4; k++) wgmma_rs_n128(acc, a + 4 * k, db64 + 128 * k, k ? 1 : accumulate);
    if (I == N - 1) {
      wgmma_commit();
      prev = 64 + ((n & 7) << 3);
      advance<N>();
    }
  }
  template <int BN> __device__ __forceinline__ void steps(float (&acc)[BN / 2], int cnt) {
#pragma unroll 1
    do { step<BN>(acc); } while (--cnt > 0);
  }
  __device__ __forceinline__ void skip3() { off += 3 << 10; if (off >= (NPAGE << 10)) off = 0; asm volatile("" : "+r"(off)); }
  __device__ __forceinline__ void steps_skip(float (&acc)[64], int at) {
    int i = 0;
#pragma unroll 1
    do { if (i == at) off += 2 << 10; step<128>(acc); } while (++i < 2);
  }
  __device__ __forceinline__ void drain() {
    wgmma_wait<0>();
    if (lane < 2) mbar_arrive_cluster(ebar + prev);
    prev = 0;
  }
};

#define MAPPING 2
__device__ __forceinline__ uint32_t role_of_sm(uint32_t smid) {
  const uint32_t t = smid >> 1;
  uint32_t q, i;
  if (t < 32) { q = t & 7; i = t >> 3; }
  else if (t < 60) { const uint32_t u = t - 32, d = (u * 37) >> 8; q = 1 + u - d * 7; i = 4 + d; }
  else if (t < 62) return 128 + smid - 120;
  else { q = 0; i = t - 58; }
  return (q * 2 + (smid & 1)) * 8 + i;
}

template <typename T> __device__ __forceinline__ T* scratch(const Params& P, uint32_t off) { return (T*)ptr_add(P.scratch, off); }
__device__ __forceinline__ uint32_t* epoch_ptr(const Params& P) { uint32_t b; asm volatile("mov.u32 %0, %%ctaid.x;" : "=r"(b)); return scratch<uint32_t>(P, G_EPOCH + b * 4u); }

__device__ __forceinline__ int o_chunk(int s, int j) { const int hf = s >= 9, m = s - 2 - 7 * hf; return s < 2 ? 2 * j + s : 2 * (m == j ? 7 : m) + hf; }

__device__ __forceinline__ void spare_role(const Params& P, uint32_t sb, int warp, int lane, uint32_t role, uint32_t rank) {
  const int j = role & 7;
  if (warp == 8) {
    if (elect_one()) {
#pragma unroll 1
      for (int i = 0; i < 8; i++) { mbar_init(sb + BAR_FULL + 8 * i, 1); mbar_init(sb + BAR_EMPTY + 8 * i, 16); }
      mbar_init(sb + BAR_XIN, 1);
      sts128(sb + SM_ROLE, role, 0, 0, 0);
      asm volatile("fence.mbarrier_init.release.cluster;\nfence.release.sync_restrict::shared::cta.cluster;" ::: "memory");
      fence_async_smem();
    }
    __syncwarp();
  }
  asm volatile("barrier.cluster.arrive.relaxed.aligned;\nbarrier.cluster.wait.acquire.aligned;" ::: "memory");
  if (warp == 8) {
    if (elect_one()) {
          Prod p; p.sb = sb; p.n = 0; p.tail = 0; p.addr = 0; p.rank = rank; p.flip = 1; p.mask = 1 << rank;
          uint32_t fb;
          p.pat = 0x55555000u;
#pragma unroll 1
          for (int r = -1; r < 7; r++) {
            const int ch = r < 0 ? 4 * j : ((r < 2 ? r : r == 2 ? 6 : r - 1) * 4 + j) * 2;
#pragma unroll 1
            for (int k = 0; k < 16; k++) { const uint32_t a = p.acquire<2>(fb); p.load_b(a, PAGE, &P.map[r < 0 ? M_WKV : M_W1], r < 0 ? 0 : 128, fb, k, ch, r < 0 ? 2 : 0); }
          }
          p.finish();
          mbar_expect_tx(sb + BAR_XIN, 4 * PAGE);
#pragma unroll 1
          for (int h = 0; h < 8; h++) tma_ld3(sb + h * 8192, &P.map[M_W2], sb + BAR_XIN, 0, (h >> 2) * 64, 4 * j + (h & 3));
          p.pat = 0x55555550u;
          const uint32_t full = (ld_relaxed(epoch_ptr(P)) + 1) * 255;
#pragma unroll 1
          for (int u = 0; u < 32; u++) {
            const uint32_t* f = scratch<uint32_t>(P, (u & 15) * G_BLOCK + G_FLAGS + ((u >> 4) * EV_N + EV_H0) * 128);
            uint32_t spins = 0;
            while (ld_relaxed(f) != full) { __nanosleep(200); spin_check(++spins); }
            p.acquire_fence();
            p.addr = (4 + 2 * (u & 1)) * PAGE;
            const uint32_t a = p.acquire<2>(fb);
            tma_ld3(a, &P.map[M_H_LD], fb, 0, u & 15, 0); tma_ld3(a + PAGE, &P.map[M_H_LD], fb, 64, u & 15, 0);
          }
    }
  } else if (warp < 8) {
      const int wg = warp >> 2, quad = lane & 3, gr = lane >> 2;
      Cons c; c.sb = sb; c.n = 0; c.off = 0; c.prev = 0; c.lane = lane;
      c.ebar = mapa(sb + BAR_EMPTY - 64, rank);
      const uint32_t stage = sb + SM_STAGE + wg * PAGE, dstage = desc_lo(stage, 16);
      const uint32_t tag = ld_relaxed(epoch_ptr(P)) + 1;
      const int tid = threadIdx.x & 127;
#pragma unroll
      for (int i = 0; i < 4; i++) sts128(stage + (i * 128 + tid) * 16, 0x3f803f80u, 0x3f803f80u, 0x3f803f80u, 0x3f803f80u);
      fence_async_smem();
      bar_sync(2 + wg, 128);
      c.db0 = desc_lo(sb + wg * PAGE, 8192);
#pragma unroll 1
      for (int r = -1; r < 7; r++) {
        float acc[64];
#pragma unroll 1
        for (int k = 0; k < 16; k++) c.step_ab<128, 2>(acc, dstage, c.db0 + c.off, k);
        c.drain();
        acc_fence<64>(acc);
        {
          float v = 0;
#pragma unroll
          for (int i = 0; i < 32; i++) asm("{\n.reg .pred p;\nsetp.eq.u32 p, %2, %3;\nselp.f32 %0, %1, %0, p;\n}" : "+f"(v) : "f"(acc[4 * (i >> 1) + (i & 1)]), "r"(tid >> 2), "r"(i));
          st_b128(scratch<uint4>(P, G_CS + (uint32_t)((r < 0 ? j * 256 + wg * 128 : 3 * DM + wg * FF + ((r < 2 ? r : r == 2 ? 6 : r - 1) * 4 + j) * 128) + (tid >> 3) * 8 + quad * 2 + (gr & 1)) * 16u),
                  tagf(v, tag), tag & 15u, tag & 15u, tag & 15u);
        }
        __syncwarp();
      }
      c.da0 = desc_lo(sb + wg * 8192, 16); c.db0 = desc_lo(sb, 8192); c.off = 0;
      const uint32_t sa = sb + 10 * PAGE + warp * 8192;
      bar_sync(1, 256);
      mbar_wait_fast(sb + BAR_XIN, 0);
#pragma unroll 1
      for (int u = 0; u < 32; u++) {
        float acc[128];
        c.off = (4 + 2 * (u & 1)) << 10;
        c.wait_full(0);
        if (!(u & 15) && wg) bar_sync(6, 256);
        const uint64_t da = desc64(c.da0 + c.off), db = desc64(c.db0);
        wgmma_fence();
#pragma unroll
        for (int k = 0; k < 8; k++) wgmma<256>(acc, da + (k >> 2) * 1024 + (k & 3) * 2, db + (k >> 2) * 2048 + (k & 3) * 128, k);
        wgmma_commit();
        c.prev = 64 + ((c.n & 7) << 3);
        c.advance<2>();
        if (!(u & 15) && !wg) asm volatile("bar.arrive 6, 256;" ::: "memory");
        if (elect_one()) bulk_wait<0>();
        __syncwarp();
        c.drain();
        acc_fence<128>(acc);
#pragma unroll
        for (int hf = 0; hf < 2; hf++) {
#pragma unroll
          for (int i = 0; i < 8; i++) {
            const float* a = acc + 64 * hf + 8 * i;
            sts128(sa + hf * 4096 + i * 512 + lane * 16, pkt_head(pack_bf16(a[0], a[1])), pack_bf16(a[2], a[3]), pack_bf16(a[4], a[5]), pack_bf16(a[6], a[7]));
          }
          fence_async_smem();
          __syncwarp();
          if (elect_one()) {
            asm volatile("cp.async.bulk.global.shared::cta.bulk_group [%0], [%1], 4096;"
                         :: "l"(scratch<uint4>(P, (u & 15) * G_BLOCK + G_O + (2 * j + hf) * 32768u + warp * 4096u)), "r"(sa + hf * 4096) : "memory");
            bulk_commit();
          }
        }
      }
      if (elect_one()) bulk_wait<0>();
      __syncwarp();
      bar_sync(1, 256);
      if (threadIdx.x == 0) *epoch_ptr(P) = tag;
  }
}

__global__ void __cluster_dims__(2, 1, 1) __launch_bounds__(384, 1) fused_kernel(const __grid_constant__ Params P) {
  extern __shared__ __align__(1024) uint8_t smem_raw[];
  SP(0);
  const uint32_t sb = __shfl_sync(0xffffffffu, smem_u32(smem_raw), 0);
  const int warp = __shfl_sync(0xffffffffu, threadIdx.x >> 5, 0);
  const int lane = threadIdx.x & 31;
  if (warp == 7 && elect_one()) { prefetch_map(&P.map[M_XIN64]); prefetch_map(&P.map[M_WKV]); prefetch_map(&P.map[M_XIN]); }
  uint32_t role = blockIdx.x < 128 ? ((blockIdx.x >> 4) * 2 + (blockIdx.x & 1)) * 8 + ((blockIdx.x >> 1) & 7) : blockIdx.x;
  if (P.use_smid) { uint32_t smid; asm volatile("mov.u32 %0, %%smid;" : "=r"(smid)); role = role_of_sm(smid); }
  const bool spare = role >= 128;
  const int g = role >> 3, j = role & 7;
  uint32_t rank; asm("mov.u32 %0, %%cluster_ctarank;" : "=r"(rank));
  auto shared_b = [&]() {
    uint32_t peer;
    asm volatile("ld.shared::cluster.u32 %0, [%1];" : "=r"(peer) : "r"(mapa(sb + SM_ROLE, rank ^ 1)) : "memory");
    return peer < 128 && (peer & 7) == (uint32_t)j;
  };
  SP(1);

  if (__builtin_expect(spare, 0)) {
    spare_role(P, sb, warp, lane, role, rank);
  } else if (warp >= 8) {
    asm volatile("setmaxnreg.dec.sync.aligned.u32 40;");
    if (elect_one()) {
      if (warp == 8) {
#pragma unroll
        for (int i = 0; i < 6; i++) mbar_init(sb + BAR_FULL + 8 * i, 1);
        mbar_init(sb + BAR_XIN, 1);
      } else if (warp == 9) {
#pragma unroll
        for (int i = 0; i < 8; i++) mbar_init(sb + BAR_EMPTY + 8 * i, 16);
      } else if (warp == 10) {
#pragma unroll
        for (int i = 0; i < 4; i++) mbar_init(sb + BAR_SFULL + 8 * i, 4);
        mbar_init(sb + BAR_CLR, 1); mbar_init(sb + BAR_CLR2, 1); mbar_init(sb + BAR_FULL + 48, 1); mbar_init(sb + BAR_FULL + 56, 1);
      } else {
        sts128(sb + SM_ROLE, role, 0, 0, 0);
        mbar_init(sb + BAR_TAG, 1); mbar_init(sb + BAR_XFULL, 8); mbar_init(sb + BAR_CSE, 8);
        mbar_init(sb + BAR_SEMPTY, 1); mbar_init(sb + BAR_CSF, 1); mbar_init(sb + BAR_CSF + 8, 2);
      }
      asm volatile("fence.mbarrier_init.release.cluster;\nfence.release.sync_restrict::shared::cta.cluster;" ::: "memory");
      fence_async_smem();
    }
    __syncwarp();
    SP(2);
    asm volatile("barrier.cluster.arrive.relaxed.aligned;" ::: "memory");
    if (warp == 8) {
      if (elect_one()) {
        const int par = g & 1, row = (g >> 1) * 128;
        mbar_arrive(sb + BAR_FULL);
        {
          const int s = 1;
          const uint32_t xb = sb + BAR_XIN, fb = sb + BAR_FULL + 8;
          mbar_expect_tx(xb, PAGE); mbar_expect_tx(fb, 2 * PAGE);
#pragma unroll
          for (int h = 0; h < 2; h++) tma_ld3(sb + SM_STAGE + h * PAGE + s * 8192, &P.map[M_XIN64], xb, s * 64, par, row + h * 64);
#pragma unroll
          for (int h = 0; h < 2; h++) tma_ld3(sb + (2 * s + h) * PAGE, &P.map[M_WKV], fb, 0, s * 64, 16 + 16 * h + 2 * j);
        }
#pragma unroll 1
        for (int s = 0; s < 2; s++) {
          const uint32_t fb = sb + BAR_FULL + 16 + 8 * s;
          mbar_expect_tx(fb, PAGE);
          tma_ld3(sb + (4 + s) * PAGE, &P.map[M_WKV], fb, 0, s * 64, 2 * j);
        }
#pragma unroll 1
        for (int s = 0; s < 2; s++) {
          const uint32_t fb = sb + BAR_FULL + 32 + 8 * s, a = sb + (6 + 3 * s) * PAGE;
          const int k = (j == 1 ? 4 : 2) + s;
          mbar_expect_tx(fb, 3 * PAGE);
          tma_ld3(a, &P.map[M_XIN], fb, k * 64, par, row);
#pragma unroll
          for (int h = 0; h < 2; h++) tma_ld3(a + PAGE + h * PAGE, &P.map[M_WKV], fb, 0, k * 64, 16 + 16 * h + 2 * j);
        }
        spin_check((sb & 1023) << 22);
      }
      __syncwarp();
    }
    SP(3);
    asm volatile("barrier.cluster.wait.acquire.aligned;" ::: "memory");
    SP(4);
    if (warp == 8) {
      if (elect_one()) {
        Prod p; p.sb = sb; p.n = 0; p.tail = 0; p.ready = 0; p.addr = 0;
        { const bool mc = shared_b(); p.rank = rank; p.flip = !mc; p.mask = mc ? 3 : 1 << rank; }
        uint32_t fb;
        {
          p.seen = 0;
          const int xpar = g & 1, xrow = (g >> 1) * 128;
          SP(5);
#pragma unroll 1
          for (int hl = 0; hl < 4; hl++) {
            const int ffn = hl & 1;
            const CUtensorMap* xmap = &P.map[hl ? M_OUT_LD : M_XIN];
            if (hl) {
              p.pat = ffn ? Pat<3>::v : Pat<8>::v;
#pragma unroll 1
              for (int s = 0; s < 2; s++) { const uint32_t a = p.acquire<2>(fb); p.load_wide(P, ffn, a, fb, 2 * j + s, 2 * j); }
#pragma unroll 1
              for (int s = 0; s < 2; s++) { const uint32_t a = p.acquire<1>(fb); p.load_narrow(P, ffn, a, fb, 2 * j + s, j); }
            } else { p.pat = (Pat<0>::v >> 12) | 0x55500000u; p.addr = 0; p.n = 6; }
            if (hl == 0) SP(6);
            uint32_t fb0 = 0;
#pragma unroll 1
            for (int m = hl ? 0 : 2; m < 14; m++) {
              const int hf = m >= 7, mm = m - 7 * hf, jj = mm == j ? 7 : mm;
              int k = 2 * jj + hf;
              if (hl == 0) {
                const int pr = (m >> 1) + 1;
                k = 2 * (j && pr == 2 ? j : pr == j ? 2 : pr) + (m & 1);
              }
              const uint32_t a = p.acquire<3>(fb);
              p.load_wide(P, ffn, a + PAGE, fb, k, 2 * j);
              if (hl) {
                if (m == 0) { fb0 = fb; continue; }
                if (m == 1) {
                  const int j0 = j ? 0 : 7;
                  p.flag = scratch<uint32_t>(P, g * G_BLOCK + G_FLAGS + (ffn ? (hl >> 1) * EV_N + EV_XA : EV_XB) * 128);
                  p.ready = 0; p.need(1u << j0);
                  tma_ld3(a - 3 * PAGE, xmap, fb0, j0 * 128, xpar, xrow);
                }
                if (m < 7) p.need(1u << jj); else if (m == 7) p.next();
              }
              tma_ld3(a, xmap, fb, k * 64, xpar, xrow);
            }
            if (hl == 0) { mbar_wait(sb + BAR_TAG, 0); asm volatile("ld.shared.u32 %0, [%1];" : "=r"(p.base) : "r"(sb + SM_TAG) : "memory"); p.base = (p.base - 1) * 255; }
            p.pat = ffn ? Pat<4>::v : Pat<1>::v;
#pragma unroll 1
            for (int m = 0; m < 14; m++) {
              const int k = (m >> 1) == (hl ? j : 0) ? 14 + (m & 1) : m;
              if (ffn && m == 8) p.addr += 2 * PAGE;
              const uint32_t a = p.acquire<2>(fb);
              p.load_narrow(P, ffn, a + PAGE, fb, k, j);
              tma_ld3(a, xmap, fb, k * 64, xpar, xrow);
            }
            if (!ffn) {
              p.pat = Pat<2>::v;
              uint32_t a = 0;
#pragma unroll 1
              for (int s = 0; s < 16; s++) {
                if ((0x4925 >> s) & 1) a = p.acquire_n(s == 0 || s == 14 ? 2 : 3, fb); else a += PAGE;
                p.load_b(a, 8192, &P.map[M_WO], 0, fb, o_chunk(s, j), 2 * j, 1);
              }
              p.addr += 2 * PAGE;
              a = p.acquire<2>(fb);
              tma_ld3(a, xmap, fb, j * 128, xpar, xrow); tma_ld3(a + PAGE, xmap, fb, j * 128 + 64, xpar, xrow);
            } else {
              p.pat = Pat<5>::v;
#pragma unroll 1
              for (int s = 16; s < 48; s++) {
                const int pi = (s >> 1) & 7;
                if (s == 32) p.pat = Pat<6>::v;
                if ((s & 15) == WSKIP) { p.addr += 3 * PAGE; if (p.addr >= NPAGE * PAGE) p.addr = 0; }
                const int k = (s < 32 ? pi : pi == 4 ? j : pi == j ? 4 : pi) * 2 + (s & 1);
                const uint32_t a = p.acquire<3>(fb);
                p.load_wide(P, 1, a + PAGE, fb, k, (s & 48) + 2 * j);
                tma_ld3(a, xmap, fb, k * 64, xpar, xrow);
              }
              p.pat = Pat<7>::v;
#pragma unroll 1
              for (int q = 0; q < 4; q++) {
                p.next();
                const int k0 = q == 0 ? 2 : q == 1 ? 48 : q * 16 - 16, k1 = q == 1 ? 56 : (k0 & 48) + 16;
#pragma unroll 1
                for (int k = k0; k < k1; k++) {
                  const uint32_t a = p.acquire<2>(fb);
                  p.load_b(a + PAGE, 8192, &P.map[M_W2], 0, fb, k, 2 * j, 1);
                  tma_ld3(a, &P.map[M_H_LD], fb, k * 64, g, 0);
                }
              }
            }
            TL(2, 1 + hl);
          }
        }
        p.finish();
      }
    } else {
      mbar_wait(sb + BAR_XIN, 0);
      if (elect_one()) {
#pragma unroll 1
        for (int i = warp - 9; i < 8; i += 3) prefetch_l2(ptr_add(P.wqkv, (i * 128 + role) * 6144u + 2048u), 4096);
      }
      uint32_t tag;
      {
        const uint32_t part = warp - 9, col = DM + role * 16 + (lane & 1) * 8;
        const int cnt = part ? 21 : 22;
        const uint4* wp = ptr_add((const uint4*)P.wqkv, ((part ? 16 + part * 336 : 0) + (lane >> 1)) * 6144u + col * 2);
        float s[8] = {0, 0, 0, 0, 0, 0, 0, 0};
        uint4 v[4];
#pragma unroll
        for (int i = 0; i < 4; i++) v[i] = ld_relaxed4(wp + i * (16 * 6144 / 16));
        tag = ld_relaxed(epoch_ptr(P)) + 1;
        if (warp == 10 && lane == 0) { asm volatile("st.shared.u32 [%0], %1;" :: "r"(sb + SM_TAG), "r"(tag) : "memory"); mbar_arrive(sb + BAR_TAG); }
#pragma unroll 1
        for (int b = 4; b < 28; b += 4) {
          wp += 64 * 6144 / 16;
#pragma unroll
          for (int i = 0; i < 4; i++) {
            s[0] += bf_lo(v[i].x); s[1] += bf_hi(v[i].x); s[2] += bf_lo(v[i].y); s[3] += bf_hi(v[i].y);
            s[4] += bf_lo(v[i].z); s[5] += bf_hi(v[i].z); s[6] += bf_lo(v[i].w); s[7] += bf_hi(v[i].w);
            v[i] = make_uint4(0, 0, 0, 0);
            if (b + i < cnt) v[i] = __ldcg(wp + i * (16 * 6144 / 16));
          }
        }
#pragma unroll
        for (int e = 0; e < 4; e++) { const bool h = lane & 16; const float t = __shfl_xor_sync(0xffffffffu, h ? s[e] : s[e + 4], 16); s[e] = (h ? s[e + 4] : s[e]) + t; }
#pragma unroll
        for (int e = 0; e < 2; e++) { const bool h = lane & 8; const float t = __shfl_xor_sync(0xffffffffu, h ? s[e] : s[e + 2], 8); s[e] = (h ? s[e + 2] : s[e]) + t; }
        { const bool h = lane & 4; const float t = __shfl_xor_sync(0xffffffffu, h ? s[0] : s[1], 4); s[0] = (h ? s[1] : s[0]) + t; }
        s[0] += __shfl_xor_sync(0xffffffffu, s[0], 2);
        if (!(lane & 2) || part == 0) st_relaxed(scratch<uint32_t>(P, G_CS + (col + (lane >> 2)) * 16 + ((lane & 2) ? 3 : part) * 4), tagf((lane & 2) ? 0.f : s[0], tag));
        __syncwarp();
      }
      if (warp == 11 && lane == 0) TL(2, 30);
      {
        const uint32_t cspos = sb + SM_CS + ((lane & 16) + ((lane >> 1) & 3) * 4 + ((lane >> 3) & 1) * 2 + (lane & 1)) * 4;
#pragma unroll 1
        for (int it = 0; it < (warp == 10 ? 8 : 1); it++) {
          const int t = it & 3;
          if (it) mbar_wait(sb + BAR_CSE, (it - 1) & 1);
          if (t == 1) mbar_wait(sb + BAR_SEMPTY, 0);
#pragma unroll 1
          for (int b = it ? 0 : warp - 9; b < (it == 0 ? warp - 8 : t < 2 ? 3 : 2); b++) {
            uint32_t c0, c1;
            if (b < 2) { c0 = (t ? 2048 + t * 1024 + b * FF : 1024 + b * 1024) + j * 128; c1 = c0 + 64; }
            else if (t) { c0 = 6144 + j * 64; c1 = c0 + FF; }
            else { c0 = j * 128; c1 = c0 + 64; }
            const uint4* p0 = scratch<uint4>(P, G_CS + (c0 + lane) * 16u);
            const uint4* p1 = scratch<uint4>(P, G_CS + (c1 + lane) * 16u);
            uint4 v[4]; uint32_t spins = 0; bool ok;
            do {
              if (spins) __nanosleep(200);
              v[0] = ld_relaxed4(p0); v[1] = ld_relaxed4(p0 + 32); v[2] = ld_relaxed4(p1); v[3] = ld_relaxed4(p1 + 32);
              ok = tag_ok4(v[0], tag) && tag_ok4(v[1], tag) && tag_ok4(v[2], tag) && tag_ok4(v[3], tag);
              spin_check(++spins);
            } while (__any_sync(0xffffffffu, !ok));
#pragma unroll
            for (int m = 0; m < 4; m++) sts32f(cspos + b * 512 + m * 128, (untag(v[m].x) + untag(v[m].y)) + (untag(v[m].z) + untag(v[m].w)));
            __syncwarp();
            if (lane == 0) mbar_arrive(sb + BAR_CSF + (b ? 8 : 0));
          }
          if (lane == 0) { if (t >= 2) mbar_arrive(sb + BAR_CSF + 8); TL(2, 16 + it + (warp == 11 ? 8 : warp == 9 ? 9 : 0)); }
          if (t == 3) {
            if (g >= 2) {
              uint4* op = scratch<uint4>(P, G_HALO + (((it >> 2) * 16 + g - 2) * 8 + j) * 4096u + lane * 16u);
#pragma unroll 1
              for (int i = 0; i < 8; i++) { st_b128(op, 0, 0, 0, 0); op += 32; }
            }
          }
        }
      }
      if (warp == 11) {
        if (elect_one()) prefetch_l2(ptr_add(P.wo, role * 16384u), 16384);
        uint32_t* const fl = scratch<uint32_t>(P, g * G_BLOCK + G_FLAGS);
        uint32_t seen = 0;
#pragma unroll 1
        for (int e = EV_XA; e < EV_N + EV_XB; e++) {
          if (e == EV_XB) continue;
          const bool clr = (e & 7) == EV_XA;
          uint32_t* const f = ptr_add(fl, (clr ? 16 + e : e) * 128u);
          if (clr || (e & 7) == EV_H0) {
            uint4* op = scratch<uint4>(P, g * G_BLOCK + G_O + j * 32768u + lane * 16u);
#pragma unroll 1
            for (int i = 0; i < 64; i++) { st_b128(op, 0, 0, 0, 0); op += 32; if (e || (i & 1)) __nanosleep(10); }
            __syncwarp();
            if (lane == 0) { if (clr) red_release(f, 1u << j); else mbar_arrive(sb + BAR_CLR2); }
          }
          uint32_t spins = 0, m;
          while ((m = ld_relaxed(f) - (tag - 1) * 255) != 255) { __nanosleep(m ? 50 : 500); spin_check(++spins); }
          asm volatile("fence.acquire.gpu;" ::: "memory");
          if (lane == 0) {
            if (clr) mbar_arrive(sb + BAR_CLR);
            else asm volatile("st.release.cta.shared.u32 [%0], %1;" :: "r"(sb + SM_SEEN), "r"(++seen) : "memory");
          }
          if (e == EV_H3) {
#pragma unroll 1
            for (int i = 0; i < 7; i++) { if (elect_one()) prefetch_l2(ptr_add(P.w2, (i * 128 + role) * 8192u), 8192); __nanosleep(500); }
          }
          __syncwarp();
        }
      } else if (warp == 9) {
        if (elect_one()) {
          prefetch_map(&P.map[M_WQ]); prefetch_map(&P.map[M_OUT_LD]); prefetch_map(&P.map[M_WO]); prefetch_map(&P.map[M_W1 + rank]);
          prefetch_map(&P.map[M_H_ST]); prefetch_map(&P.map[M_H_LD]); prefetch_map(&P.map[M_W1H + rank]); prefetch_map(&P.map[M_W2]); prefetch_map(&P.map[M_OUT_ST]);
          uint32_t* fl = scratch<uint32_t>(P, g * G_BLOCK + G_FLAGS);
          int pe = 0;
#pragma unroll 1
          for (int e = 0; e < 2 * EV_N; e++) {
            const int q = e & 7;
            const bool is_h = q >= EV_H0 && q < EV_XB, last = e >= EV_N + EV_XB;
            const CUtensorMap* map = &P.map[is_h ? M_H_ST : M_OUT_ST];
            const int col = q == EV_H3 ? 3072 - 64 + j * 64 : (q == EV_H1 ? 1024 : q == EV_H2 ? 2048 : 0) + j * 128;
            const int row = is_h ? 0 : (g >> 1) * 128, par = is_h ? g : g & 1;
#pragma unroll 1
            for (int hb = is_h ? q == EV_H3 : q & 1; hb <= (is_h ? 1 : q & 1); hb++) {
#pragma unroll
              for (int w = 0; w < 2; w++) {
                const bool sw = last;
                const int wg = sw ? hb : w, h = sw ? w : hb, p = sw ? pe - hb + w : pe;
                mbar_wait(sb + BAR_SFULL + 16 * wg + 8 * (p & 1), (p >> 1) & 1);
                if (w == 0) TL(3, 20 + e);
                const uint32_t src = sb + (last ? 0 : SM_STAGE) + wg * PAGE + h * 8192;
                if (is_h) {
#pragma unroll 1
                  for (int r = 0; r < 64; r += H_ROWS) { tma_st3(map, src + r * 128, col + h * 64, par, wg * 64 + r); __nanosleep(60); }
                } else tma_st3(map, src, col + h * 64, par, row + wg * 64);
              }
              pe++;
            }
            bulk_commit();
            if (e != EV_N + EV_XB) bulk_wait<0>();
            TL(3, 40 + e);
            if (is_h || (q & 1)) mbar_arrive(sb + BAR_SEMPTY);
            if (q == EV_H0) mbar_wait(sb + BAR_CLR2, e >> 3);
            if (!last) red_release(fl, 1u << j);
            TL(3, e);
            fl += 32;
          }
          *epoch_ptr(P) = tag;
        }
      }
    }
  } else {
    {
      const uint32_t r = threadIdx.x >> 3, so = r * 128 + (((threadIdx.x ^ r) & 7) << 4);
      const uint8_t* xp = ptr_add((const uint8_t*)P.x, (2 * ((g >> 1) * 128 + r) + (g & 1)) * 2048u + (threadIdx.x & 7) * 16u);
      const uint8_t* wp = ptr_add((const uint8_t*)P.wqkv, r * 6144u + 2048u + j * 256u + (threadIdx.x & 7) * 16u);
#pragma unroll
      for (int i = 0; i < 4; i++) asm volatile("cp.async.cg.shared.global [%0], [%1], 16;" :: "r"(sb + SM_STAGE + (i >> 1) * PAGE + (i & 1) * 4096 + so), "l"(xp + i * 32 * 4096) : "memory");
#pragma unroll
      for (int q = 0; q < 8; q++) {
        const int i = (q & 3) * 2 + (q >> 2);
        asm volatile("cp.async.cg.shared.global [%0], [%1], 16;" :: "r"(sb + i * 4096 + so), "l"(wp + (i & 1) * 32 * 6144 + ((i >> 1) & 1) * 128 + (i >> 2) * 2048) : "memory");
      }
    }
    {
      if (warp == 0) asm volatile("prefetch.global.L2 [%0];" :: "l"(ptr_add(P.x, (2 * ((g >> 1) * 128 + j * 16 + (lane >> 1)) + (g & 1)) * 2048u + (lane & 1) * 128u)));
      else if (warp < 3 && (warp == 1 || lane < 16)) asm volatile("prefetch.global.L2 [%0];" :: "l"(ptr_add(P.wqkv, role * 6144u + (warp - 1) * 4096u + lane * 128u)));
      __syncwarp();
    }
    asm volatile("barrier.cluster.arrive.relaxed.aligned;" ::: "memory");
    asm volatile("setmaxnreg.inc.sync.aligned.u32 232;");
    SP(4);
    asm volatile("barrier.cluster.wait.acquire.aligned;" ::: "memory");
    SP(5);
    const int wg = warp >> 2;
    const int quad = lane & 3, gr = lane >> 2;
    Cons c; c.sb = sb; c.n = 0; c.off = 0; c.prev = 0; c.lane = lane;
    c.ebar = mapa(sb + BAR_EMPTY - 64, shared_b() ? lane & 1 : rank);
    const uint32_t stage = sb + SM_STAGE + wg * PAGE;
    const uint32_t dstage = desc_lo(stage, 16);
    {
    c.da0 = desc_lo(sb + wg * 8192, 16); c.db0 = desc_lo(sb, 8192);
    uint32_t sphase = 1, sfull = sb + BAR_SFULL + 16 * wg;
    const uint32_t maddr = stage + ((warp & 3) * 16 + (lane & 15)) * 128 + (((lane >> 4) ^ (lane & 7)) << 4);
    const uint32_t csaddr = sb + SM_CS + quad * 16;
    float st[8] = {0, 0, 0, 0, 0, 0, 0, 0};
    float* const mean = st; float* const rstd = st + 2;
    SP(6);

    auto stage_wait = [&]() { mbar_wait_fast(sb + BAR_SEMPTY, sphase); sphase ^= 1; };
    auto stage_publish = [&]() { fence_async_smem(); __syncwarp(); if (lane == 0) mbar_arrive(sfull); sfull ^= 8; };
    auto cs_load = [&](uint32_t (&cs)[16], int grp) {
#pragma unroll
      for (int i = 0; i < 4; i++) lds128(csaddr + grp * 256 + i * 64, cs[4 * i], cs[4 * i + 1], cs[4 * i + 2], cs[4 * i + 3]);
    };
    auto cs_apply = [&](float* acc, uint32_t (&cs)[16]) {
      acc_fence<32>(acc);
#pragma unroll
      for (int b = 0; b < 8; b++) {
        acc[4 * b] -= mean[0] * __uint_as_float(cs[2 * b]); acc[4 * b + 1] -= mean[0] * __uint_as_float(cs[2 * b + 1]);
        acc[4 * b + 2] -= mean[1] * __uint_as_float(cs[2 * b]); acc[4 * b + 3] -= mean[1] * __uint_as_float(cs[2 * b + 1]);
      }
      acc_fence<32>(acc);
    };
    auto glu_pair = [&](float g0, float g1, float u0, float u1, int r) {
      const float nl = -LOG2E * rstd[r], r2 = rstd[r] * rstd[r];
      return pack_bf16(g0 * u0 * r2 * rcp(1.0f + ex2(g0 * nl)), g1 * u1 * r2 * rcp(1.0f + ex2(g1 * nl)));
    };
    auto glu_slice = [&](uint32_t (&pk)[64], int i) {
      uint32_t hp[4];
#pragma unroll
      for (int e = 0; e < 4; e++) {
        asm volatile("" : "+r"(pk[4 * i + e]), "+r"(pk[32 + 4 * i + e]));
        const uint32_t pg = pk[4 * i + e], pu = pk[32 + 4 * i + e];
        hp[e] = glu_pair(bf_lo(pg), bf_hi(pg), bf_lo(pu), bf_hi(pu), e & 1);
      }
      stsm4((maddr ^ ((i & 3) << 5)) + (i >> 2) * 8192, hp[0], hp[1], hp[2], hp[3]);
    };
    auto glu_slice_acc = [&](float (&acc)[128], int i) {
      uint32_t hp[4];
      acc_fence<8>(acc + 8 * i);
#pragma unroll
      for (int e = 0; e < 4; e++) hp[e] = glu_pair(acc[8 * i + 2 * e], acc[8 * i + 2 * e + 1], acc[64 + 8 * i + 2 * e], acc[64 + 8 * i + 2 * e + 1], e & 1);
      stsm4((maddr ^ ((i & 3) << 5)) + (i >> 2) * 8192, hp[0], hp[1], hp[2], hp[3]);
    };
    auto stage_x = [&](uint32_t (&x)[32], int hf, uint32_t maddr) {
#pragma unroll
      for (int i = 4 * hf; i < 4 * hf + 4; i++) stsm4((maddr ^ ((i & 3) << 5)) + hf * 8192, x[4 * i], x[4 * i + 1], x[4 * i + 2], x[4 * i + 3]);
    };

    float acc[128];
    asm volatile("cp.async.wait_all;" ::: "memory");
    fence_async_smem();
    bar_sync(1, 256);
    SP(7);
    c.step_own<256>(acc, dstage, 0);
    mbar_wait_fast(sb + BAR_XIN, 0);
    SP(8);
#pragma unroll 1
    for (int hl = 0;; hl++) {
      int t = hl & 1;
      float acc2[64];
      uint32_t res[32];
      c.step_own<256>(acc, dstage + 512, 1);
#pragma unroll
      for (int s = 0; s < 2; s++) c.step_own<128>(acc2, dstage + s * 512, s);
#pragma unroll 1
      for (int s = 2; s < 11; s++) {
        const uint32_t apage = (c.off << 4) - (SM_STAGE + wg * 8192);
        if (s == 3 && wg) bar_sync(6, 256);
        c.step<256>(acc);
        if (s == 3 && !wg) asm volatile("bar.arrive 6, 256;" ::: "memory");
        int act = s;
        asm volatile("" : "+r"(act));
        auto get_tag = [&]() { uint32_t tag; asm volatile("ld.shared.u32 %0, [%1];" : "=r"(tag) : "r"(sb + SM_TAG) : "memory"); return tag; };
        const uint32_t stat_off = g * G_BLOCK + G_STATS + (hl * 128 + warp * 16) * 64u;
        auto stat_get = [&]() {
          const uint2* sp = scratch<uint2>(P, opaque(stat_off) + lane_now() * 16);
          const uint4 a = ld_relaxed4(sp), b = ld_relaxed4(sp + 64);
          st[0] = __uint_as_float(a.x); st[1] = __uint_as_float(a.y); st[2] = __uint_as_float(a.z); st[3] = __uint_as_float(a.w);
          st[4] = __uint_as_float(b.x); st[5] = __uint_as_float(b.y); st[6] = __uint_as_float(b.z); st[7] = __uint_as_float(b.w);
        };
        switch (act) {
          case 4: case 5: {
            const uint32_t ra = maddr + ((hl || j == 0) ? (s & 1) * 8192 : apage);
#pragma unroll
            for (int i = 0; i < 4; i++) {
              uint32_t v[4];
              ldsm4(ra ^ (i << 5), v[0], v[1], v[2], v[3]);
              if (i == 0 && s == 4) { st[0] = bf_lo(v[0]); st[1] = bf_lo(v[1]); st[2] = st[3] = st[4] = st[5] = 0; }
#pragma unroll
              for (int e = 0; e < 4; e++) {
                const float a = bf_lo(v[e]) - st[e & 1], b = bf_hi(v[e]) - st[e & 1];
                st[2 + (e & 1)] += a + b; st[4 + (e & 1)] += a * a; st[4 + (e & 1)] += b * b;
              }
            }
          } break;
          case 6: {
            mbar_wait_fast(sb + BAR_TAG, 0);
            const uint32_t tag = get_tag();
            float m[2], q[2];
#pragma unroll
            for (int r = 0; r < 2; r++) {
              const float mt = st[r] + st[2 + r] * (1.0f / 32);
              m[r] = mt + __shfl_xor_sync(0xffffffffu, mt, 1); m[r] += __shfl_xor_sync(0xffffffffu, m[r], 2); m[r] *= 0.25f;
              q[r] = st[4 + r] - st[2 + r] * st[2 + r] * (1.0f / 32) + 32.0f * (mt - m[r]) * (mt - m[r]);
            }
#pragma unroll
            for (int o = 1; o < 4; o <<= 1) { q[0] += __shfl_xor_sync(0xffffffffu, q[0], o); q[1] += __shfl_xor_sync(0xffffffffu, q[1], o); }
            const uint32_t l = lane_now();
            uint2* sp = scratch<uint2>(P, opaque(stat_off + j * 8) + (l >> 2) * 64 + (l & 1) * 512);
            if (!(l & 2)) st_relaxed2(sp, tagf(l & 1 ? m[1] : m[0], tag), tagf(l & 1 ? q[1] : q[0], tag));
          } break;
          case 8: stat_get(); break;
          case 10: {
            const uint32_t tag = get_tag();
            uint32_t spins = 0;
            for (;;) {
              uint32_t bad = 0;
#pragma unroll
              for (int i = 0; i < 8; i++) bad |= __float_as_uint(st[i]) ^ tag;
              if (!__any_sync(0xffffffffu, bad & 15u)) break;
              stat_get(); spin_check(++spins);
            }
            float mr[4];
#pragma unroll
            for (int r = 0; r < 2; r++) {
              const float m0 = untag(__float_as_uint(st[4 * r])), m1 = untag(__float_as_uint(st[4 * r + 2]));
              float m = m0 + m1; m += __shfl_xor_sync(0xffffffffu, m, 1); m += __shfl_xor_sync(0xffffffffu, m, 2); m *= 0.125f;
              float q = untag(__float_as_uint(st[4 * r + 1])) + untag(__float_as_uint(st[4 * r + 3])) + 128.0f * ((m0 - m) * (m0 - m) + (m1 - m) * (m1 - m));
              q += __shfl_xor_sync(0xffffffffu, q, 1); q += __shfl_xor_sync(0xffffffffu, q, 2);
              mr[r] = m; mr[2 + r] = rsqrtf(fmaxf(q, 0.f) * (1.0f / DM) + LN_EPS);
            }
            st[0] = mr[0]; st[1] = mr[1]; st[2] = mr[2]; st[3] = mr[3];
          } break;
          default: break;
        }
      }
#pragma unroll 1
      for (;;) {
      const int it = (hl >> 1) * 4 + t;
#pragma unroll
      for (int s = 0; s < 4; s++) {
        uint32_t cs[16];
        if (WSKIP == 11 + s && t >= 2) c.skip3();
        c.step<256>(acc);
        if (!(s & 1)) mbar_wait_fast(sb + BAR_CSF + 4 * s, t & 1);
        if (s >= 2 && t <= 1) { cs_load(cs, 2 + s); cs_apply(acc2 + 32 * (s - 2), cs); }
        cs_load(cs, s);
        c.drain();
        cs_apply(acc + 32 * s, cs);
      }
      if (WSKIP == 15 && t >= 2) c.skip3();
      c.step<256>(acc);
      if (lane == 0) mbar_arrive(sb + BAR_CSE);
      c.drain();
      acc_fence<128>(acc);
      TLC(1 + it * 6);
      uint32_t pkB[64];
      if (t == 2) {
#pragma unroll
        for (int i = 0; i < 64; i++) pkB[i] = pack_bf16(acc[2 * i], acc[2 * i + 1]);
      } else if (t == 0) {
        uint32_t pkA[64];
        auto kv_pack = [&](int v, int r) {
#pragma unroll
          for (int i = 32 * v + r; i < 32 * v + 32; i += 2) { acc_fence<2>(acc + 2 * i); pkA[i] = pack_bf16(acc[2 * i] * rstd[r], acc[2 * i + 1] * rstd[r]); }
        };
        const uint32_t l16 = lane_now() * 16u;
        uint4* const xs = ptr_add((uint4*)smem_raw, SM_STAGE + l16);
        uint4* const hp = scratch<uint4>(P, G_HALO + (((hl >> 1) * 16 + g) * 8 + j) * 4096u + l16);
        {
          uint4* const dst = (warp == 7 && g < 14) ? hp : ptr_add(xs, warp * 4096u);
#pragma unroll
          for (int s = 0; s < 2; s++) {
            c.steps<128>(acc2, s ? 2 : 1 + wg);
            if (s == 0) stage_wait();
            kv_pack(s, 1);
#pragma unroll
            for (int i = 4 * s; i < 4 * s + 4; i++) { pkA[8 * i + 1] = pkt_head(pkA[8 * i + 1]); gen_store(dst + i * 32, pkA[8 * i + 1], pkA[8 * i + 3], pkA[8 * i + 5], pkA[8 * i + 7]); }
          }
        }
        __syncwarp();
        if (lane == 0) mbar_arrive(sb + BAR_XFULL);
#pragma unroll
        for (int s = 0; s < 2; s++) {
          c.steps<128>(acc2, 2);
#pragma unroll
          for (int i = 33 - s; i < 64; i += 2) pkA[i] = movm(pkA[i]);
          kv_pack(1 - s, 0);
        }
        uint32_t kvH[32];
        {
          const uint4* const src = (warp == 0 && g >= 2) ? hp - 2 * 8 * 256 : ptr_add(xs, (warp ? warp - 1 : 0) * 4096u);
          c.steps<128>(acc2, 2);
          mbar_wait_fast(sb + BAR_XFULL, hl >> 1);
#pragma unroll
          for (int i = 0; i < 8; i++) gen_load(src + i * 32, kvH + 4 * i);
          c.steps<128>(acc2, 3 - wg);
          uint32_t spins = 0;
          while (__any_sync(0xffffffffu, !(kvH[0] && kvH[4] && kvH[8] && kvH[12] && kvH[16] && kvH[20] && kvH[24] && kvH[28]))) {
#pragma unroll
            for (int i = 0; i < 8; i++) gen_load(src + i * 32, kvH + 4 * i);
            spin_check(++spins);
          }
        }
#pragma unroll
        for (int i = 16; i < 32; i++) kvH[i] = movm(kvH[i]);
        mbar_wait_fast(sb + BAR_CLR, hl >> 1);
        c.steps<128>(acc2, 2);
        AP(0);
        c.wait_full(0);
        AP(1);
        c.drain();
        AP(2);
        acc_fence<64>(acc2);
        TLC(2 + it * 6);
        uint32_t q[32];
#pragma unroll
        for (int i = 0; i < 32; i++) q[i] = pack_bf16(acc2[2 * i], acc2[2 * i + 1]);
        const uint32_t zm = bar_sync_zero(1, 256);
        AP(3);
        uint32_t ob[6][16];
        uint4* const omail = scratch<uint4>(P, g * G_BLOCK + G_O + warp * 2048u + l16);
        float o2[8][4], r2[4];
        {
          const float hv = (warp == 0 && g < 2) ? -INFINITY : 0.f;
          const float hinit[4] = {hv, hv, hv, hv};
          const bool c0 = (2 * quad <= gr), c1 = (2 * quad + 1 <= gr);
          const uint32_t lm = (c0 ? 0xffffu : 0u) | (c1 ? 0xffff0000u : 0u);
          const float sc[2] = {rstd[0] * (0.17677669529663687f * LOG2E), rstd[1] * (0.17677669529663687f * LOG2E)};
          float lg[4][4], mx[4][2];
#pragma unroll
          for (int h = 0; h < 4; h++) {
            const int b = h * 4;
            float sH[4], sL[4], sU[4];
            q[2 * b] |= zm;
            mma16816(sH, q[2 * b], q[2 * b + 1], q[2 * b + 2], q[2 * b + 3], kvH[b], kvH[b + 1], hinit);
            mma16816z(sL, q[2 * b], q[2 * b + 1], q[2 * b + 2], q[2 * b + 3], pkA[2 * b], pkA[2 * b + 2]);
            mma16816z(sU, q[2 * b], q[2 * b + 1], q[2 * b + 2], q[2 * b + 3], pkA[2 * b + 1], pkA[2 * b + 3]);
            mma16816(sH, q[2 * b + 4], q[2 * b + 5], q[2 * b + 6], q[2 * b + 7], kvH[b + 2], kvH[b + 3], sH);
            mma16816(sL, q[2 * b + 4], q[2 * b + 5], q[2 * b + 6], q[2 * b + 7], pkA[2 * b + 4], pkA[2 * b + 6], sL);
            mma16816(sU, q[2 * b + 4], q[2 * b + 5], q[2 * b + 6], q[2 * b + 7], pkA[2 * b + 5], pkA[2 * b + 7], sU);
            lg[h][0] = c0 ? sL[0] : sH[0]; lg[h][1] = c1 ? sL[1] : sH[1]; lg[h][2] = c0 ? sU[2] : sL[2]; lg[h][3] = c1 ? sU[3] : sL[3];
            mx[h][0] = fmaxf(lg[h][0], lg[h][1]); mx[h][1] = fmaxf(lg[h][2], lg[h][3]);
          }
#pragma unroll
          for (int o = 1; o < 4; o <<= 1) {
#pragma unroll
            for (int i = 0; i < 8; i++) mx[i >> 1][i & 1] = fmaxf(mx[i >> 1][i & 1], __shfl_xor_sync(0xffffffffu, mx[i >> 1][i & 1], o));
          }
          AP(4);
          uint32_t z = zm, pp[4][2];
          float rs[4][2];
          auto probs = [&](int h) {
            pp[h][0] = pack_bf16(ex2((lg[h][0] - mx[h][0]) * sc[0]), ex2((lg[h][1] - mx[h][0]) * sc[0]));
            pp[h][1] = pack_bf16(ex2((lg[h][2] - mx[h][1]) * sc[1]), ex2((lg[h][3] - mx[h][1]) * sc[1]));
            float sum[4];
            mma1688z(sum, pp[h][0], pp[h][1], 0x3f803f80u);
            rs[h][0] = rcp(sum[0]); rs[h][1] = rcp(sum[2]);
            asm volatile("" : "+f"(rs[h][0]), "+f"(rs[h][1]));
          };
          probs(0); probs(1); probs(2); probs(3);
#pragma unroll
          for (int hf = 0; hf < 2; hf++) {
#pragma unroll
            for (int hh = 0; hh < 2; hh++) {
              const int h = hf * 2 + hh, b = h * 4;
              const uint32_t pa = pp[h][0], pb = pp[h][1];
              const uint32_t p0 = pa & ~lm, p1 = pa & z, p2 = pa & lm, p3 = pb & ~lm, p4 = pb & z, p5 = pb & lm;
              const float ra = rs[h][0], rb = rs[h][1];
#pragma unroll
              for (int d = 0; d < 4; d++) {
                float o[4];
                mma16816z(o, p0, p1, p2, p3, kvH[16 + b + d], pkA[32 + 2 * (b + d)]);
                mma1688(o, p4, p5, pkA[32 + 2 * (b + d) + 1], o);
                if (hf == 0) { ob[0][(hh * 4 + d) * 2] = pack_bf16(o[0] * ra, o[1] * ra); ob[0][(hh * 4 + d) * 2 + 1] = pack_bf16(o[2] * rb, o[3] * rb); }
                else { o2[hh * 4 + d][0] = o[0]; o2[hh * 4 + d][1] = o[1]; o2[hh * 4 + d][2] = o[2]; o2[hh * 4 + d][3] = o[3]; }
              }
              if (hf) { r2[2 * hh] = ra; r2[2 * hh + 1] = rb; }
            }
            if (hf == 0) {
#pragma unroll
              for (int i = 0; i < 4; i++) ob[0][4 * i] = pkt_head(ob[0][4 * i]);
              AP(5);
              uint4* op = scratch<uint4>(P, opaque(g * G_BLOCK + G_O + j * 32768u + warp * 2048u) + l16);
#pragma unroll
              for (int i = 0; i < 4; i++) st_b128(op + i * 32, ob[0][4 * i], ob[0][4 * i + 1], ob[0][4 * i + 2], ob[0][4 * i + 3]);
              z = late_zero(zm);
              AP(6);
            }
          }
        }
        auto finish_o2 = [&](uint32_t z) {
#pragma unroll
          for (int i = 0; i < 4; i++) r2[i] = __uint_as_float(__float_as_uint(r2[i]) | z);
#pragma unroll
          for (int i = 0; i < 8; i++) {
            ob[1][2 * i] = pack_bf16(o2[i][0] * r2[(i >> 2) * 2], o2[i][1] * r2[(i >> 2) * 2]);
            ob[1][2 * i + 1] = pack_bf16(o2[i][2] * r2[(i >> 2) * 2 + 1], o2[i][3] * r2[(i >> 2) * 2 + 1]);
          }
#pragma unroll
          for (int i = 0; i < 4; i++) { ob[1][4 * i] = pkt_head(ob[1][4 * i]); sts128(stage + (warp & 3) * 2048 + i * 512 + l16, ob[1][4 * i], ob[1][4 * i + 1], ob[1][4 * i + 2], ob[1][4 * i + 3]); }
        };
        {
          uint32_t dep = __float_as_uint(r2[0]) | __float_as_uint(r2[2]);
#pragma unroll
          for (int i = 0; i < 8; i++) dep |= __float_as_uint(o2[i][3]);
          const uint32_t cnt = 256 | (dep & zm);
          AP(7);
          if (wg) { asm volatile("bar.arrive 1, %0;" :: "r"(cnt) : "memory"); bar_sync(6, 256); } else bar_sync(1, cnt);
        }
        TLC(3 + it * 6);
        AP(8);
        uint64_t todo;
        { const uint32_t o7 = 0x6543210u | (7u << (4 * j) & 0xfffffffu); todo = (uint64_t)(o7 * 2) | (uint64_t)(o7 * 2 + 0x1111111u) << 28; }
        const uint4* pf[3];
        auto next_ptrs = [&](const uint4* (&p)[3]) {
#pragma unroll
          for (int i = 0; i < 3; i++) p[i] = ptr_add(omail, (((uint32_t)todo >> (4 * i)) & 15u) << 14);
          asm volatile("" : "+l"(p[0]), "+l"(p[1]), "+l"(p[2]));
          todo >>= 12;
        };
        next_ptrs(pf);
        auto batch = [&](int b, bool first, bool three) {
          const int y = 3 - b;
          auto o_fetch = [&]() {
#pragma unroll
            for (int i = 0; i < 8; i++) pkt_load(pf[i >> 2] + (i & 3) * 32, ob[y + (i >> 2)] + 4 * (i & 3));
            if (three) {
#pragma unroll
              for (int i = 0; i < 4; i++) pkt_load(pf[2] + i * 32, ob[y + 2] + 4 * i);
            }
          };
          if (first) {
            c.issue_rs<0, 2>(acc2, ob[0], 0);
            finish_o2(late_zero(zm));
            o_fetch();
            c.issue_rs<1, 2>(acc2, ob[1]);
            if (!wg) asm volatile("bar.arrive 6, 256;" ::: "memory");
          } else {
            o_fetch();
            c.issue_rs<0, 3>(acc2, ob[b]); c.issue_rs<1, 3>(acc2, ob[b + 1]); c.issue_rs<2, 3>(acc2, ob[b + 2]);
          }
          const uint32_t z = late_zero(zm);
          const uint4* pn[3];
          next_ptrs(pn);
          c.wait_full(0);
          uint32_t spins = 0;
          for (;;) {
            bool bad[3];
#pragma unroll
            for (int i = 0; i < 3; i++) bad[i] = ob[y + i][0] == z || ob[y + i][4] == z || ob[y + i][8] == z || ob[y + i][12] == z;
            if (__builtin_expect(!__any_sync(0xffffffffu, bad[0] | bad[1] | bad[2]), 1)) break;
            o_fetch();
            spin_check(++spins);
          }
          if (first) {
            fence_async_smem();
            __syncwarp();
            if (elect_one()) {
              asm volatile("cp.async.bulk.global.shared::cta.bulk_group [%0], [%1], 2048;"
                           :: "l"(scratch<uint4>(P, g * G_BLOCK + G_O + (2 * j + 1) * 16384u + warp * 2048u)), "r"(stage + (warp & 3) * 2048) : "memory");
              bulk_commit();
            }
          }
          pf[0] = pn[0]; pf[1] = pn[1]; pf[2] = pn[2];
          c.drain();
        };
        batch(0, true, true);
#pragma unroll 1
        for (int i = 0; i < 2; i++) { batch(3, false, true); batch(0, false, i == 0); }
        c.issue_rs<0, 2>(acc2, ob[3]); c.issue_rs<1, 2>(acc2, ob[4]);
        if (elect_one()) bulk_wait<0>();
        __syncwarp();
        {
          c.off += 2 << 10;
          c.wait_full(0);
          const uint32_t ra = maddr - (SM_STAGE + wg * 8192) + (c.off << 4);
#pragma unroll
          for (int i = 0; i < 8; i++) ldsm4((ra ^ ((i & 3) << 5)) + (i >> 2) * PAGE, res[4 * i], res[4 * i + 1], res[4 * i + 2], res[4 * i + 3]);
          if (lane < 2) mbar_arrive_cluster(c.ebar + 64 + ((c.n & 7) << 3));
          c.advance<2>();
          c.drain();
        }
        break;
      } else {
        c.steps<128>(acc2, 1 + wg);
        stage_wait();
        glu_slice_acc(acc, 0);
#pragma unroll
        for (int s = 1; s < 8; s++) {
          if (s == 5) c.steps_skip(acc2, t == 1 ? 1 - wg : 2); else c.steps<128>(acc2, (s & 1) || t == 3 ? 2 : 1);
          if (s == 4) stage_publish();
          glu_slice_acc(acc, s);
        }
        c.steps<128>(acc2, 2 - wg);
        stage_publish();
        if (t == 3) {
          c.steps<128>(acc2, RES_AT + wg);
          const uint4* rp = scratch<uint4>(P, g * G_BLOCK + G_O + j * 32768u + warp * 4096u + lane_now() * 16u);
#pragma unroll
          for (int i = 0; i < 8; i++) pkt_load(rp + i * 32, res + 4 * i);
          c.steps<128>(acc2, 4);
          uint32_t spins = 0;
          while (__any_sync(0xffffffffu, !(res[0] && res[4] && res[8] && res[12] && res[16] && res[20] && res[24] && res[28]))) {
#pragma unroll
            for (int i = 0; i < 8; i++) pkt_load(rp + i * 32, res + 4 * i);
            spin_check(++spins);
          }
#pragma unroll 1
          for (int i = 0; i < 2; i++) {
            c.steps<128>(acc2, i ? TAIL_LAG : 33 - RES_AT - TAIL_LAG - wg);
            if (hl == 3) { if (wg == 1 && i == 0) c.drain(); if (wg + i == 1) bar_sync(5, 256); }
          }
          stage_wait();
          c.drain();
          break;
        }
        c.drain();
        TLC(2 + it * 6);
        c.step<256>(acc, 0);
        acc_fence<64>(acc2);
#pragma unroll
        for (int i = 0; i < 16; i++) {
          pkB[16 + i] = pack_bf16(acc2[2 * i], acc2[2 * i + 1]); pkB[48 + i] = pack_bf16(acc2[32 + 2 * i], acc2[32 + 2 * i + 1]);
          pkB[i] = 0; pkB[32 + i] = 0;
        }
      }
      t++;
#pragma unroll 1
      for (int s = 3 - t; s < 8; s++) {
        c.step<256>(acc, s);
        int act = (t == 3 || s >= 4) ? s : 8;
        asm volatile("" : "+r"(act));
        if (act < 8) {
          if (!(act & 3)) { if (act && t == 3) stage_publish(); else stage_wait(); }
          auto f = [&](int i) { glu_slice(pkB, i); };
          SELECT8(act, f);
        }
      }
#pragma unroll
      for (int s = 0; s < 2; s++) {
        const uint32_t ra = maddr - (SM_STAGE + wg * 8192) + (c.off << 4);
        c.step<256>(acc);
        if (s == 0) stage_publish();
#pragma unroll
        for (int i = 0; i < 4; i++) {
          uint32_t v[4];
          ldsm4(ra ^ (i << 5), v[0], v[1], v[2], v[3]);
#pragma unroll
          for (int e = 0; e < 4; e++) { acc2[32 * s + 8 * i + 2 * e] = bf_lo(v[e]); acc2[32 * s + 8 * i + 2 * e + 1] = bf_hi(v[e]); }
        }
        acc_fence<32>(acc2 + 32 * s);
      }
      if (WSKIP == 10) c.skip3();
      c.step<256>(acc);
      }
      const int it = (hl >> 1) * 4 + t;
      acc_fence<64>(acc2);
      TLC(4 + it * 6);
      uint32_t xn[32];
#pragma unroll
      for (int i = 0; i < 16; i++) xn[i] = add_bf16x2(res[i], pack_bf16(acc2[2 * i], acc2[2 * i + 1]));
      const uint32_t xaddr = hl == 3 ? maddr - SM_STAGE : maddr;
      stage_x(xn, 0, xaddr);
#pragma unroll
      for (int i = 16; i < 32; i++) { xn[i] = add_bf16x2(res[i], pack_bf16(acc2[2 * i], acc2[2 * i + 1])); asm volatile("" : "+r"(xn[i])); }
      stage_publish();
      if (hl == 3) { stage_x(xn, 1, xaddr); stage_publish(); TLE(47); TLG(63); break; }
      bar_sync(2 + wg, 128);
      TLC(5 + it * 6);
      c.step_own<256>(acc, dstage, 0);
      stage_x(xn, 1, maddr);
      stage_publish();
      bar_sync(2 + wg, 128);
    }
    }
  }
}

typedef CUresult (*EncodeFn)(CUtensorMap*, CUtensorMapDataType, cuuint32_t, void*, const cuuint64_t*, const cuuint64_t*, const cuuint32_t*,
                             const cuuint32_t*, CUtensorMapInterleave, CUtensorMapSwizzle, CUtensorMapL2promotion, CUtensorMapFloatOOBfill);

void encode(EncodeFn fn, CUtensorMap* m, const void* ptr, int rank, const cuuint64_t* dims, const cuuint64_t* strides, const cuuint32_t* box) {
  cuuint32_t es[5] = {1, 1, 1, 1, 1};
  fn(m, CU_TENSOR_MAP_DATA_TYPE_BFLOAT16, rank, const_cast<void*>(ptr), dims, strides, box, es, CU_TENSOR_MAP_INTERLEAVE_NONE,
     CU_TENSOR_MAP_SWIZZLE_128B, CU_TENSOR_MAP_L2_PROMOTION_L2_128B, CU_TENSOR_MAP_FLOAT_OOB_FILL_NONE);
}

}

extern "C" void kernel_launch(void* const* d_in, const int* in_sizes, int n_in, void* d_out, int out_size) {
  const __nv_bfloat16* x = (const __nv_bfloat16*)d_in[0];
  const __nv_bfloat16* wqkv = (const __nv_bfloat16*)d_in[1];
  const __nv_bfloat16* wo = (const __nv_bfloat16*)d_in[2];
  const __nv_bfloat16* w1 = (const __nv_bfloat16*)d_in[4];
  const __nv_bfloat16* w3 = (const __nv_bfloat16*)d_in[5];
  const __nv_bfloat16* w2 = (const __nv_bfloat16*)d_in[6];

  void* fnp = nullptr; cudaDriverEntryPointQueryResult qr;
  cudaGetDriverEntryPoint("cuTensorMapEncodeTiled", &fnp, cudaEnableDefault, &qr);
  EncodeFn fn = (EncodeFn)fnp;
  void* sym;
  cudaGetSymbolAddress(&sym, g_scratch);
  uint8_t* scr = (uint8_t*)(((uintptr_t)sym + G_PAGE - 1) / G_PAGE * G_PAGE);

  Params P = {};
  { cuuint64_t d[3] = {DM, 2, SEQ / 2}, s[2] = {DM * 2, DM * 4}; cuuint32_t b[3] = {64, 1, 128}, b2[3] = {64, 1, 64};
    encode(fn, &P.map[M_XIN], x, 3, d, s, b); encode(fn, &P.map[M_XIN64], x, 3, d, s, b2);
    encode(fn, &P.map[M_OUT_LD], d_out, 3, d, s, b); encode(fn, &P.map[M_OUT_ST], d_out, 3, d, s, b2); }
  { cuuint64_t d[3] = {FF, 16, 128}, s[2] = {G_BLOCK, FF * 2}; cuuint32_t b[3] = {64, 1, 128}, b2[3] = {64, 1, H_ROWS};
    encode(fn, &P.map[M_H_LD], scr + G_H, 3, d, s, b); encode(fn, &P.map[M_H_ST], scr + G_H, 3, d, s, b2); }
  { const cuuint32_t b2[3] = {64, 64, 2}, b1[3] = {64, 64, 1};
    { cuuint64_t d[3] = {64, DM, 48}, s[2] = {3 * DM * 2, 128}; encode(fn, &P.map[M_WKV], wqkv, 3, d, s, b2); encode(fn, &P.map[M_WQ], wqkv, 3, d, s, b1); }
    { cuuint64_t d[3] = {64, DM, 16}, s[2] = {DM * 2, 128}; encode(fn, &P.map[M_WO], wo, 3, d, s, b1); }
    { cuuint64_t d[3] = {64, FF, 16}, s[2] = {DM * 2, 128}; encode(fn, &P.map[M_W2], w2, 3, d, s, b1); }
    { cuuint64_t d[3] = {64, DM, FF / 64}, s[2] = {FF * 2, 128};
      encode(fn, &P.map[M_W1], w1, 3, d, s, b2); encode(fn, &P.map[M_W3], w3, 3, d, s, b2);
      encode(fn, &P.map[M_W1H], w1, 3, d, s, b1); encode(fn, &P.map[M_W3H], w3, 3, d, s, b1); }
  }
  P.scratch = scr; P.x = x; P.wqkv = wqkv; P.wo = wo; P.w2 = w2;
  int dev = 0, sms = 0;
  cudaGetDevice(&dev);
  cudaDeviceGetAttribute(&sms, cudaDevAttrMultiProcessorCount, dev);
  P.use_smid = (sms == 132);
  cudaFuncSetAttribute(fused_kernel, cudaFuncAttributeMaxDynamicSharedMemorySize, SM_ALLOC);
  fused_kernel<<<132, 384, SM_ALLOC>>>(P);
}
```

```cpp
#include <cuda_runtime.h>
#include <cuda_bf16.h>
#include <cuda.h>
#include <stdint.h>
#include <math.h>

namespace {

constexpr int SEQ = 2048, DM = 1024, FF = 3584;
constexpr float LN_EPS = 1e-5f;
constexpr float LOG2E = 1.4426950408889634f;

#define G_SKEW 4096
constexpr uint32_t G_PAGE = 2u << 20, G_BLOCK = G_PAGE + G_SKEW;
constexpr uint32_t G_H = 0;
constexpr uint32_t G_O = G_H + 128 * FF * 2;
constexpr uint32_t G_STATS = G_O + 128 * DM * 2;
constexpr uint32_t G_FLAGS = G_STATS + 4 * 128 * 64;
static_assert(G_FLAGS + 4096 + 15 * G_SKEW <= G_PAGE, "");
constexpr uint32_t G_HALO = 16 * G_PAGE;
constexpr uint32_t G_CS = G_HALO + 2 * 16 * 8 * 4096;
constexpr uint32_t G_EPOCH = G_CS + (3 * DM + 2 * FF) * 16;
__device__ __align__(1024) uint8_t g_scratch[18 * G_PAGE];

enum { M_XIN, M_XIN64, M_H_LD, M_H_ST, M_OUT_LD, M_OUT_ST, M_WKV, M_WQ, M_WO, M_W1, M_W3, M_W1H, M_W3H, M_W2, M_COUNT };
struct alignas(64) Params {
  CUtensorMap map[M_COUNT];
  uint8_t* scratch;
  const __nv_bfloat16* x;
  const __nv_bfloat16* wqkv;
  const __nv_bfloat16* wo;
  const __nv_bfloat16* w2;
  int use_smid;
};

constexpr uint32_t PAGE = 16384, NPAGE = 12;
constexpr uint32_t SM_STAGE = NPAGE * PAGE;
constexpr uint32_t SM_BAR = SM_STAGE + 2 * PAGE;
constexpr uint32_t SM_CS = SM_BAR + 256;
constexpr uint32_t SM_TOTAL = SM_CS + 1536;
constexpr uint32_t SM_ALLOC = SM_TOTAL;
static_assert(SM_ALLOC <= 232448, "shared memory");
constexpr uint32_t BAR_FULL = SM_BAR, BAR_EMPTY = SM_BAR + 64, BAR_SFULL = SM_BAR + 128;
constexpr uint32_t BAR_XFULL = SM_BAR + 160, BAR_CSE = SM_BAR + 168;
constexpr uint32_t BAR_SEMPTY = SM_BAR + 176, BAR_CSF = SM_BAR + 184, BAR_XIN = SM_BAR + 200;
constexpr uint32_t BAR_CLR = SM_BAR + 240, BAR_CLR2 = SM_BAR + 248, BAR_TAG = SM_BAR + 216, SM_ROLE = SM_BAR + 224, SM_TAG = SM_BAR + 228, SM_SEEN = SM_BAR + 232;
enum { EV_XA, EV_XA2, EV_H0, EV_H3, EV_H1, EV_H2, EV_XB, EV_XB2, EV_N };

#define WSKIP 15
struct Sched { uint32_t pat[16]; uint32_t page0[16]; bool ok; };
constexpr int seg_steps(int seg) { return seg == 0 || seg == 3 ? 18 : seg == 1 || seg == 4 ? 14 : seg == 2 ? 7 : seg == 7 ? 54 : 16; }
constexpr int step_pages(int seg, int i) {
  return seg == 0 || seg == 3 ? (i < 2 ? 2 : i < 4 ? 1 : 3) : seg == 5 || seg == 6 || (seg == 2 && i >= 1 && i <= 4) ? 3 : 2;
}
constexpr Sched make_sched() {
  Sched s = {};
  int owner[NPAGE] = {-1, -1, -1, -1, -1, -1, -1, -1, -1, -1, -1, -1};
  int n = 0, tail = 0, page = 0;
  s.ok = true;
  for (int sg = 0; sg < 16; sg++) {
    const int seg = sg % 8;
    s.page0[sg] = page;
    for (int i = 0; i < seg_steps(seg); i++) {
      const int p = step_pages(seg, i);
      if ((seg == 2 && i == 6) || (seg == 4 && i == 8)) page = (page + 2) % NPAGE;
      if ((seg == 5 || seg == 6) && i == WSKIP) page = (page + 3) % NPAGE;
      if (page + p > (int)NPAGE) { s.ok = false; return s; }
      int need = n - 8;
      for (int q = 0; q < p; q++) { if (owner[page + q] > need) need = owner[page + q]; owner[page + q] = n; }
      int nw = need + 1 - tail; if (nw < 0) nw = 0;
      tail += nw;
      if (i < 16) s.pat[sg] |= (uint32_t)nw << (2 * i); else if (nw != 1) s.ok = false;
      if (nw > 3) s.ok = false;
      page = (page + p) % NPAGE; n++;
    }
  }
  for (int sg = 0; sg < 8; sg++) if (s.page0[sg] != s.page0[sg + 8] || (sg && s.pat[sg] != s.pat[sg + 8])) s.ok = false;
  return s;
}
constexpr Sched SCHED = make_sched();
static_assert(SCHED.ok && SCHED.page0[0] == 0 && SCHED.page0[3] == 0 && SCHED.page0[5] == 6 && SCHED.page0[2] == 4 && SCHED.page0[7] == 0 && (SCHED.pat[0] & 0xfff) == 0, "ring schedule");
template <int SEG> struct Pat { static constexpr uint32_t v = SCHED.pat[SEG]; };

constexpr int H_ROWS = 16;
#define RES_AT 26
#define TAIL_LAG 3
__device__ __forceinline__ uint32_t smem_u32(const void* p) { return (uint32_t)__cvta_generic_to_shared(p); }
__device__ __forceinline__ void mbar_init(uint32_t bar, uint32_t cnt) { asm volatile("mbarrier.init.shared::cta.b64 [%0], %1;" :: "r"(bar), "r"(cnt)); }
__device__ __forceinline__ void mbar_expect_tx(uint32_t bar, uint32_t bytes) { asm volatile("mbarrier.arrive.expect_tx.shared::cta.b64 _, [%0], %1;" :: "r"(bar), "r"(bytes) : "memory"); }
__device__ __forceinline__ void mbar_arrive(uint32_t bar) { asm volatile("mbarrier.arrive.shared::cta.b64 _, [%0];" :: "r"(bar) : "memory"); }
__device__ __forceinline__ void mbar_wait(uint32_t bar, uint32_t parity) {
  asm volatile("{\n.reg .pred p;\n.reg .u32 n;\nmov.u32 n, 0;\nLAB_WAIT:\n"
               "mbarrier.try_wait.parity.shared::cta.b64 p, [%0], %1;\n@p bra LAB_DONE;\n"
               "add.u32 n, n, 1;\nsetp.lt.u32 p, n, 4194304;\n@p bra LAB_WAIT;\ntrap;\nLAB_DONE:\n}" :: "r"(bar), "r"(parity) : "memory");
}
__device__ __forceinline__ void mbar_wait_fast(uint32_t bar, uint32_t parity) {
  asm volatile("{\n.reg .pred p;\nLAB_WAIT:\nmbarrier.try_wait.parity.shared::cta.b64 p, [%0], %1;\n@!p bra LAB_WAIT;\n}" :: "r"(bar), "r"(parity) : "memory");
}
__device__ __forceinline__ void spin_check(uint32_t n) { asm volatile("{\n.reg .pred p;\nsetp.ge.u32 p, %0, 4194304;\n@p st.volatile.global.u32 [%1], %0;\n}" :: "r"(n), "l"(0ull)); }
__device__ __forceinline__ void tma_ld3(uint32_t dst, const CUtensorMap* m, uint32_t bar, int c0, int c1, int c2) {
  asm volatile("cp.async.bulk.tensor.3d.shared::cluster.global.mbarrier::complete_tx::bytes [%0], [%1, {%3, %4, %5}], [%2];" :: "r"(dst), "l"(m), "r"(bar), "r"(c0), "r"(c1), "r"(c2) : "memory");
}
__device__ __forceinline__ void tma_ld3_mc(uint32_t dst, const CUtensorMap* m, uint32_t bar, int c0, int c1, int c2, uint16_t mask) {
  asm volatile("cp.async.bulk.tensor.3d.shared::cluster.global.mbarrier::complete_tx::bytes.multicast::cluster [%0], [%1, {%3, %4, %5}], [%2], %6;"
               :: "r"(dst), "l"(m), "r"(bar), "r"(c0), "r"(c1), "r"(c2), "h"(mask) : "memory");
}
__device__ __forceinline__ uint32_t mapa(uint32_t addr, uint32_t cta) { uint32_t r; asm("mapa.shared::cluster.u32 %0, %1, %2;" : "=r"(r) : "r"(addr), "r"(cta)); return r; }
__device__ __forceinline__ void mbar_arrive_cluster(uint32_t bar) { asm volatile("mbarrier.arrive.shared::cluster.b64 _, [%0];" :: "r"(bar) : "memory"); }
__device__ __forceinline__ void tma_st3(const CUtensorMap* m, uint32_t src, int c0, int c1, int c2) {
  asm volatile("cp.async.bulk.tensor.3d.global.shared::cta.bulk_group [%0, {%2, %3, %4}], [%1];" :: "l"(m), "r"(src), "r"(c0), "r"(c1), "r"(c2) : "memory");
}
__device__ __forceinline__ void bulk_commit() { asm volatile("cp.async.bulk.commit_group;" ::: "memory"); }
template <int N> __device__ __forceinline__ void bulk_wait() { asm volatile("cp.async.bulk.wait_group %0;" :: "n"(N) : "memory"); }
__device__ __forceinline__ void fence_async_smem() { asm volatile("fence.proxy.async.shared::cta;" ::: "memory"); }
__device__ __forceinline__ void fence_async_global() { asm volatile("fence.proxy.async.global;" ::: "memory"); }
__device__ __forceinline__ bool elect_one() { uint32_t p; asm volatile("{\n.reg .pred P;\nelect.sync _|P, 0xffffffff;\nselp.u32 %0, 1, 0, P;\n}" : "=r"(p)); return p; }
__device__ __forceinline__ void prefetch_map(const CUtensorMap* m) { asm volatile("prefetch.tensormap [%0];" :: "l"(m) : "memory"); }
__device__ __forceinline__ void prefetch_l2(const void* p, uint32_t bytes) { asm volatile("cp.async.bulk.prefetch.L2.global [%0], %1;" :: "l"(p), "r"(bytes) : "memory"); }
__device__ __forceinline__ void wgmma_fence() { asm volatile("wgmma.fence.sync.aligned;" ::: "memory"); }
__device__ __forceinline__ void wgmma_commit() { asm volatile("wgmma.commit_group.sync.aligned;" ::: "memory"); }
template <int N> __device__ __forceinline__ void wgmma_wait() { asm volatile("wgmma.wait_group.sync.aligned %0;" :: "n"(N) : "memory"); }
__device__ __forceinline__ uint32_t desc_lo(uint32_t addr, uint32_t lbo) { return ((addr & 0x3FFFF) >> 4) | ((lbo >> 4) << 16); }
__device__ __forceinline__ uint64_t desc64(uint32_t lo) { uint64_t r; asm("mov.b64 %0, {%1, %2};" : "=l"(r) : "r"(lo), "r"(0x40000040u)); return r; }
__device__ __forceinline__ void bar_sync(int id, int n) { asm volatile("bar.sync %0, %1;" :: "r"(id), "r"(n) : "memory"); }
__device__ __forceinline__ uint32_t pack_bf16(float lo, float hi) { uint32_t r; asm("cvt.rn.bf16x2.f32 %0, %1, %2;" : "=r"(r) : "f"(hi), "f"(lo)); return r; }
__device__ __forceinline__ float bf_lo(uint32_t v) { return __uint_as_float(v << 16); }
__device__ __forceinline__ float bf_hi(uint32_t v) { return __uint_as_float(v & 0xffff0000u); }
__device__ __forceinline__ float ex2(float x) { float r; asm("ex2.approx.ftz.f32 %0, %1;" : "=f"(r) : "f"(x)); return r; }
__device__ __forceinline__ float rcp(float x) { float r; asm("rcp.approx.ftz.f32 %0, %1;" : "=f"(r) : "f"(x)); return r; }
__device__ __forceinline__ void stsm4(uint32_t a, uint32_t r0, uint32_t r1, uint32_t r2, uint32_t r3) {
  asm volatile("stmatrix.sync.aligned.m8n8.x4.shared.b16 [%0], {%1, %2, %3, %4};" :: "r"(a), "r"(r0), "r"(r1), "r"(r2), "r"(r3) : "memory");
}
__device__ __forceinline__ void ldsm4(uint32_t a, uint32_t& r0, uint32_t& r1, uint32_t& r2, uint32_t& r3) {
  asm volatile("ldmatrix.sync.aligned.m8n8.x4.shared.b16 {%0, %1, %2, %3}, [%4];" : "=r"(r0), "=r"(r1), "=r"(r2), "=r"(r3) : "r"(a) : "memory");
}
__device__ __forceinline__ uint32_t movm(uint32_t v) { uint32_t r; asm volatile("movmatrix.sync.aligned.m8n8.trans.b16 %0, %1;" : "=r"(r) : "r"(v)); return r; }
__device__ __forceinline__ void sts128(uint32_t a, uint32_t r0, uint32_t r1, uint32_t r2, uint32_t r3) {
  asm volatile("st.shared.v4.b32 [%0], {%1, %2, %3, %4};" :: "r"(a), "r"(r0), "r"(r1), "r"(r2), "r"(r3) : "memory");
}
__device__ __forceinline__ void lds128(uint32_t a, uint32_t& r0, uint32_t& r1, uint32_t& r2, uint32_t& r3) {
  asm volatile("ld.shared.v4.b32 {%0, %1, %2, %3}, [%4];" : "=r"(r0), "=r"(r1), "=r"(r2), "=r"(r3) : "r"(a) : "memory");
}
__device__ __forceinline__ uint32_t add_bf16x2(uint32_t a, uint32_t b) { uint32_t r; asm("add.rn.bf16x2 %0, %1, %2;" : "=r"(r) : "r"(a), "r"(b)); return r; }
__device__ __forceinline__ void sts32f(uint32_t a, float v) { asm volatile("st.shared.f32 [%0], %1;" :: "r"(a), "f"(v) : "memory"); }
__device__ __forceinline__ void mma16816(float (&d)[4], uint32_t a0, uint32_t a1, uint32_t a2, uint32_t a3, uint32_t b0, uint32_t b1, const float (&c)[4]) {
  asm("mma.sync.aligned.m16n8k16.row.col.f32.bf16.bf16.f32 {%0, %1, %2, %3}, {%4, %5, %6, %7}, {%8, %9}, {%10, %11, %12, %13};"
      : "=f"(d[0]), "=f"(d[1]), "=f"(d[2]), "=f"(d[3]) : "r"(a0), "r"(a1), "r"(a2), "r"(a3), "r"(b0), "r"(b1), "f"(c[0]), "f"(c[1]), "f"(c[2]), "f"(c[3]));
}
__device__ __forceinline__ void mma1688(float (&d)[4], uint32_t a0, uint32_t a1, uint32_t b0, const float (&c)[4]) {
  asm("mma.sync.aligned.m16n8k8.row.col.f32.bf16.bf16.f32 {%0, %1, %2, %3}, {%4, %5}, {%6}, {%7, %8, %9, %10};"
      : "=f"(d[0]), "=f"(d[1]), "=f"(d[2]), "=f"(d[3]) : "r"(a0), "r"(a1), "r"(b0), "f"(c[0]), "f"(c[1]), "f"(c[2]), "f"(c[3]));
}
__device__ __forceinline__ void mma16816z(float (&d)[4], uint32_t a0, uint32_t a1, uint32_t a2, uint32_t a3, uint32_t b0, uint32_t b1) {
  asm("mma.sync.aligned.m16n8k16.row.col.f32.bf16.bf16.f32 {%0, %1, %2, %3}, {%4, %5, %6, %7}, {%8, %9}, {0f00000000, 0f00000000, 0f00000000, 0f00000000};"
      : "=f"(d[0]), "=f"(d[1]), "=f"(d[2]), "=f"(d[3]) : "r"(a0), "r"(a1), "r"(a2), "r"(a3), "r"(b0), "r"(b1));
}
__device__ __forceinline__ void mma1688z(float (&d)[4], uint32_t a0, uint32_t a1, uint32_t b0) {
  asm("mma.sync.aligned.m16n8k8.row.col.f32.bf16.bf16.f32 {%0, %1, %2, %3}, {%4, %5}, {%6}, {0f00000000, 0f00000000, 0f00000000, 0f00000000};"
      : "=f"(d[0]), "=f"(d[1]), "=f"(d[2]), "=f"(d[3]) : "r"(a0), "r"(a1), "r"(b0));
}
__device__ __forceinline__ uint32_t bar_sync_zero(int id, int n) {
  uint32_t r;
  asm volatile("{\n.reg .pred p;\nsetp.eq.u32 p, %1, 0;\nbarrier.cta.red.popc.aligned.u32 %0, %1, %2, p;\n}" : "=r"(r) : "r"(id), "r"(n) : "memory");
  return r;
}
__device__ __forceinline__ uint32_t late_zero(uint32_t zm) { uint32_t c; asm volatile("mov.u32 %0, %%clock;" : "=r"(c) :: "memory"); return c & zm; }
__device__ __forceinline__ void st_b128(uint4* p, uint32_t a, uint32_t b, uint32_t c, uint32_t d) {
  asm volatile("{\n.reg .b128 t;\n.reg .b64 lo, hi;\nmov.b64 lo, {%0, %1};\nmov.b64 hi, {%2, %3};\nmov.b128 t, {lo, hi};\nst.relaxed.gpu.global.b128 [%4], t;\n}"
               :: "r"(a), "r"(b), "r"(c), "r"(d), "l"(p) : "memory");
}
__device__ __forceinline__ uint32_t pkt_head(uint32_t a) { return a ? a : 0x8000u; }
__device__ __forceinline__ void gen_store(uint4* p, uint32_t a, uint32_t b, uint32_t c, uint32_t d) {
  asm volatile("{\n.reg .b128 t;\n.reg .b64 lo, hi;\nmov.b64 lo, {%0, %1};\nmov.b64 hi, {%2, %3};\nmov.b128 t, {lo, hi};\nst.relaxed.gpu.b128 [%4], t;\n}"
               :: "r"(a), "r"(b), "r"(c), "r"(d), "l"(p) : "memory");
}
__device__ __forceinline__ void gen_load(const uint4* p, uint32_t* v) {
  asm volatile("{\n.reg .b128 t;\n.reg .b64 lo, hi;\nld.relaxed.gpu.b128 t, [%4];\nmov.b128 {lo, hi}, t;\nmov.b64 {%0, %1}, lo;\nmov.b64 {%2, %3}, hi;\n}"
               : "=r"(v[0]), "=r"(v[1]), "=r"(v[2]), "=r"(v[3]) : "l"(p) : "memory");
}
__device__ __forceinline__ void pkt_load(const uint4* p, uint32_t* v) {
  asm volatile("{\n.reg .b128 t;\n.reg .b64 lo, hi;\nld.relaxed.gpu.global.b128 t, [%4];\nmov.b128 {lo, hi}, t;\nmov.b64 {%0, %1}, lo;\nmov.b64 {%2, %3}, hi;\n}"
               : "=r"(v[0]), "=r"(v[1]), "=r"(v[2]), "=r"(v[3]) : "l"(p) : "memory");
}
__device__ __forceinline__ uint32_t ld_relaxed(const uint32_t* p) { uint32_t v; asm volatile("ld.relaxed.gpu.global.u32 %0, [%1];" : "=r"(v) : "l"(p) : "memory"); return v; }
__device__ __forceinline__ uint4 ld_relaxed4(const void* p) { uint4 v; asm volatile("ld.relaxed.gpu.global.v4.u32 {%0, %1, %2, %3}, [%4];" : "=r"(v.x), "=r"(v.y), "=r"(v.z), "=r"(v.w) : "l"(p) : "memory"); return v; }
__device__ __forceinline__ void st_relaxed(uint32_t* p, uint32_t v) { asm volatile("st.relaxed.gpu.global.u32 [%0], %1;" :: "l"(p), "r"(v) : "memory"); }
__device__ __forceinline__ void st_relaxed2(void* p, uint32_t a, uint32_t b) { asm volatile("st.relaxed.gpu.global.v2.u32 [%0], {%1, %2};" :: "l"(p), "r"(a), "r"(b) : "memory"); }
__device__ __forceinline__ void red_release(uint32_t* p, uint32_t v) { asm volatile("red.release.gpu.global.add.u32 [%0], %1;" :: "l"(p), "r"(v) : "memory"); }
__device__ __forceinline__ uint32_t tagf(float v, uint32_t tag) { return (__float_as_uint(v) & ~15u) | (tag & 15u); }
__device__ __forceinline__ bool tag_ok4(const uint4& v, uint32_t tag) { return (((v.x ^ tag) | (v.y ^ tag) | (v.z ^ tag) | (v.w ^ tag)) & 15u) == 0; }
__device__ __forceinline__ float untag(uint32_t v) { return __uint_as_float(v & ~15u); }
template <typename T> __device__ __forceinline__ T* ptr_add(T* p, uint32_t bytes) {
  uint64_t r;
  asm("{\n.reg .u32 lo, hi;\nmov.b64 {lo, hi}, %1;\nadd.cc.u32 lo, lo, %2;\naddc.u32 hi, hi, 0;\nmov.b64 %0, {lo, hi};\n}" : "=l"(r) : "l"(p), "r"(bytes));
  return (T*)r;
}
#define TL(who, slot) do {} while (0)
#define TLC(slot) do {} while (0)
#define TLE(slot) do {} while (0)
#define ST(who, n) do {} while (0)
#define AP(i) do {} while (0)
#define SP(v) do {} while (0)
#define TLG(slot) do {} while (0)
#define STA() do {} while (0)
#define STB(n) do {} while (0)

__device__ __forceinline__ void wgmma_n128(float (&d)[64], uint64_t da, uint64_t db, int scale_d) {
  asm volatile("{\n.reg .pred p;\nsetp.ne.b32 p, %66, 0;\n"
    "wgmma.mma_async.sync.aligned.m64n128k16.f32.bf16.bf16 "
    "{%0, %1, %2, %3, %4, %5, %6, %7, %8, %9, %10, %11, %12, %13, %14, %15, "
    "%16, %17, %18, %19, %20, %21, %22, %23, %24, %25, %26, %27, %28, %29, %30, %31, "
    "%32, %33, %34, %35, %36, %37, %38, %39, %40, %41, %42, %43, %44, %45, %46, %47, "
    "%48, %49, %50, %51, %52, %53, %54, %55, %56, %57, %58, %59, %60, %61, %62, %63}, "
    "%64, %65, p, 1, 1, 0, 1;\n}\n"
    : "+f"(d[0]), "+f"(d[1]), "+f"(d[2]), "+f"(d[3]), "+f"(d[4]), "+f"(d[5]), "+f"(d[6]), "+f"(d[7]),
      "+f"(d[8]), "+f"(d[9]), "+f"(d[10]), "+f"(d[11]), "+f"(d[12]), "+f"(d[13]), "+f"(d[14]), "+f"(d[15]),
      "+f"(d[16]), "+f"(d[17]), "+f"(d[18]), "+f"(d[19]), "+f"(d[20]), "+f"(d[21]), "+f"(d[22]), "+f"(d[23]),
      "+f"(d[24]), "+f"(d[25]), "+f"(d[26]), "+f"(d[27]), "+f"(d[28]), "+f"(d[29]), "+f"(d[30]), "+f"(d[31]),
      "+f"(d[32]), "+f"(d[33]), "+f"(d[34]), "+f"(d[35]), "+f"(d[36]), "+f"(d[37]), "+f"(d[38]), "+f"(d[39]),
      "+f"(d[40]), "+f"(d[41]), "+f"(d[42]), "+f"(d[43]), "+f"(d[44]), "+f"(d[45]), "+f"(d[46]), "+f"(d[47]),
      "+f"(d[48]), "+f"(d[49]), "+f"(d[50]), "+f"(d[51]), "+f"(d[52]), "+f"(d[53]), "+f"(d[54]), "+f"(d[55]),
      "+f"(d[56]), "+f"(d[57]), "+f"(d[58]), "+f"(d[59]), "+f"(d[60]), "+f"(d[61]), "+f"(d[62]), "+f"(d[63])
    : "l"(da), "l"(db), "r"(scale_d));
}
__device__ __forceinline__ void wgmma_n256(float (&d)[128], uint64_t da, uint64_t db, int scale_d) {
  asm volatile("{\n.reg .pred p;\nsetp.ne.b32 p, %130, 0;\n"
    "wgmma.mma_async.sync.aligned.m64n256k16.f32.bf16.bf16 "
    "{%0, %1, %2, %3, %4, %5, %6, %7, %8, %9, %10, %11, %12, %13, %14, %15, "
    "%16, %17, %18, %19, %20, %21, %22, %23, %24, %25, %26, %27, %28, %29, %30, %31, "
    "%32, %33, %34, %35, %36, %37, %38, %39, %40, %41, %42, %43, %44, %45, %46, %47, "
    "%48, %49, %50, %51, %52, %53, %54, %55, %56, %57, %58, %59, %60, %61, %62, %63, "
    "%64, %65, %66, %67, %68, %69, %70, %71, %72, %73, %74, %75, %76, %77, %78, %79, "
    "%80, %81, %82, %83, %84, %85, %86, %87, %88, %89, %90, %91, %92, %93, %94, %95, "
    "%96, %97, %98, %99, %100, %101, %102, %103, %104, %105, %106, %107, %108, %109, %110, %111, "
    "%112, %113, %114, %115, %116, %117, %118, %119, %120, %121, %122, %123, %124, %125, %126, %127}, "
    "%128, %129, p, 1, 1, 0, 1;\n}\n"
    : "+f"(d[0]), "+f"(d[1]), "+f"(d[2]), "+f"(d[3]), "+f"(d[4]), "+f"(d[5]), "+f"(d[6]), "+f"(d[7]),
      "+f"(d[8]), "+f"(d[9]), "+f"(d[10]), "+f"(d[11]), "+f"(d[12]), "+f"(d[13]), "+f"(d[14]), "+f"(d[15]),
      "+f"(d[16]), "+f"(d[17]), "+f"(d[18]), "+f"(d[19]), "+f"(d[20]), "+f"(d[21]), "+f"(d[22]), "+f"(d[23]),
      "+f"(d[24]), "+f"(d[25]), "+f"(d[26]), "+f"(d[27]), "+f"(d[28]), "+f"(d[29]), "+f"(d[30]), "+f"(d[31]),
      "+f"(d[32]), "+f"(d[33]), "+f"(d[34]), "+f"(d[35]), "+f"(d[36]), "+f"(d[37]), "+f"(d[38]), "+f"(d[39]),
      "+f"(d[40]), "+f"(d[41]), "+f"(d[42]), "+f"(d[43]), "+f"(d[44]), "+f"(d[45]), "+f"(d[46]), "+f"(d[47]),
      "+f"(d[48]), "+f"(d[49]), "+f"(d[50]), "+f"(d[51]), "+f"(d[52]), "+f"(d[53]), "+f"(d[54]), "+f"(d[55]),
      "+f"(d[56]), "+f"(d[57]), "+f"(d[58]), "+f"(d[59]), "+f"(d[60]), "+f"(d[61]), "+f"(d[62]), "+f"(d[63]),
      "+f"(d[64]), "+f"(d[65]), "+f"(d[66]), "+f"(d[67]), "+f"(d[68]), "+f"(d[69]), "+f"(d[70]), "+f"(d[71]),
      "+f"(d[72]), "+f"(d[73]), "+f"(d[74]), "+f"(d[75]), "+f"(d[76]), "+f"(d[77]), "+f"(d[78]), "+f"(d[79]),
      "+f"(d[80]), "+f"(d[81]), "+f"(d[82]), "+f"(d[83]), "+f"(d[84]), "+f"(d[85]), "+f"(d[86]), "+f"(d[87]),
      "+f"(d[88]), "+f"(d[89]), "+f"(d[90]), "+f"(d[91]), "+f"(d[92]), "+f"(d[93]), "+f"(d[94]), "+f"(d[95]),
      "+f"(d[96]), "+f"(d[97]), "+f"(d[98]), "+f"(d[99]), "+f"(d[100]), "+f"(d[101]), "+f"(d[102]), "+f"(d[103]),
      "+f"(d[104]), "+f"(d[105]), "+f"(d[106]), "+f"(d[107]), "+f"(d[108]), "+f"(d[109]), "+f"(d[110]), "+f"(d[111]),
      "+f"(d[112]), "+f"(d[113]), "+f"(d[114]), "+f"(d[115]), "+f"(d[116]), "+f"(d[117]), "+f"(d[118]), "+f"(d[119]),
      "+f"(d[120]), "+f"(d[121]), "+f"(d[122]), "+f"(d[123]), "+f"(d[124]), "+f"(d[125]), "+f"(d[126]), "+f"(d[127])
    : "l"(da), "l"(db), "r"(scale_d));
}
__device__ __forceinline__ void wgmma_rs_n128(float (&d)[64], const uint32_t* a, uint64_t db, int scale_d) {
  asm volatile("{\n.reg .pred p;\nsetp.ne.b32 p, %69, 0;\n"
    "wgmma.mma_async.sync.aligned.m64n128k16.f32.bf16.bf16 "
    "{%0, %1, %2, %3, %4, %5, %6, %7, %8, %9, %10, %11, %12, %13, %14, %15, "
    "%16, %17, %18, %19, %20, %21, %22, %23, %24, %25, %26, %27, %28, %29, %30, %31, "
    "%32, %33, %34, %35, %36, %37, %38, %39, %40, %41, %42, %43, %44, %45, %46, %47, "
    "%48, %49, %50, %51, %52, %53, %54, %55, %56, %57, %58, %59, %60, %61, %62, %63}, "
    "{%64, %65, %66, %67}, %68, p, 1, 1, 1;\n}\n"
    : "+f"(d[0]), "+f"(d[1]), "+f"(d[2]), "+f"(d[3]), "+f"(d[4]), "+f"(d[5]), "+f"(d[6]), "+f"(d[7]),
      "+f"(d[8]), "+f"(d[9]), "+f"(d[10]), "+f"(d[11]), "+f"(d[12]), "+f"(d[13]), "+f"(d[14]), "+f"(d[15]),
      "+f"(d[16]), "+f"(d[17]), "+f"(d[18]), "+f"(d[19]), "+f"(d[20]), "+f"(d[21]), "+f"(d[22]), "+f"(d[23]),
      "+f"(d[24]), "+f"(d[25]), "+f"(d[26]), "+f"(d[27]), "+f"(d[28]), "+f"(d[29]), "+f"(d[30]), "+f"(d[31]),
      "+f"(d[32]), "+f"(d[33]), "+f"(d[34]), "+f"(d[35]), "+f"(d[36]), "+f"(d[37]), "+f"(d[38]), "+f"(d[39]),
      "+f"(d[40]), "+f"(d[41]), "+f"(d[42]), "+f"(d[43]), "+f"(d[44]), "+f"(d[45]), "+f"(d[46]), "+f"(d[47]),
      "+f"(d[48]), "+f"(d[49]), "+f"(d[50]), "+f"(d[51]), "+f"(d[52]), "+f"(d[53]), "+f"(d[54]), "+f"(d[55]),
      "+f"(d[56]), "+f"(d[57]), "+f"(d[58]), "+f"(d[59]), "+f"(d[60]), "+f"(d[61]), "+f"(d[62]), "+f"(d[63])
    : "r"(a[0]), "r"(a[1]), "r"(a[2]), "r"(a[3]), "l"(db), "r"(scale_d));
}
__device__ __forceinline__ void wgmma_n64(float* d, uint64_t da, uint64_t db, int scale_d) {
  asm volatile("{\n.reg .pred p;\nsetp.ne.b32 p, %34, 0;\n"
    "wgmma.mma_async.sync.aligned.m64n64k16.f32.bf16.bf16 "
    "{%0, %1, %2, %3, %4, %5, %6, %7, %8, %9, %10, %11, %12, %13, %14, %15, "
    "%16, %17, %18, %19, %20, %21, %22, %23, %24, %25, %26, %27, %28, %29, %30, %31}, "
    "%32, %33, p, 1, 1, 0, 1;\n}\n"
    : "+f"(d[0]), "+f"(d[1]), "+f"(d[2]), "+f"(d[3]), "+f"(d[4]), "+f"(d[5]), "+f"(d[6]), "+f"(d[7]),
      "+f"(d[8]), "+f"(d[9]), "+f"(d[10]), "+f"(d[11]), "+f"(d[12]), "+f"(d[13]), "+f"(d[14]), "+f"(d[15]),
      "+f"(d[16]), "+f"(d[17]), "+f"(d[18]), "+f"(d[19]), "+f"(d[20]), "+f"(d[21]), "+f"(d[22]), "+f"(d[23]),
      "+f"(d[24]), "+f"(d[25]), "+f"(d[26]), "+f"(d[27]), "+f"(d[28]), "+f"(d[29]), "+f"(d[30]), "+f"(d[31])
    : "l"(da), "l"(db), "r"(scale_d));
}
__device__ __forceinline__ void wgmma_rs_n64(float* d, const uint32_t* a, uint64_t db, int scale_d) {
  asm volatile("{\n.reg .pred p;\nsetp.ne.b32 p, %37, 0;\n"
    "wgmma.mma_async.sync.aligned.m64n64k16.f32.bf16.bf16 "
    "{%0, %1, %2, %3, %4, %5, %6, %7, %8, %9, %10, %11, %12, %13, %14, %15, "
    "%16, %17, %18, %19, %20, %21, %22, %23, %24, %25, %26, %27, %28, %29, %30, %31}, "
    "{%32, %33, %34, %35}, %36, p, 1, 1, 1;\n}\n"
    : "+f"(d[0]), "+f"(d[1]), "+f"(d[2]), "+f"(d[3]), "+f"(d[4]), "+f"(d[5]), "+f"(d[6]), "+f"(d[7]),
      "+f"(d[8]), "+f"(d[9]), "+f"(d[10]), "+f"(d[11]), "+f"(d[12]), "+f"(d[13]), "+f"(d[14]), "+f"(d[15]),
      "+f"(d[16]), "+f"(d[17]), "+f"(d[18]), "+f"(d[19]), "+f"(d[20]), "+f"(d[21]), "+f"(d[22]), "+f"(d[23]),
      "+f"(d[24]), "+f"(d[25]), "+f"(d[26]), "+f"(d[27]), "+f"(d[28]), "+f"(d[29]), "+f"(d[30]), "+f"(d[31])
    : "r"(a[0]), "r"(a[1]), "r"(a[2]), "r"(a[3]), "l"(db), "r"(scale_d));
}

template <int BN> __device__ __forceinline__ void wgmma(float (&d)[BN / 2], uint64_t a, uint64_t b, int s) {
  if constexpr (BN == 128) wgmma_n128(d, a, b, s);
  else wgmma_n256(d, a, b, s);
}

template <int N> __device__ __forceinline__ void acc_fence(float* a) {
#pragma unroll
  for (int i = 0; i < N; i++) asm volatile("" : "+f"(a[i]) :: "memory");
}

#define SELECT8(a, f) do { \
  if ((a) & 4) { if ((a) & 2) { if ((a) & 1) f(7); else f(6); } else { if ((a) & 1) f(5); else f(4); } } \
  else { if ((a) & 2) { if ((a) & 1) f(3); else f(2); } else { if ((a) & 1) f(1); else f(0); } } } while (0)
__device__ __forceinline__ uint32_t opaque(uint32_t v) { asm volatile("" : "+r"(v)); return v; }
__device__ __forceinline__ uint32_t lane_now() { uint32_t l; asm volatile("mov.u32 %0, %%laneid;" : "=r"(l)); return l; }

struct Prod {
  uint32_t sb, n, tail, addr, pat, ready;
  uint32_t rank, flip; uint16_t mask;
  __device__ __forceinline__ void load_b(uint32_t dst, uint32_t half, const CUtensorMap* m, uint32_t mstep, uint32_t fb, int k, int ch, int cstep) {
    uint32_t h = rank;
    do { tma_ld3_mc(dst + h * half, ptr_add(m, h * mstep), fb, 0, k * 64, ch + h * cstep, mask); h ^= flip; } while (h != rank);
  }
  __device__ __forceinline__ void load_wide(const Params& P, int ffn, uint32_t dst, uint32_t fb, int k, int ch) {
    load_b(dst, PAGE, &P.map[ffn ? M_W1 : M_WKV], ffn ? 128 : 0, fb, k, ffn ? ch : ch + 16, ffn ? 0 : 16);
  }
  __device__ __forceinline__ void load_narrow(const Params& P, int ffn, uint32_t dst, uint32_t fb, int k, int j) {
    load_b(dst, 8192, &P.map[ffn ? M_W1H : M_WQ], ffn ? 128 : 0, fb, k, ffn ? 48 + j : 2 * j, ffn ? 0 : 1);
  }
  __device__ __forceinline__ void finish() {
#pragma unroll 1
    for (; tail < n; tail++) mbar_wait(sb + BAR_EMPTY + ((tail & 7) << 3), (tail >> 3) & 1);
  }
  template <int PAGES> __device__ __forceinline__ uint32_t acquire(uint32_t& fb) { return acquire_n(PAGES, fb); }
  __device__ __forceinline__ uint32_t acquire_n(uint32_t PAGES, uint32_t& fb) {
    uint32_t nw = pat & 3; pat = (pat >> 2) | 0x40000000u;
#pragma unroll 1
    for (; nw; nw--) { mbar_wait(sb + BAR_EMPTY + ((tail & 7) << 3), (tail >> 3) & 1); tail++; }
    ST(4, n);
    fb = sb + BAR_FULL + ((n & 7) << 3);
    mbar_expect_tx(fb, PAGES * PAGE);
    const uint32_t a = sb + addr;
    addr += PAGES * PAGE; if (addr >= NPAGE * PAGE) addr = 0;
    n++;
    return a;
  }
  const uint32_t* flag; uint32_t base, seen;
  __device__ __forceinline__ void acquire_fence() { asm volatile("fence.acquire.gpu;" ::: "memory"); fence_async_global(); }
  __device__ __forceinline__ void next() {
    uint32_t v, spins = 0;
    seen++;
    do { asm volatile("ld.acquire.cta.shared.u32 %0, [%1];" : "=r"(v) : "r"(sb + SM_SEEN) : "memory"); spin_check(++spins >> 4); } while (v < seen);
    fence_async_global();
  }
  __device__ __forceinline__ void need(uint32_t mask) {
    if ((ready & mask) != mask) {
      uint32_t spins = 0;
      do { ready = ld_relaxed(flag) - base; spin_check(++spins); } while ((ready & mask) != mask);
      acquire_fence();
    }
    ST(5, n - 1);
  }
};

struct Cons {
  uint32_t sb, n, off, prev;
  uint32_t ebar;
  uint32_t da0, db0;
  int lane;
  template <int PAGES> __device__ __forceinline__ void advance() {
    n++; off += PAGES << 10; if (off >= (NPAGE << 10)) off = 0;
    asm volatile("" : "+r"(n), "+r"(off));
  }
  template <int BN, int PAGES> __device__ __forceinline__ void step_ab(float (&acc)[BN / 2], uint32_t da, uint32_t db, int accumulate) {
    STA();
    mbar_wait_fast(sb + BAR_FULL + ((n & 7) << 3), (n >> 3) & 1);
    STB(n);
    const uint64_t da64 = desc64(da), db64 = desc64(db);
    wgmma_fence();
#pragma unroll
    for (int k = 0; k < 4; k++) wgmma<BN>(acc, da64 + 2 * k, db64 + 128 * k, k ? 1 : accumulate);
    wgmma_commit();
    wgmma_wait<1>();
    if (prev && lane < 2) mbar_arrive_cluster(ebar + prev);
    prev = 64 + ((n & 7) << 3);
    advance<PAGES>();
  }
  template <int BN> __device__ __forceinline__ void step(float (&acc)[BN / 2], int accumulate = 1) { step_ab<BN, BN / 128 + 1>(acc, da0 + off, db0 + 1024 + off, accumulate); }
  template <int BN> __device__ __forceinline__ void step_own(float (&acc)[BN / 2], uint32_t da, int accumulate) { step_ab<BN, BN / 128>(acc, da, db0 + off, accumulate); }
  __device__ __forceinline__ void wait_full(uint32_t i) { mbar_wait_fast(sb + BAR_FULL + (((n + i) & 7) << 3), ((n + i) >> 3) & 1); }
  template <int I, int N> __device__ __forceinline__ void issue_rs(float (&acc)[64], uint32_t (&a)[16], int accumulate = 1) {
    if (I == 0) { STA(); STB(n); }
    const uint64_t db64 = desc64(db0 + off) + 1024 * I;
    wgmma_fence();
#pragma unroll
    for (int k = 0; k < 4; k++) wgmma_rs_n128(acc, a + 4 * k, db64 + 128 * k, k ? 1 : accumulate);
    if (I == N - 1) {
      wgmma_commit();
      prev = 64 + ((n & 7) << 3);
      advance<N>();
    }
  }
  template <int BN> __device__ __forceinline__ void steps(float (&acc)[BN / 2], int cnt) {
#pragma unroll 1
    do { step<BN>(acc); } while (--cnt > 0);
  }
  __device__ __forceinline__ void skip3() { off += 3 << 10; if (off >= (NPAGE << 10)) off = 0; asm volatile("" : "+r"(off)); }
  __device__ __forceinline__ void steps_skip(float (&acc)[64], int at) {
    int i = 0;
#pragma unroll 1
    do { if (i == at) off += 2 << 10; step<128>(acc); } while (++i < 2);
  }
  __device__ __forceinline__ void drain() {
    wgmma_wait<0>();
    if (lane < 2) mbar_arrive_cluster(ebar + prev);
    prev = 0;
  }
};

#define MAPPING 2
__device__ __forceinline__ uint32_t role_of_sm(uint32_t smid) {
  const uint32_t t = smid >> 1;
  uint32_t q, i;
  if (t < 32) { q = t & 7; i = t >> 3; }
  else if (t < 60) { const uint32_t u = t - 32, d = (u * 37) >> 8; q = 1 + u - d * 7; i = 4 + d; }
  else if (t < 62) return 128 + smid - 120;
  else { q = 0; i = t - 58; }
  return (q * 2 + (smid & 1)) * 8 + i;
}

template <typename T> __device__ __forceinline__ T* scratch(const Params& P, uint32_t off) { return (T*)ptr_add(P.scratch, off); }
__device__ __forceinline__ uint32_t* epoch_ptr(const Params& P) { uint32_t b; asm volatile("mov.u32 %0, %%ctaid.x;" : "=r"(b)); return scratch<uint32_t>(P, G_EPOCH + b * 4u); }

__device__ __forceinline__ int o_chunk(int s, int j) { const int hf = s >= 9, m = s - 2 - 7 * hf; return s < 2 ? 2 * j + s : 2 * (m == j ? 7 : m) + hf; }

__device__ __forceinline__ void spare_role(const Params& P, uint32_t sb, int warp, int lane, uint32_t role, uint32_t rank) {
  const int j = role & 7;
  if (warp == 8) {
    if (elect_one()) {
#pragma unroll 1
      for (int i = 0; i < 8; i++) { mbar_init(sb + BAR_FULL + 8 * i, 1); mbar_init(sb + BAR_EMPTY + 8 * i, 16); }
      mbar_init(sb + BAR_XIN, 1);
      sts128(sb + SM_ROLE, role, 0, 0, 0);
      asm volatile("fence.mbarrier_init.release.cluster;\nfence.release.sync_restrict::shared::cta.cluster;" ::: "memory");
      fence_async_smem();
    }
    __syncwarp();
  }
  asm volatile("barrier.cluster.arrive.relaxed.aligned;\nbarrier.cluster.wait.acquire.aligned;" ::: "memory");
  if (warp == 8) {
    if (elect_one()) {
          Prod p; p.sb = sb; p.n = 0; p.tail = 0; p.addr = 0; p.rank = rank; p.flip = 1; p.mask = 1 << rank;
          uint32_t fb;
          p.pat = 0x55555000u;
#pragma unroll 1
          for (int r = -1; r < 7; r++) {
            const int ch = r < 0 ? 4 * j : ((r < 2 ? r : r == 2 ? 6 : r - 1) * 4 + j) * 2;
#pragma unroll 1
            for (int k = 0; k < 16; k++) { const uint32_t a = p.acquire<2>(fb); p.load_b(a, PAGE, &P.map[r < 0 ? M_WKV : M_W1], r < 0 ? 0 : 128, fb, k, ch, r < 0 ? 2 : 0); }
          }
          p.finish();
          mbar_expect_tx(sb + BAR_XIN, 4 * PAGE);
#pragma unroll 1
          for (int h = 0; h < 8; h++) tma_ld3(sb + h * 8192, &P.map[M_W2], sb + BAR_XIN, 0, (h >> 2) * 64, 4 * j + (h & 3));
          p.pat = 0x55555550u;
          const uint32_t full = (ld_relaxed(epoch_ptr(P)) + 1) * 255;
#pragma unroll 1
          for (int u = 0; u < 32; u++) {
            const uint32_t* f = scratch<uint32_t>(P, (u & 15) * G_BLOCK + G_FLAGS + ((u >> 4) * EV_N + EV_H0) * 128);
            uint32_t spins = 0;
            while (ld_relaxed(f) != full) { __nanosleep(200); spin_check(++spins); }
            p.acquire_fence();
            p.addr = (4 + 2 * (u & 1)) * PAGE;
            const uint32_t a = p.acquire<2>(fb);
            tma_ld3(a, &P.map[M_H_LD], fb, 0, u & 15, 0); tma_ld3(a + PAGE, &P.map[M_H_LD], fb, 64, u & 15, 0);
          }
    }
  } else if (warp < 8) {
      const int wg = warp >> 2;
      Cons c; c.sb = sb; c.n = 0; c.off = 0; c.prev = 0; c.lane = lane;
      c.ebar = mapa(sb + BAR_EMPTY - 64, rank);
      const uint32_t stage = sb + SM_STAGE + wg * PAGE, dstage = desc_lo(stage, 16);
      const uint32_t tag = ld_relaxed(epoch_ptr(P)) + 1;
      const int tid = threadIdx.x & 127;
#pragma unroll
      for (int i = 0; i < 4; i++) sts128(stage + (i * 128 + tid) * 16, 0x3f803f80u, 0x3f803f80u, 0x3f803f80u, 0x3f803f80u);
      fence_async_smem();
      bar_sync(2 + wg, 128);
      c.db0 = desc_lo(sb + wg * PAGE, 8192);
#pragma unroll 1
      for (int r = -1; r < 7; r++) {
        float acc[64];
#pragma unroll 1
        for (int k = 0; k < 16; k++) c.step_ab<128, 2>(acc, dstage, c.db0 + c.off, k);
        c.drain();
        acc_fence<64>(acc);
        {
          const uint32_t ca = sb + SM_STAGE + wg * PAGE + 8192 + (warp & 3) * 512;
          if (lane < 4) {
#pragma unroll
            for (int b = 0; b < 16; b++) asm volatile("st.shared.v2.f32 [%0], {%1, %2};" :: "r"(ca + b * 32 + lane * 8), "f"(acc[4 * b]), "f"(acc[4 * b + 1]) : "memory");
          }
          __syncwarp();
          float v;
          asm volatile("ld.shared.f32 %0, [%1];" : "=f"(v) : "r"(ca + tid * 4) : "memory");
          st_b128(scratch<uint4>(P, G_CS + (uint32_t)((r < 0 ? j * 256 + wg * 128 : 3 * DM + wg * FF + ((r < 2 ? r : r == 2 ? 6 : r - 1) * 4 + j) * 128) + tid) * 16u),
                  tagf(v, tag), tag & 15u, tag & 15u, tag & 15u);
        }
        __syncwarp();
      }
      c.da0 = desc_lo(sb + wg * 8192, 16); c.db0 = desc_lo(sb, 8192); c.off = 0;
      const uint32_t sa = sb + 10 * PAGE + warp * 8192;
      bar_sync(1, 256);
      mbar_wait_fast(sb + BAR_XIN, 0);
#pragma unroll 1
      for (int u = 0; u < 32; u++) {
        float acc[128];
        c.off = (4 + 2 * (u & 1)) << 10;
        c.wait_full(0);
        if (!(u & 15) && wg) bar_sync(6, 256);
        const uint64_t da = desc64(c.da0 + c.off), db = desc64(c.db0);
        wgmma_fence();
#pragma unroll
        for (int k = 0; k < 8; k++) wgmma<256>(acc, da + (k >> 2) * 1024 + (k & 3) * 2, db + (k >> 2) * 2048 + (k & 3) * 128, k);
        wgmma_commit();
        c.prev = 64 + ((c.n & 7) << 3);
        c.advance<2>();
        if (!(u & 15) && !wg) asm volatile("bar.arrive 6, 256;" ::: "memory");
        if (elect_one()) bulk_wait<0>();
        __syncwarp();
        c.drain();
        acc_fence<128>(acc);
#pragma unroll
        for (int hf = 0; hf < 2; hf++) {
#pragma unroll
          for (int i = 0; i < 8; i++) {
            const float* a = acc + 64 * hf + 8 * i;
            sts128(sa + hf * 4096 + i * 512 + lane * 16, pkt_head(pack_bf16(a[0], a[1])), pack_bf16(a[2], a[3]), pack_bf16(a[4], a[5]), pack_bf16(a[6], a[7]));
          }
          fence_async_smem();
          __syncwarp();
          if (elect_one()) {
            asm volatile("cp.async.bulk.global.shared::cta.bulk_group [%0], [%1], 4096;"
                         :: "l"(scratch<uint4>(P, (u & 15) * G_BLOCK + G_O + (2 * j + hf) * 32768u + warp * 4096u)), "r"(sa + hf * 4096) : "memory");
            bulk_commit();
          }
        }
      }
      if (elect_one()) bulk_wait<0>();
      __syncwarp();
      bar_sync(1, 256);
      if (threadIdx.x == 0) *epoch_ptr(P) = tag;
  }
}

__global__ void __cluster_dims__(2, 1, 1) __launch_bounds__(384, 1) fused_kernel(const __grid_constant__ Params P) {
  extern __shared__ __align__(1024) uint8_t smem_raw[];
  SP(0);
  const uint32_t sb = __shfl_sync(0xffffffffu, smem_u32(smem_raw), 0);
  const int warp = __shfl_sync(0xffffffffu, threadIdx.x >> 5, 0);
  const int lane = threadIdx.x & 31;
  if (warp == 7 && elect_one()) { prefetch_map(&P.map[M_XIN64]); prefetch_map(&P.map[M_WKV]); prefetch_map(&P.map[M_XIN]); }
  uint32_t role = blockIdx.x < 128 ? ((blockIdx.x >> 4) * 2 + (blockIdx.x & 1)) * 8 + ((blockIdx.x >> 1) & 7) : blockIdx.x;
  if (P.use_smid) { uint32_t smid; asm volatile("mov.u32 %0, %%smid;" : "=r"(smid)); role = role_of_sm(smid); }
  const bool spare = role >= 128;
  const int g = role >> 3, j = role & 7;
  uint32_t rank; asm("mov.u32 %0, %%cluster_ctarank;" : "=r"(rank));
  auto shared_b = [&]() {
    uint32_t peer;
    asm volatile("ld.shared::cluster.u32 %0, [%1];" : "=r"(peer) : "r"(mapa(sb + SM_ROLE, rank ^ 1)) : "memory");
    return peer < 128 && (peer & 7) == (uint32_t)j;
  };
  SP(1);

  if (__builtin_expect(spare, 0)) {
    spare_role(P, sb, warp, lane, role, rank);
  } else if (warp >= 8) {
    asm volatile("setmaxnreg.dec.sync.aligned.u32 40;");
    if (elect_one()) {
      if (warp == 8) {
#pragma unroll
        for (int i = 0; i < 6; i++) mbar_init(sb + BAR_FULL + 8 * i, 1);
        mbar_init(sb + BAR_XIN, 1);
      } else if (warp == 9) {
#pragma unroll
        for (int i = 0; i < 8; i++) mbar_init(sb + BAR_EMPTY + 8 * i, 16);
      } else if (warp == 10) {
#pragma unroll
        for (int i = 0; i < 4; i++) mbar_init(sb + BAR_SFULL + 8 * i, 4);
        mbar_init(sb + BAR_CLR, 1); mbar_init(sb + BAR_CLR2, 1); mbar_init(sb + BAR_FULL + 48, 1); mbar_init(sb + BAR_FULL + 56, 1);
      } else {
        sts128(sb + SM_ROLE, role, 0, 0, 0);
        mbar_init(sb + BAR_TAG, 1); mbar_init(sb + BAR_XFULL, 8); mbar_init(sb + BAR_CSE, 8);
        mbar_init(sb + BAR_SEMPTY, 1); mbar_init(sb + BAR_CSF, 1); mbar_init(sb + BAR_CSF + 8, 2);
      }
      asm volatile("fence.mbarrier_init.release.cluster;\nfence.release.sync_restrict::shared::cta.cluster;" ::: "memory");
      fence_async_smem();
    }
    __syncwarp();
    SP(2);
    asm volatile("barrier.cluster.arrive.relaxed.aligned;" ::: "memory");
    if (warp == 8) {
      if (elect_one()) {
        const int par = g & 1, row = (g >> 1) * 128;
        mbar_arrive(sb + BAR_FULL);
        {
          const int s = 1;
          const uint32_t xb = sb + BAR_XIN, fb = sb + BAR_FULL + 8;
          mbar_expect_tx(xb, PAGE); mbar_expect_tx(fb, 2 * PAGE);
#pragma unroll
          for (int h = 0; h < 2; h++) tma_ld3(sb + SM_STAGE + h * PAGE + s * 8192, &P.map[M_XIN64], xb, s * 64, par, row + h * 64);
#pragma unroll
          for (int h = 0; h < 2; h++) tma_ld3(sb + (2 * s + h) * PAGE, &P.map[M_WKV], fb, 0, s * 64, 16 + 16 * h + 2 * j);
        }
#pragma unroll 1
        for (int s = 0; s < 2; s++) {
          const uint32_t fb = sb + BAR_FULL + 16 + 8 * s;
          mbar_expect_tx(fb, PAGE);
          tma_ld3(sb + (4 + s) * PAGE, &P.map[M_WKV], fb, 0, s * 64, 2 * j);
        }
#pragma unroll 1
        for (int s = 0; s < 2; s++) {
          const uint32_t fb = sb + BAR_FULL + 32 + 8 * s, a = sb + (6 + 3 * s) * PAGE;
          const int k = (j == 1 ? 4 : 2) + s;
          mbar_expect_tx(fb, 3 * PAGE);
          tma_ld3(a, &P.map[M_XIN], fb, k * 64, par, row);
#pragma unroll
          for (int h = 0; h < 2; h++) tma_ld3(a + PAGE + h * PAGE, &P.map[M_WKV], fb, 0, k * 64, 16 + 16 * h + 2 * j);
        }
        spin_check((sb & 1023) << 22);
      }
      __syncwarp();
    }
    SP(3);
    asm volatile("barrier.cluster.wait.acquire.aligned;" ::: "memory");
    SP(4);
    if (warp == 8) {
      if (elect_one()) {
        Prod p; p.sb = sb; p.n = 0; p.tail = 0; p.ready = 0; p.addr = 0;
        { const bool mc = shared_b(); p.rank = rank; p.flip = !mc; p.mask = mc ? 3 : 1 << rank; }
        uint32_t fb;
        {
          p.seen = 0;
          const int xpar = g & 1, xrow = (g >> 1) * 128;
          SP(5);
#pragma unroll 1
          for (int hl = 0; hl < 4; hl++) {
            const int ffn = hl & 1;
            const CUtensorMap* xmap = &P.map[hl ? M_OUT_LD : M_XIN];
            if (hl) {
              p.pat = ffn ? Pat<3>::v : Pat<8>::v;
#pragma unroll 1
              for (int s = 0; s < 2; s++) { const uint32_t a = p.acquire<2>(fb); p.load_wide(P, ffn, a, fb, 2 * j + s, 2 * j); }
#pragma unroll 1
              for (int s = 0; s < 2; s++) { const uint32_t a = p.acquire<1>(fb); p.load_narrow(P, ffn, a, fb, 2 * j + s, j); }
            } else { p.pat = (Pat<0>::v >> 12) | 0x55500000u; p.addr = 0; p.n = 6; }
            if (hl == 0) SP(6);
            uint32_t fb0 = 0;
#pragma unroll 1
            for (int m = hl ? 0 : 2; m < 14; m++) {
              const int hf = m >= 7, mm = m - 7 * hf, jj = mm == j ? 7 : mm;
              int k = 2 * jj + hf;
              if (hl == 0) {
                const int pr = (m >> 1) + 1;
                k = 2 * (j && pr == 2 ? j : pr == j ? 2 : pr) + (m & 1);
              }
              const uint32_t a = p.acquire<3>(fb);
              p.load_wide(P, ffn, a + PAGE, fb, k, 2 * j);
              if (hl) {
                if (m == 0) { fb0 = fb; continue; }
                if (m == 1) {
                  const int j0 = j ? 0 : 7;
                  p.flag = scratch<uint32_t>(P, g * G_BLOCK + G_FLAGS + (ffn ? (hl >> 1) * EV_N + EV_XA : EV_XB) * 128);
                  p.ready = 0; p.need(1u << j0);
                  tma_ld3(a - 3 * PAGE, xmap, fb0, j0 * 128, xpar, xrow);
                }
                if (m < 7) p.need(1u << jj); else if (m == 7) p.next();
              }
              tma_ld3(a, xmap, fb, k * 64, xpar, xrow);
            }
            if (hl == 0) { mbar_wait(sb + BAR_TAG, 0); asm volatile("ld.shared.u32 %0, [%1];" : "=r"(p.base) : "r"(sb + SM_TAG) : "memory"); p.base = (p.base - 1) * 255; }
            p.pat = ffn ? Pat<4>::v : Pat<1>::v;
#pragma unroll 1
            for (int m = 0; m < 14; m++) {
              const int k = (m >> 1) == (hl ? j : 0) ? 14 + (m & 1) : m;
              if (ffn && m == 8) p.addr += 2 * PAGE;
              const uint32_t a = p.acquire<2>(fb);
              p.load_narrow(P, ffn, a + PAGE, fb, k, j);
              tma_ld3(a, xmap, fb, k * 64, xpar, xrow);
            }
            if (!ffn) {
              p.pat = Pat<2>::v;
              uint32_t a = 0;
#pragma unroll 1
              for (int s = 0; s < 16; s++) {
                if ((0x4925 >> s) & 1) a = p.acquire_n(s == 0 || s == 14 ? 2 : 3, fb); else a += PAGE;
                p.load_b(a, 8192, &P.map[M_WO], 0, fb, o_chunk(s, j), 2 * j, 1);
              }
              p.addr += 2 * PAGE;
              a = p.acquire<2>(fb);
              tma_ld3(a, xmap, fb, j * 128, xpar, xrow); tma_ld3(a + PAGE, xmap, fb, j * 128 + 64, xpar, xrow);
            } else {
              p.pat = Pat<5>::v;
#pragma unroll 1
              for (int s = 16; s < 48; s++) {
                const int pi = (s >> 1) & 7;
                if (s == 32) p.pat = Pat<6>::v;
                if ((s & 15) == WSKIP) { p.addr += 3 * PAGE; if (p.addr >= NPAGE * PAGE) p.addr = 0; }
                const int k = (s < 32 ? pi : pi == 4 ? j : pi == j ? 4 : pi) * 2 + (s & 1);
                const uint32_t a = p.acquire<3>(fb);
                p.load_wide(P, 1, a + PAGE, fb, k, (s & 48) + 2 * j);
                tma_ld3(a, xmap, fb, k * 64, xpar, xrow);
              }
              p.pat = Pat<7>::v;
#pragma unroll 1
              for (int q = 0; q < 4; q++) {
                p.next();
                const int k0 = q == 0 ? 2 : q == 1 ? 48 : q * 16 - 16, k1 = q == 1 ? 56 : (k0 & 48) + 16;
#pragma unroll 1
                for (int k = k0; k < k1; k++) {
                  const uint32_t a = p.acquire<2>(fb);
                  p.load_b(a + PAGE, 8192, &P.map[M_W2], 0, fb, k, 2 * j, 1);
                  tma_ld3(a, &P.map[M_H_LD], fb, k * 64, g, 0);
                }
              }
            }
            TL(2, 1 + hl);
          }
        }
        p.finish();
      }
    } else {
      mbar_wait(sb + BAR_XIN, 0);
      if (elect_one()) {
#pragma unroll 1
        for (int i = warp - 9; i < 8; i += 3) prefetch_l2(ptr_add(P.wqkv, (i * 128 + role) * 6144u + 2048u), 4096);
      }
      uint32_t tag;
      {
        const uint32_t part = warp - 9, col = DM + role * 16 + (lane & 1) * 8;
        const int cnt = part ? 21 : 22;
        const uint4* wp = ptr_add((const uint4*)P.wqkv, ((part ? 16 + part * 336 : 0) + (lane >> 1)) * 6144u + col * 2);
        float s[8] = {0, 0, 0, 0, 0, 0, 0, 0};
        uint4 v[4];
#pragma unroll
        for (int i = 0; i < 4; i++) v[i] = ld_relaxed4(wp + i * (16 * 6144 / 16));
        tag = ld_relaxed(epoch_ptr(P)) + 1;
        if (warp == 10 && lane == 0) { asm volatile("st.shared.u32 [%0], %1;" :: "r"(sb + SM_TAG), "r"(tag) : "memory"); mbar_arrive(sb + BAR_TAG); }
#pragma unroll 1
        for (int b = 4; b < 28; b += 4) {
          wp += 64 * 6144 / 16;
#pragma unroll
          for (int i = 0; i < 4; i++) {
            s[0] += bf_lo(v[i].x); s[1] += bf_hi(v[i].x); s[2] += bf_lo(v[i].y); s[3] += bf_hi(v[i].y);
            s[4] += bf_lo(v[i].z); s[5] += bf_hi(v[i].z); s[6] += bf_lo(v[i].w); s[7] += bf_hi(v[i].w);
            v[i] = make_uint4(0, 0, 0, 0);
            if (b + i < cnt) v[i] = __ldcg(wp + i * (16 * 6144 / 16));
          }
        }
#pragma unroll
        for (int e = 0; e < 4; e++) { const bool h = lane & 16; const float t = __shfl_xor_sync(0xffffffffu, h ? s[e] : s[e + 4], 16); s[e] = (h ? s[e + 4] : s[e]) + t; }
#pragma unroll
        for (int e = 0; e < 2; e++) { const bool h = lane & 8; const float t = __shfl_xor_sync(0xffffffffu, h ? s[e] : s[e + 2], 8); s[e] = (h ? s[e + 2] : s[e]) + t; }
        { const bool h = lane & 4; const float t = __shfl_xor_sync(0xffffffffu, h ? s[0] : s[1], 4); s[0] = (h ? s[1] : s[0]) + t; }
        s[0] += __shfl_xor_sync(0xffffffffu, s[0], 2);
        if (!(lane & 2) || part == 0) st_relaxed(scratch<uint32_t>(P, G_CS + (col + (lane >> 2)) * 16 + ((lane & 2) ? 3 : part) * 4), tagf((lane & 2) ? 0.f : s[0], tag));
        __syncwarp();
      }
      if (warp == 11 && lane == 0) TL(2, 30);
      {
        const uint32_t cspos = sb + SM_CS + ((lane & 16) + ((lane >> 1) & 3) * 4 + ((lane >> 3) & 1) * 2 + (lane & 1)) * 4;
#pragma unroll 1
        for (int it = 0; it < (warp == 10 ? 8 : 1); it++) {
          const int t = it & 3;
          if (it) mbar_wait(sb + BAR_CSE, (it - 1) & 1);
          if (t == 1) mbar_wait(sb + BAR_SEMPTY, 0);
#pragma unroll 1
          for (int b = it ? 0 : warp - 9; b < (it == 0 ? warp - 8 : t < 2 ? 3 : 2); b++) {
            uint32_t c0, c1;
            if (b < 2) { c0 = (t ? 2048 + t * 1024 + b * FF : 1024 + b * 1024) + j * 128; c1 = c0 + 64; }
            else if (t) { c0 = 6144 + j * 64; c1 = c0 + FF; }
            else { c0 = j * 128; c1 = c0 + 64; }
            const uint4* p0 = scratch<uint4>(P, G_CS + (c0 + lane) * 16u);
            const uint4* p1 = scratch<uint4>(P, G_CS + (c1 + lane) * 16u);
            uint4 v[4]; uint32_t spins = 0; bool ok;
            do {
              if (spins) __nanosleep(200);
              v[0] = ld_relaxed4(p0); v[1] = ld_relaxed4(p0 + 32); v[2] = ld_relaxed4(p1); v[3] = ld_relaxed4(p1 + 32);
              ok = tag_ok4(v[0], tag) && tag_ok4(v[1], tag) && tag_ok4(v[2], tag) && tag_ok4(v[3], tag);
              spin_check(++spins);
            } while (__any_sync(0xffffffffu, !ok));
#pragma unroll
            for (int m = 0; m < 4; m++) sts32f(cspos + b * 512 + m * 128, (untag(v[m].x) + untag(v[m].y)) + (untag(v[m].z) + untag(v[m].w)));
            __syncwarp();
            if (lane == 0) mbar_arrive(sb + BAR_CSF + (b ? 8 : 0));
          }
          if (lane == 0) { if (t >= 2) mbar_arrive(sb + BAR_CSF + 8); TL(2, 16 + it + (warp == 11 ? 8 : warp == 9 ? 9 : 0)); }
          if (t == 3) {
            if (g >= 2) {
              uint4* op = scratch<uint4>(P, G_HALO + (((it >> 2) * 16 + g - 2) * 8 + j) * 4096u + lane * 16u);
#pragma unroll 1
              for (int i = 0; i < 8; i++) { st_b128(op, 0, 0, 0, 0); op += 32; }
            }
          }
        }
      }
      if (warp == 11) {
        if (elect_one()) prefetch_l2(ptr_add(P.wo, role * 16384u), 16384);
        uint32_t* const fl = scratch<uint32_t>(P, g * G_BLOCK + G_FLAGS);
        uint32_t seen = 0;
#pragma unroll 1
        for (int e = EV_XA; e < EV_N + EV_XB; e++) {
          if (e == EV_XB) continue;
          const bool clr = (e & 7) == EV_XA;
          uint32_t* const f = ptr_add(fl, (clr ? 16 + e : e) * 128u);
          if (clr || (e & 7) == EV_H0) {
            uint4* op = scratch<uint4>(P, g * G_BLOCK + G_O + j * 32768u + lane * 16u);
#pragma unroll 1
            for (int i = 0; i < 64; i++) { st_b128(op, 0, 0, 0, 0); op += 32; if (e || (i & 1)) __nanosleep(10); }
            __syncwarp();
            if (lane == 0) { if (clr) red_release(f, 1u << j); else mbar_arrive(sb + BAR_CLR2); }
          }
          uint32_t spins = 0, m;
          while ((m = ld_relaxed(f) - (tag - 1) * 255) != 255) { __nanosleep(m ? 50 : 500); spin_check(++spins); }
          asm volatile("fence.acquire.gpu;" ::: "memory");
          if (lane == 0) {
            if (clr) mbar_arrive(sb + BAR_CLR);
            else asm volatile("st.release.cta.shared.u32 [%0], %1;" :: "r"(sb + SM_SEEN), "r"(++seen) : "memory");
          }
          if (e == EV_H3) {
#pragma unroll 1
            for (int i = 0; i < 7; i++) { if (elect_one()) prefetch_l2(ptr_add(P.w2, (i * 128 + role) * 8192u), 8192); __nanosleep(500); }
          }
          __syncwarp();
        }
      } else if (warp == 9) {
        if (elect_one()) {
          prefetch_map(&P.map[M_WQ]); prefetch_map(&P.map[M_OUT_LD]); prefetch_map(&P.map[M_WO]); prefetch_map(&P.map[M_W1 + rank]);
          prefetch_map(&P.map[M_H_ST]); prefetch_map(&P.map[M_H_LD]); prefetch_map(&P.map[M_W1H + rank]); prefetch_map(&P.map[M_W2]); prefetch_map(&P.map[M_OUT_ST]);
          uint32_t* fl = scratch<uint32_t>(P, g * G_BLOCK + G_FLAGS);
          int pe = 0;
#pragma unroll 1
          for (int e = 0; e < 2 * EV_N; e++) {
            const int q = e & 7;
            const bool is_h = q >= EV_H0 && q < EV_XB, last = e >= EV_N + EV_XB;
            const CUtensorMap* map = &P.map[is_h ? M_H_ST : M_OUT_ST];
            const int col = q == EV_H3 ? 3072 - 64 + j * 64 : (q == EV_H1 ? 1024 : q == EV_H2 ? 2048 : 0) + j * 128;
            const int row = is_h ? 0 : (g >> 1) * 128, par = is_h ? g : g & 1;
#pragma unroll 1
            for (int hb = is_h ? q == EV_H3 : q & 1; hb <= (is_h ? 1 : q & 1); hb++) {
#pragma unroll 1
              for (int w = 0; w < 2; w++) {
                const bool sw = last;
                const int wg = sw ? hb : w, h = sw ? w : hb, p = sw ? pe - hb + w : pe;
                mbar_wait(sb + BAR_SFULL + 16 * wg + 8 * (p & 1), (p >> 1) & 1);
                if (w == 0) TL(3, 20 + e);
                const uint32_t src = sb + (last ? 0 : SM_STAGE) + wg * PAGE + h * 8192;
                if (is_h) {
#pragma unroll 1
                  for (int r = 0; r < 64; r += H_ROWS) { tma_st3(map, src + r * 128, col + h * 64, par, wg * 64 + r); __nanosleep(60); }
                } else tma_st3(map, src, col + h * 64, par, row + wg * 64);
              }
              pe++;
            }
            bulk_commit();
            if (e != EV_N + EV_XB) bulk_wait<0>();
            TL(3, 40 + e);
            if (is_h || (q & 1)) mbar_arrive(sb + BAR_SEMPTY);
            if (q == EV_H0) mbar_wait(sb + BAR_CLR2, e >> 3);
            if (!last) red_release(fl, 1u << j);
            TL(3, e);
            fl += 32;
          }
          *epoch_ptr(P) = tag;
        }
      }
    }
  } else {
    {
      const uint32_t r = threadIdx.x >> 3, so = r * 128 + (((threadIdx.x ^ r) & 7) << 4);
      const uint8_t* xp = ptr_add((const uint8_t*)P.x, (2 * ((g >> 1) * 128 + r) + (g & 1)) * 2048u + (threadIdx.x & 7) * 16u);
      const uint8_t* wp = ptr_add((const uint8_t*)P.wqkv, r * 6144u + 2048u + j * 256u + (threadIdx.x & 7) * 16u);
#pragma unroll
      for (int i = 0; i < 4; i++) asm volatile("cp.async.cg.shared.global [%0], [%1], 16;" :: "r"(sb + SM_STAGE + (i >> 1) * PAGE + (i & 1) * 4096 + so), "l"(xp + i * 32 * 4096) : "memory");
#pragma unroll
      for (int q = 0; q < 8; q++) {
        const int i = (q & 3) * 2 + (q >> 2);
        asm volatile("cp.async.cg.shared.global [%0], [%1], 16;" :: "r"(sb + i * 4096 + so), "l"(wp + (i & 1) * 32 * 6144 + ((i >> 1) & 1) * 128 + (i >> 2) * 2048) : "memory");
      }
    }
    {
      if (warp == 0) asm volatile("prefetch.global.L2 [%0];" :: "l"(ptr_add(P.x, (2 * ((g >> 1) * 128 + j * 16 + (lane >> 1)) + (g & 1)) * 2048u + (lane & 1) * 128u)));
      else if (warp < 3 && (warp == 1 || lane < 16)) asm volatile("prefetch.global.L2 [%0];" :: "l"(ptr_add(P.wqkv, role * 6144u + (warp - 1) * 4096u + lane * 128u)));
      __syncwarp();
    }
    asm volatile("barrier.cluster.arrive.relaxed.aligned;" ::: "memory");
    asm volatile("setmaxnreg.inc.sync.aligned.u32 232;");
    SP(4);
    asm volatile("barrier.cluster.wait.acquire.aligned;" ::: "memory");
    SP(5);
    const int wg = warp >> 2;
    const int quad = lane & 3, gr = lane >> 2;
    Cons c; c.sb = sb; c.n = 0; c.off = 0; c.prev = 0; c.lane = lane;
    c.ebar = mapa(sb + BAR_EMPTY - 64, shared_b() ? lane & 1 : rank);
    const uint32_t stage = sb + SM_STAGE + wg * PAGE;
    const uint32_t dstage = desc_lo(stage, 16);
    {
    c.da0 = desc_lo(sb + wg * 8192, 16); c.db0 = desc_lo(sb, 8192);
    uint32_t sphase = 1, sfull = sb + BAR_SFULL + 16 * wg;
    const uint32_t maddr = stage + ((warp & 3) * 16 + (lane & 15)) * 128 + (((lane >> 4) ^ (lane & 7)) << 4);
    const uint32_t csaddr = sb + SM_CS + quad * 16;
    float st[8] = {0, 0, 0, 0, 0, 0, 0, 0};
    float* const mean = st; float* const rstd = st + 2;
    SP(6);

    auto stage_wait = [&]() { mbar_wait_fast(sb + BAR_SEMPTY, sphase); sphase ^= 1; };
    auto stage_publish = [&]() { fence_async_smem(); __syncwarp(); if (lane == 0) mbar_arrive(sfull); sfull ^= 8; };
    auto cs_load = [&](uint32_t (&cs)[16], int grp) {
#pragma unroll
      for (int i = 0; i < 4; i++) lds128(csaddr + grp * 256 + i * 64, cs[4 * i], cs[4 * i + 1], cs[4 * i + 2], cs[4 * i + 3]);
    };
    auto cs_apply = [&](float* acc, uint32_t (&cs)[16]) {
      acc_fence<32>(acc);
#pragma unroll
      for (int b = 0; b < 8; b++) {
        acc[4 * b] -= mean[0] * __uint_as_float(cs[2 * b]); acc[4 * b + 1] -= mean[0] * __uint_as_float(cs[2 * b + 1]);
        acc[4 * b + 2] -= mean[1] * __uint_as_float(cs[2 * b]); acc[4 * b + 3] -= mean[1] * __uint_as_float(cs[2 * b + 1]);
      }
      acc_fence<32>(acc);
    };
    auto glu_pair = [&](float g0, float g1, float u0, float u1, int r) {
      const float nl = -LOG2E * rstd[r], r2 = rstd[r] * rstd[r];
      return pack_bf16(g0 * u0 * r2 * rcp(1.0f + ex2(g0 * nl)), g1 * u1 * r2 * rcp(1.0f + ex2(g1 * nl)));
    };
    auto glu_slice = [&](uint32_t (&pk)[64], int i) {
      uint32_t hp[4];
#pragma unroll
      for (int e = 0; e < 4; e++) {
        asm volatile("" : "+r"(pk[4 * i + e]), "+r"(pk[32 + 4 * i + e]));
        const uint32_t pg = pk[4 * i + e], pu = pk[32 + 4 * i + e];
        hp[e] = glu_pair(bf_lo(pg), bf_hi(pg), bf_lo(pu), bf_hi(pu), e & 1);
      }
      stsm4((maddr ^ ((i & 3) << 5)) + (i >> 2) * 8192, hp[0], hp[1], hp[2], hp[3]);
    };
    auto glu_slice_acc = [&](float (&acc)[128], int i) {
      uint32_t hp[4];
      acc_fence<8>(acc + 8 * i);
#pragma unroll
      for (int e = 0; e < 4; e++) hp[e] = glu_pair(acc[8 * i + 2 * e], acc[8 * i + 2 * e + 1], acc[64 + 8 * i + 2 * e], acc[64 + 8 * i + 2 * e + 1], e & 1);
      stsm4((maddr ^ ((i & 3) << 5)) + (i >> 2) * 8192, hp[0], hp[1], hp[2], hp[3]);
    };
    auto stage_x = [&](uint32_t (&x)[32], int hf, uint32_t maddr) {
#pragma unroll
      for (int i = 4 * hf; i < 4 * hf + 4; i++) stsm4((maddr ^ ((i & 3) << 5)) + hf * 8192, x[4 * i], x[4 * i + 1], x[4 * i + 2], x[4 * i + 3]);
    };

    float acc[128];
    asm volatile("cp.async.wait_all;" ::: "memory");
    fence_async_smem();
    bar_sync(1, 256);
    SP(7);
    c.step_own<256>(acc, dstage, 0);
    mbar_wait_fast(sb + BAR_XIN, 0);
    SP(8);
#pragma unroll 1
    for (int hl = 0;; hl++) {
      int t = hl & 1;
      float acc2[64];
      uint32_t res[32];
      c.step_own<256>(acc, dstage + 512, 1);
#pragma unroll
      for (int s = 0; s < 2; s++) c.step_own<128>(acc2, dstage + s * 512, s);
#pragma unroll 1
      for (int s = 2; s < 11; s++) {
        const uint32_t apage = (c.off << 4) - (SM_STAGE + wg * 8192);
        if (s == 3 && wg) bar_sync(6, 256);
        c.step<256>(acc);
        if (s == 3 && !wg) asm volatile("bar.arrive 6, 256;" ::: "memory");
        int act = s;
        asm volatile("" : "+r"(act));
        auto get_tag = [&]() { uint32_t tag; asm volatile("ld.shared.u32 %0, [%1];" : "=r"(tag) : "r"(sb + SM_TAG) : "memory"); return tag; };
        const uint32_t stat_off = g * G_BLOCK + G_STATS + (hl * 128 + warp * 16) * 64u;
        auto stat_get = [&]() {
          const uint2* sp = scratch<uint2>(P, opaque(stat_off) + lane_now() * 16);
          const uint4 a = ld_relaxed4(sp), b = ld_relaxed4(sp + 64);
          st[0] = __uint_as_float(a.x); st[1] = __uint_as_float(a.y); st[2] = __uint_as_float(a.z); st[3] = __uint_as_float(a.w);
          st[4] = __uint_as_float(b.x); st[5] = __uint_as_float(b.y); st[6] = __uint_as_float(b.z); st[7] = __uint_as_float(b.w);
        };
        switch (act) {
          case 4: case 5: {
            const uint32_t ra = maddr + ((hl || j == 0) ? (s & 1) * 8192 : apage);
#pragma unroll
            for (int i = 0; i < 4; i++) {
              uint32_t v[4];
              ldsm4(ra ^ (i << 5), v[0], v[1], v[2], v[3]);
              if (i == 0 && s == 4) { st[0] = bf_lo(v[0]); st[1] = bf_lo(v[1]); st[2] = st[3] = st[4] = st[5] = 0; }
#pragma unroll
              for (int e = 0; e < 4; e++) {
                const float a = bf_lo(v[e]) - st[e & 1], b = bf_hi(v[e]) - st[e & 1];
                st[2 + (e & 1)] += a + b; st[4 + (e & 1)] += a * a; st[4 + (e & 1)] += b * b;
              }
            }
          } break;
          case 6: {
            mbar_wait_fast(sb + BAR_TAG, 0);
            const uint32_t tag = get_tag();
            float m[2], q[2];
#pragma unroll
            for (int r = 0; r < 2; r++) {
              const float mt = st[r] + st[2 + r] * (1.0f / 32);
              m[r] = mt + __shfl_xor_sync(0xffffffffu, mt, 1); m[r] += __shfl_xor_sync(0xffffffffu, m[r], 2); m[r] *= 0.25f;
              q[r] = st[4 + r] - st[2 + r] * st[2 + r] * (1.0f / 32) + 32.0f * (mt - m[r]) * (mt - m[r]);
            }
#pragma unroll
            for (int o = 1; o < 4; o <<= 1) { q[0] += __shfl_xor_sync(0xffffffffu, q[0], o); q[1] += __shfl_xor_sync(0xffffffffu, q[1], o); }
            const uint32_t l = lane_now();
            uint2* sp = scratch<uint2>(P, opaque(stat_off + j * 8) + (l >> 2) * 64 + (l & 1) * 512);
            if (!(l & 2)) st_relaxed2(sp, tagf(l & 1 ? m[1] : m[0], tag), tagf(l & 1 ? q[1] : q[0], tag));
          } break;
          case 8: stat_get(); break;
          case 10: {
            const uint32_t tag = get_tag();
            uint32_t spins = 0;
            for (;;) {
              uint32_t bad = 0;
#pragma unroll
              for (int i = 0; i < 8; i++) bad |= __float_as_uint(st[i]) ^ tag;
              if (!__any_sync(0xffffffffu, bad & 15u)) break;
              stat_get(); spin_check(++spins);
            }
            float mr[4];
#pragma unroll
            for (int r = 0; r < 2; r++) {
              const float m0 = untag(__float_as_uint(st[4 * r])), m1 = untag(__float_as_uint(st[4 * r + 2]));
              float m = m0 + m1; m += __shfl_xor_sync(0xffffffffu, m, 1); m += __shfl_xor_sync(0xffffffffu, m, 2); m *= 0.125f;
              float q = untag(__float_as_uint(st[4 * r + 1])) + untag(__float_as_uint(st[4 * r + 3])) + 128.0f * ((m0 - m) * (m0 - m) + (m1 - m) * (m1 - m));
              q += __shfl_xor_sync(0xffffffffu, q, 1); q += __shfl_xor_sync(0xffffffffu, q, 2);
              mr[r] = m; mr[2 + r] = rsqrtf(fmaxf(q, 0.f) * (1.0f / DM) + LN_EPS);
            }
            st[0] = mr[0]; st[1] = mr[1]; st[2] = mr[2]; st[3] = mr[3];
          } break;
          default: break;
        }
      }
#pragma unroll 1
      for (;;) {
      const int it = (hl >> 1) * 4 + t;
#pragma unroll
      for (int s = 0; s < 4; s++) {
        uint32_t cs[16];
        if (WSKIP == 11 + s && t >= 2) c.skip3();
        c.step<256>(acc);
        if (!(s & 1)) mbar_wait_fast(sb + BAR_CSF + 4 * s, t & 1);
        if (s >= 2 && t <= 1) { cs_load(cs, 2 + s); cs_apply(acc2 + 32 * (s - 2), cs); }
        cs_load(cs, s);
        c.drain();
        cs_apply(acc + 32 * s, cs);
      }
      if (WSKIP == 15 && t >= 2) c.skip3();
      c.step<256>(acc);
      if (lane == 0) mbar_arrive(sb + BAR_CSE);
      c.drain();
      acc_fence<128>(acc);
      TLC(1 + it * 6);
      uint32_t pkB[64];
      if (t == 2) {
#pragma unroll
        for (int i = 0; i < 64; i++) pkB[i] = pack_bf16(acc[2 * i], acc[2 * i + 1]);
      } else if (t == 0) {
        uint32_t pkA[64];
        auto kv_pack = [&](int v, int r) {
#pragma unroll
          for (int i = 32 * v + r; i < 32 * v + 32; i += 2) { acc_fence<2>(acc + 2 * i); pkA[i] = pack_bf16(acc[2 * i] * rstd[r], acc[2 * i + 1] * rstd[r]); }
        };
        const uint32_t l16 = lane_now() * 16u;
        uint4* const xs = ptr_add((uint4*)smem_raw, SM_STAGE + l16);
        uint4* const hp = scratch<uint4>(P, G_HALO + (((hl >> 1) * 16 + g) * 8 + j) * 4096u + l16);
        {
          uint4* const dst = (warp == 7 && g < 14) ? hp : ptr_add(xs, warp * 4096u);
#pragma unroll
          for (int s = 0; s < 2; s++) {
            c.steps<128>(acc2, s ? 2 : 1 + wg);
            if (s == 0) stage_wait();
            kv_pack(s, 1);
#pragma unroll
            for (int i = 4 * s; i < 4 * s + 4; i++) { pkA[8 * i + 1] = pkt_head(pkA[8 * i + 1]); gen_store(dst + i * 32, pkA[8 * i + 1], pkA[8 * i + 3], pkA[8 * i + 5], pkA[8 * i + 7]); }
          }
        }
        __syncwarp();
        if (lane == 0) mbar_arrive(sb + BAR_XFULL);
#pragma unroll
        for (int s = 0; s < 2; s++) {
          c.steps<128>(acc2, 2);
#pragma unroll
          for (int i = 33 - s; i < 64; i += 2) pkA[i] = movm(pkA[i]);
          kv_pack(1 - s, 0);
        }
        uint32_t kvH[32];
        {
          const uint4* const src = (warp == 0 && g >= 2) ? hp - 2 * 8 * 256 : ptr_add(xs, (warp ? warp - 1 : 0) * 4096u);
          c.steps<128>(acc2, 2);
          mbar_wait_fast(sb + BAR_XFULL, hl >> 1);
#pragma unroll
          for (int i = 0; i < 8; i++) gen_load(src + i * 32, kvH + 4 * i);
          c.steps<128>(acc2, 3 - wg);
          uint32_t spins = 0;
          while (__any_sync(0xffffffffu, !(kvH[0] && kvH[4] && kvH[8] && kvH[12] && kvH[16] && kvH[20] && kvH[24] && kvH[28]))) {
#pragma unroll
            for (int i = 0; i < 8; i++) gen_load(src + i * 32, kvH + 4 * i);
            spin_check(++spins);
          }
        }
#pragma unroll
        for (int i = 16; i < 32; i++) kvH[i] = movm(kvH[i]);
        mbar_wait_fast(sb + BAR_CLR, hl >> 1);
        c.steps<128>(acc2, 2);
        AP(0);
        c.wait_full(0);
        AP(1);
        c.drain();
        AP(2);
        acc_fence<64>(acc2);
        TLC(2 + it * 6);
        uint32_t q[32];
#pragma unroll
        for (int i = 0; i < 32; i++) q[i] = pack_bf16(acc2[2 * i], acc2[2 * i + 1]);
        const uint32_t zm = bar_sync_zero(1, 256);
        AP(3);
        uint32_t ob[6][16];
        uint4* const omail = scratch<uint4>(P, g * G_BLOCK + G_O + warp * 2048u + l16);
        float o2[8][4], r2[4];
        {
          const float hv = (warp == 0 && g < 2) ? -INFINITY : 0.f;
          const float hinit[4] = {hv, hv, hv, hv};
          const bool c0 = (2 * quad <= gr), c1 = (2 * quad + 1 <= gr);
          const uint32_t lm = (c0 ? 0xffffu : 0u) | (c1 ? 0xffff0000u : 0u);
          const float sc[2] = {rstd[0] * (0.17677669529663687f * LOG2E), rstd[1] * (0.17677669529663687f * LOG2E)};
          float lg[4][4], mx[4][2];
#pragma unroll
          for (int h = 0; h < 4; h++) {
            const int b = h * 4;
            float sH[4], sL[4], sU[4];
            q[2 * b] |= zm;
            mma16816(sH, q[2 * b], q[2 * b + 1], q[2 * b + 2], q[2 * b + 3], kvH[b], kvH[b + 1], hinit);
            mma16816z(sL, q[2 * b], q[2 * b + 1], q[2 * b + 2], q[2 * b + 3], pkA[2 * b], pkA[2 * b + 2]);
            mma16816z(sU, q[2 * b], q[2 * b + 1], q[2 * b + 2], q[2 * b + 3], pkA[2 * b + 1], pkA[2 * b + 3]);
            mma16816(sH, q[2 * b + 4], q[2 * b + 5], q[2 * b + 6], q[2 * b + 7], kvH[b + 2], kvH[b + 3], sH);
            mma16816(sL, q[2 * b + 4], q[2 * b + 5], q[2 * b + 6], q[2 * b + 7], pkA[2 * b + 4], pkA[2 * b + 6], sL);
            mma16816(sU, q[2 * b + 4], q[2 * b + 5], q[2 * b + 6], q[2 * b + 7], pkA[2 * b + 5], pkA[2 * b + 7], sU);
            lg[h][0] = c0 ? sL[0] : sH[0]; lg[h][1] = c1 ? sL[1] : sH[1]; lg[h][2] = c0 ? sU[2] : sL[2]; lg[h][3] = c1 ? sU[3] : sL[3];
            mx[h][0] = fmaxf(lg[h][0], lg[h][1]); mx[h][1] = fmaxf(lg[h][2], lg[h][3]);
          }
#pragma unroll
          for (int o = 1; o < 4; o <<= 1) {
#pragma unroll
            for (int i = 0; i < 8; i++) mx[i >> 1][i & 1] = fmaxf(mx[i >> 1][i & 1], __shfl_xor_sync(0xffffffffu, mx[i >> 1][i & 1], o));
          }
          AP(4);
          uint32_t z = zm, pp[4][2];
          float rs[4][2];
          auto probs = [&](int h) {
            pp[h][0] = pack_bf16(ex2((lg[h][0] - mx[h][0]) * sc[0]), ex2((lg[h][1] - mx[h][0]) * sc[0]));
            pp[h][1] = pack_bf16(ex2((lg[h][2] - mx[h][1]) * sc[1]), ex2((lg[h][3] - mx[h][1]) * sc[1]));
            float sum[4];
            mma1688z(sum, pp[h][0], pp[h][1], 0x3f803f80u);
            rs[h][0] = rcp(sum[0]); rs[h][1] = rcp(sum[2]);
            asm volatile("" : "+f"(rs[h][0]), "+f"(rs[h][1]));
          };
          probs(0); probs(1); probs(2); probs(3);
#pragma unroll
          for (int hf = 0; hf < 2; hf++) {
#pragma unroll
            for (int hh = 0; hh < 2; hh++) {
              const int h = hf * 2 + hh, b = h * 4;
              const uint32_t pa = pp[h][0], pb = pp[h][1];
              const uint32_t p0 = pa & ~lm, p1 = pa & z, p2 = pa & lm, p3 = pb & ~lm, p4 = pb & z, p5 = pb & lm;
              const float ra = rs[h][0], rb = rs[h][1];
#pragma unroll
              for (int d = 0; d < 4; d++) {
                float o[4];
                mma16816z(o, p0, p1, p2, p3, kvH[16 + b + d], pkA[32 + 2 * (b + d)]);
                mma1688(o, p4, p5, pkA[32 + 2 * (b + d) + 1], o);
                if (hf == 0) { ob[0][(hh * 4 + d) * 2] = pack_bf16(o[0] * ra, o[1] * ra); ob[0][(hh * 4 + d) * 2 + 1] = pack_bf16(o[2] * rb, o[3] * rb); }
                else { o2[hh * 4 + d][0] = o[0]; o2[hh * 4 + d][1] = o[1]; o2[hh * 4 + d][2] = o[2]; o2[hh * 4 + d][3] = o[3]; }
              }
              if (hf) { r2[2 * hh] = ra; r2[2 * hh + 1] = rb; }
            }
            if (hf == 0) {
#pragma unroll
              for (int i = 0; i < 4; i++) ob[0][4 * i] = pkt_head(ob[0][4 * i]);
              AP(5);
              uint4* op = scratch<uint4>(P, opaque(g * G_BLOCK + G_O + j * 32768u + warp * 2048u) + l16);
#pragma unroll
              for (int i = 0; i < 4; i++) st_b128(op + i * 32, ob[0][4 * i], ob[0][4 * i + 1], ob[0][4 * i + 2], ob[0][4 * i + 3]);
              z = late_zero(zm);
              AP(6);
            }
          }
        }
        auto finish_o2 = [&](uint32_t z) {
#pragma unroll
          for (int i = 0; i < 4; i++) r2[i] = __uint_as_float(__float_as_uint(r2[i]) | z);
#pragma unroll
          for (int i = 0; i < 8; i++) {
            ob[1][2 * i] = pack_bf16(o2[i][0] * r2[(i >> 2) * 2], o2[i][1] * r2[(i >> 2) * 2]);
            ob[1][2 * i + 1] = pack_bf16(o2[i][2] * r2[(i >> 2) * 2 + 1], o2[i][3] * r2[(i >> 2) * 2 + 1]);
          }
#pragma unroll
          for (int i = 0; i < 4; i++) { ob[1][4 * i] = pkt_head(ob[1][4 * i]); sts128(stage + (warp & 3) * 2048 + i * 512 + l16, ob[1][4 * i], ob[1][4 * i + 1], ob[1][4 * i + 2], ob[1][4 * i + 3]); }
        };
        {
          uint32_t dep = __float_as_uint(r2[0]) | __float_as_uint(r2[2]);
#pragma unroll
          for (int i = 0; i < 8; i++) dep |= __float_as_uint(o2[i][3]);
          const uint32_t cnt = 256 | (dep & zm);
          AP(7);
          if (wg) { asm volatile("bar.arrive 1, %0;" :: "r"(cnt) : "memory"); bar_sync(6, 256); } else bar_sync(1, cnt);
        }
        TLC(3 + it * 6);
        AP(8);
        uint64_t todo;
        { const uint32_t o7 = 0x6543210u | (7u << (4 * j) & 0xfffffffu); todo = (uint64_t)(o7 * 2) | (uint64_t)(o7 * 2 + 0x1111111u) << 28; }
        const uint4* pf[3];
        auto next_ptrs = [&](const uint4* (&p)[3]) {
#pragma unroll
          for (int i = 0; i < 3; i++) p[i] = ptr_add(omail, (((uint32_t)todo >> (4 * i)) & 15u) << 14);
          asm volatile("" : "+l"(p[0]), "+l"(p[1]), "+l"(p[2]));
          todo >>= 12;
        };
        next_ptrs(pf);
        auto batch = [&](int b, bool first, bool three) {
          const int y = 3 - b;
          auto o_fetch = [&]() {
#pragma unroll
            for (int i = 0; i < 8; i++) pkt_load(pf[i >> 2] + (i & 3) * 32, ob[y + (i >> 2)] + 4 * (i & 3));
            if (three) {
#pragma unroll
              for (int i = 0; i < 4; i++) pkt_load(pf[2] + i * 32, ob[y + 2] + 4 * i);
            }
          };
          if (first) {
            c.issue_rs<0, 2>(acc2, ob[0], 0);
            finish_o2(late_zero(zm));
            o_fetch();
            c.issue_rs<1, 2>(acc2, ob[1]);
            if (!wg) asm volatile("bar.arrive 6, 256;" ::: "memory");
          } else {
            o_fetch();
            c.issue_rs<0, 3>(acc2, ob[b]); c.issue_rs<1, 3>(acc2, ob[b + 1]); c.issue_rs<2, 3>(acc2, ob[b + 2]);
          }
          const uint32_t z = late_zero(zm);
          const uint4* pn[3];
          next_ptrs(pn);
          c.wait_full(0);
          uint32_t spins = 0;
          for (;;) {
            bool bad[3];
#pragma unroll
            for (int i = 0; i < 3; i++) bad[i] = ob[y + i][0] == z || ob[y + i][4] == z || ob[y + i][8] == z || ob[y + i][12] == z;
            if (__builtin_expect(!__any_sync(0xffffffffu, bad[0] | bad[1] | bad[2]), 1)) break;
            o_fetch();
            spin_check(++spins);
          }
          if (first) {
            fence_async_smem();
            __syncwarp();
            if (elect_one()) {
              asm volatile("cp.async.bulk.global.shared::cta.bulk_group [%0], [%1], 2048;"
                           :: "l"(scratch<uint4>(P, g * G_BLOCK + G_O + (2 * j + 1) * 16384u + warp * 2048u)), "r"(stage + (warp & 3) * 2048) : "memory");
              bulk_commit();
            }
          }
          pf[0] = pn[0]; pf[1] = pn[1]; pf[2] = pn[2];
          c.drain();
        };
        batch(0, true, true);
#pragma unroll 1
        for (int i = 0; i < 2; i++) { batch(3, false, true); batch(0, false, i == 0); }
        c.issue_rs<0, 2>(acc2, ob[3]); c.issue_rs<1, 2>(acc2, ob[4]);
        if (elect_one()) bulk_wait<0>();
        __syncwarp();
        {
          c.off += 2 << 10;
          c.wait_full(0);
          const uint32_t ra = maddr - (SM_STAGE + wg * 8192) + (c.off << 4);
#pragma unroll
          for (int i = 0; i < 8; i++) ldsm4((ra ^ ((i & 3) << 5)) + (i >> 2) * PAGE, res[4 * i], res[4 * i + 1], res[4 * i + 2], res[4 * i + 3]);
          if (lane < 2) mbar_arrive_cluster(c.ebar + 64 + ((c.n & 7) << 3));
          c.advance<2>();
          c.drain();
        }
        break;
      } else {
        c.steps<128>(acc2, 1 + wg);
        stage_wait();
        glu_slice_acc(acc, 0);
#pragma unroll
        for (int s = 1; s < 8; s++) {
          if (s == 5) c.steps_skip(acc2, t == 1 ? 1 - wg : 2); else c.steps<128>(acc2, (s & 1) || t == 3 ? 2 : 1);
          if (s == 4) stage_publish();
          glu_slice_acc(acc, s);
        }
        c.steps<128>(acc2, 2 - wg);
        stage_publish();
        if (t == 3) {
#pragma unroll
          for (int i = 0; i < 32; i++) res[i] = (i & 3) ? __float_as_uint(acc[i]) : 0;
#pragma unroll 1
          for (int i = 0; i < 4; i++) {
            c.steps<128>(acc2, i == 0 ? RES_AT + wg : i == 1 ? 4 : i == 2 ? 33 - RES_AT - TAIL_LAG - wg : TAIL_LAG);
            if (i < 2) {
              const uint4* rp = scratch<uint4>(P, opaque(g * G_BLOCK + G_O + j * 32768u + warp * 4096u) + lane_now() * 16u);
              uint32_t spins = 0;
              while (__any_sync(0xffffffffu, !(res[0] && res[4] && res[8] && res[12] && res[16] && res[20] && res[24] && res[28]))) {
#pragma unroll
                for (int q = 0; q < 8; q++) pkt_load(rp + q * 32, res + 4 * q);
                if (i == 0) break;
                spin_check(++spins);
              }
            } else if (hl == 3) {
              if (wg == 1 && i == 2) c.drain();
              if (wg + i == 3) bar_sync(5, 256);
            }
          }
          stage_wait();
          c.drain();
          break;
        }
        c.drain();
        TLC(2 + it * 6);
        c.step<256>(acc, 0);
        acc_fence<64>(acc2);
#pragma unroll
        for (int i = 0; i < 16; i++) {
          pkB[16 + i] = pack_bf16(acc2[2 * i], acc2[2 * i + 1]); pkB[48 + i] = pack_bf16(acc2[32 + 2 * i], acc2[32 + 2 * i + 1]);
          pkB[i] = 0; pkB[32 + i] = 0;
        }
      }
      t++;
#pragma unroll 1
      for (int s = 3 - t; s < 8; s++) {
        c.step<256>(acc, s);
        int act = (t == 3 || s >= 4) ? s : 8;
        asm volatile("" : "+r"(act));
        if (act < 8) {
          if (!(act & 3)) { if (act && t == 3) stage_publish(); else stage_wait(); }
          auto f = [&](int i) { glu_slice(pkB, i); };
          SELECT8(act, f);
        }
      }
#pragma unroll
      for (int s = 0; s < 2; s++) {
        const uint32_t ra = maddr - (SM_STAGE + wg * 8192) + (c.off << 4);
        c.step<256>(acc);
        if (s == 0) stage_publish();
#pragma unroll
        for (int i = 0; i < 4; i++) {
          uint32_t v[4];
          ldsm4(ra ^ (i << 5), v[0], v[1], v[2], v[3]);
#pragma unroll
          for (int e = 0; e < 4; e++) { acc2[32 * s + 8 * i + 2 * e] = bf_lo(v[e]); acc2[32 * s + 8 * i + 2 * e + 1] = bf_hi(v[e]); }
        }
        acc_fence<32>(acc2 + 32 * s);
      }
      if (WSKIP == 10) c.skip3();
      c.step<256>(acc);
      }
      const int it = (hl >> 1) * 4 + t;
      acc_fence<64>(acc2);
      TLC(4 + it * 6);
      uint32_t xn[32];
#pragma unroll
      for (int i = 0; i < 16; i++) xn[i] = add_bf16x2(res[i], pack_bf16(acc2[2 * i], acc2[2 * i + 1]));
      const uint32_t xaddr = hl == 3 ? maddr - SM_STAGE : maddr;
      stage_x(xn, 0, xaddr);
#pragma unroll
      for (int i = 16; i < 32; i++) { xn[i] = add_bf16x2(res[i], pack_bf16(acc2[2 * i], acc2[2 * i + 1])); asm volatile("" : "+r"(xn[i])); }
      stage_publish();
      if (hl == 3) { stage_x(xn, 1, xaddr); stage_publish(); TLE(47); TLG(63); break; }
      bar_sync(2 + wg, 128);
      TLC(5 + it * 6);
      c.step_own<256>(acc, dstage, 0);
      stage_x(xn, 1, maddr);
      stage_publish();
      bar_sync(2 + wg, 128);
    }
    }
  }
}

typedef CUresult (*EncodeFn)(CUtensorMap*, CUtensorMapDataType, cuuint32_t, void*, const cuuint64_t*, const cuuint64_t*, const cuuint32_t*,
                             const cuuint32_t*, CUtensorMapInterleave, CUtensorMapSwizzle, CUtensorMapL2promotion, CUtensorMapFloatOOBfill);

void encode(EncodeFn fn, CUtensorMap* m, const void* ptr, int rank, const cuuint64_t* dims, const cuuint64_t* strides, const cuuint32_t* box) {
  cuuint32_t es[5] = {1, 1, 1, 1, 1};
  fn(m, CU_TENSOR_MAP_DATA_TYPE_BFLOAT16, rank, const_cast<void*>(ptr), dims, strides, box, es, CU_TENSOR_MAP_INTERLEAVE_NONE,
     CU_TENSOR_MAP_SWIZZLE_128B, CU_TENSOR_MAP_L2_PROMOTION_L2_128B, CU_TENSOR_MAP_FLOAT_OOB_FILL_NONE);
}

}

extern "C" void kernel_launch(void* const* d_in, const int* in_sizes, int n_in, void* d_out, int out_size) {
  const __nv_bfloat16* x = (const __nv_bfloat16*)d_in[0];
  const __nv_bfloat16* wqkv = (const __nv_bfloat16*)d_in[1];
  const __nv_bfloat16* wo = (const __nv_bfloat16*)d_in[2];
  const __nv_bfloat16* w1 = (const __nv_bfloat16*)d_in[4];
  const __nv_bfloat16* w3 = (const __nv_bfloat16*)d_in[5];
  const __nv_bfloat16* w2 = (const __nv_bfloat16*)d_in[6];

  void* fnp = nullptr; cudaDriverEntryPointQueryResult qr;
  cudaGetDriverEntryPoint("cuTensorMapEncodeTiled", &fnp, cudaEnableDefault, &qr);
  EncodeFn fn = (EncodeFn)fnp;
  void* sym;
  cudaGetSymbolAddress(&sym, g_scratch);
  uint8_t* scr = (uint8_t*)(((uintptr_t)sym + G_PAGE - 1) / G_PAGE * G_PAGE);

  Params P = {};
  { cuuint64_t d[3] = {DM, 2, SEQ / 2}, s[2] = {DM * 2, DM * 4}; cuuint32_t b[3] = {64, 1, 128}, b2[3] = {64, 1, 64};
    encode(fn, &P.map[M_XIN], x, 3, d, s, b); encode(fn, &P.map[M_XIN64], x, 3, d, s, b2);
    encode(fn, &P.map[M_OUT_LD], d_out, 3, d, s, b); encode(fn, &P.map[M_OUT_ST], d_out, 3, d, s, b2); }
  { cuuint64_t d[3] = {FF, 16, 128}, s[2] = {G_BLOCK, FF * 2}; cuuint32_t b[3] = {64, 1, 128}, b2[3] = {64, 1, H_ROWS};
    encode(fn, &P.map[M_H_LD], scr + G_H, 3, d, s, b); encode(fn, &P.map[M_H_ST], scr + G_H, 3, d, s, b2); }
  { const cuuint32_t b2[3] = {64, 64, 2}, b1[3] = {64, 64, 1};
    { cuuint64_t d[3] = {64, DM, 48}, s[2] = {3 * DM * 2, 128}; encode(fn, &P.map[M_WKV], wqkv, 3, d, s, b2); encode(fn, &P.map[M_WQ], wqkv, 3, d, s, b1); }
    { cuuint64_t d[3] = {64, DM, 16}, s[2] = {DM * 2, 128}; encode(fn, &P.map[M_WO], wo, 3, d, s, b1); }
    { cuuint64_t d[3] = {64, FF, 16}, s[2] = {DM * 2, 128}; encode(fn, &P.map[M_W2], w2, 3, d, s, b1); }
    { cuuint64_t d[3] = {64, DM, FF / 64}, s[2] = {FF * 2, 128};
      encode(fn, &P.map[M_W1], w1, 3, d, s, b2); encode(fn, &P.map[M_W3], w3, 3, d, s, b2);
      encode(fn, &P.map[M_W1H], w1, 3, d, s, b1); encode(fn, &P.map[M_W3H], w3, 3, d, s, b1); }
  }
  P.scratch = scr; P.x = x; P.wqkv = wqkv; P.wo = wo; P.w2 = w2;
  int dev = 0, sms = 0;
  cudaGetDevice(&dev);
  cudaDeviceGetAttribute(&sms, cudaDevAttrMultiProcessorCount, dev);
  P.use_smid = (sms == 132);
  cudaFuncSetAttribute(fused_kernel, cudaFuncAttributeMaxDynamicSharedMemorySize, SM_ALLOC);
  fused_kernel<<<132, 384, SM_ALLOC>>>(P);
}
```
